```python
import torch

def _softmax(x, axis=-1):
    return torch.softmax(x, dim=axis)

def _gelu(x):
    return torch.nn.functional.gelu(x, approximate='tanh')

def _silu(x):
    return torch.nn.functional.silu(x)

def _sigmoid(x):
    return torch.sigmoid(x)

def _layernorm(x, axis=-1, eps=1e-05):
    m = x.mean(dim=axis, keepdim=True)
    v = x.var(dim=axis, keepdim=True, unbiased=False)
    return (x - m) / torch.sqrt(v + eps)

def _scatter_add(tgt, idx, src, axis=0):
    return tgt.clone().index_add_(axis, idx, src)

def _segment_sum(src, seg, n):
    out = torch.zeros((n,) + src.shape[1:], dtype=src.dtype)
    return out.index_add_(0, seg, src)

def _pad(x, pw):
    flat = tuple((v for pair in reversed(pw) for v in pair))
    return torch.nn.functional.pad(x, flat)
kernel_name = 'standalone__dilated_atrous__vision'

def setup_inputs():

    _w = lambda a: (lambda t: t.to(torch.bfloat16) if t.is_floating_point() else t)(torch.as_tensor(a))
    H = W = 512
    C = 96
    k = 3
    return {'x': _w((lambda *s: torch.randn(*s, dtype=torch.bfloat16) * 0.05)(1, H, W, C)), 'w': _w((lambda *s: torch.randn(*s, dtype=torch.bfloat16) * 0.05)(k, k, C, C) * (1.0 / (k * C ** 0.5)))}

def reference(x, w):
    B, H, W, C = x.shape
    k = 3
    rate = 2
    pad = (k - 1) * rate // 2
    xp = _pad(x, ((0, 0), (pad, pad), (pad, pad), (0, 0)))
    out = torch.zeros_like(x)
    for i in range(k):
        for j in range(k):
            tap = xp[:, i * rate:i * rate + H, j * rate:j * rate + W, :].clone()
            out = out + torch.einsum('bhwc,co->bhwo', tap, w[i, j])
    return out
```

```cpp
#include <cuda_runtime.h>
#include <cuda_bf16.h>
#include <cuda.h>
#include <stdint.h>

namespace {

constexpr int IMG_H = 512, IMG_W = 512, CH = 96;
constexpr int ROWS_PER_STRIP = 16;
constexpr int NSTAGE = 3;

constexpr int BT_BYTES   = 3072;
constexpr int W_BYTES    = 36 * BT_BYTES;
constexpr int PIX_PITCH  = 112;
constexpr int PLANE      = 17 * PIX_PITCH;
constexpr int BOX_BYTES  = 4 * PLANE;
constexpr int BOX_PITCH  = 7680;
constexpr int STAGE_BYTES = 2 * BOX_PITCH;
constexpr int OFF_W      = 0;
constexpr int OFF_IN     = OFF_W + W_BYTES;
constexpr int OFF_X      = OFF_IN + 2 * NSTAGE * STAGE_BYTES;
constexpr int X_BYTES    = 3072;
constexpr int OFF_BAR    = OFF_X + 8 * X_BYTES;
constexpr int BAR_FULL = 0, BAR_EMPTY = 6, BAR_XFULL = 12, BAR_XEMPTY = 20, NBAR = 28;
constexpr int SMEM_BYTES = OFF_BAR + NBAR * 8 + 128;

__device__ __forceinline__ void wg_fence()  { asm volatile("wgmma.fence.sync.aligned;" ::: "memory"); }
__device__ __forceinline__ void wg_commit() { asm volatile("wgmma.commit_group.sync.aligned;" ::: "memory"); }
template <int N> __device__ __forceinline__ void wg_wait() { asm volatile("wgmma.wait_group.sync.aligned %0;" ::"n"(N) : "memory"); }

template <int SCALE_D>
__device__ __forceinline__ void wgmma96(float (&d)[48], const uint32_t (&a)[4], uint64_t db) {
  asm volatile(
      "{\n.reg .pred p;\nsetp.ne.b32 p, %53, 0;\n"
      "wgmma.mma_async.sync.aligned.m64n96k16.f32.bf16.bf16 "
      "{%0,%1,%2,%3,%4,%5,%6,%7,%8,%9,%10,%11,%12,%13,%14,%15,%16,%17,%18,%19,%20,%21,%22,%23,"
      "%24,%25,%26,%27,%28,%29,%30,%31,%32,%33,%34,%35,%36,%37,%38,%39,%40,%41,%42,%43,%44,%45,%46,%47}, "
      "{%48,%49,%50,%51}, %52, p, 1, 1, 1;\n}\n"
      : "+f"(d[0]), "+f"(d[1]), "+f"(d[2]), "+f"(d[3]), "+f"(d[4]), "+f"(d[5]), "+f"(d[6]), "+f"(d[7]),
        "+f"(d[8]), "+f"(d[9]), "+f"(d[10]), "+f"(d[11]), "+f"(d[12]), "+f"(d[13]), "+f"(d[14]), "+f"(d[15]),
        "+f"(d[16]), "+f"(d[17]), "+f"(d[18]), "+f"(d[19]), "+f"(d[20]), "+f"(d[21]), "+f"(d[22]), "+f"(d[23]),
        "+f"(d[24]), "+f"(d[25]), "+f"(d[26]), "+f"(d[27]), "+f"(d[28]), "+f"(d[29]), "+f"(d[30]), "+f"(d[31]),
        "+f"(d[32]), "+f"(d[33]), "+f"(d[34]), "+f"(d[35]), "+f"(d[36]), "+f"(d[37]), "+f"(d[38]), "+f"(d[39]),
        "+f"(d[40]), "+f"(d[41]), "+f"(d[42]), "+f"(d[43]), "+f"(d[44]), "+f"(d[45]), "+f"(d[46]), "+f"(d[47])
      : "r"(a[0]), "r"(a[1]), "r"(a[2]), "r"(a[3]), "l"(db), "n"(SCALE_D));
}

__device__ __forceinline__ void ldsm4(uint32_t (&r)[4], uint32_t addr) {
  asm volatile("ldmatrix.sync.aligned.m8n8.x4.shared.b16 {%0,%1,%2,%3}, [%4];"
               : "=r"(r[0]), "=r"(r[1]), "=r"(r[2]), "=r"(r[3]) : "r"(addr) : "memory");
}
__device__ __forceinline__ uint32_t badd(uint32_t a, uint32_t b) {
  uint32_t d; asm volatile("add.rn.bf16x2 %0, %1, %2;" : "=r"(d) : "r"(a), "r"(b)); return d;
}
__device__ __forceinline__ uint32_t bsub(uint32_t a, uint32_t b) {
  uint32_t d; asm volatile("sub.rn.bf16x2 %0, %1, %2;" : "=r"(d) : "r"(a), "r"(b)); return d;
}
__device__ __forceinline__ uint32_t pack2(float lo, float hi) {
  uint32_t d; asm volatile("cvt.rn.bf16x2.f32 %0, %1, %2;" : "=r"(d) : "f"(hi), "f"(lo)); return d;
}

__device__ __forceinline__ bool mbar_try(uint32_t bar, uint32_t parity) {
  uint32_t ok;
  asm volatile("{\n.reg .pred p;\nmbarrier.try_wait.parity.shared::cta.b64 p, [%1], %2;\nselp.u32 %0, 1, 0, p;\n}\n"
               : "=r"(ok) : "r"(bar), "r"(parity) : "memory");
  return ok;
}
__device__ __forceinline__ void mbar_wait(uint32_t bar, uint32_t parity) {
  if (mbar_try(bar, parity)) return;
  for (int it = 0; it < (1 << 22); ++it)
    if (mbar_try(bar, parity)) return;
  __trap();
}
__device__ __forceinline__ void mbar_init(uint32_t bar, uint32_t count) {
  asm volatile("mbarrier.init.shared::cta.b64 [%0], %1;" ::"r"(bar), "r"(count) : "memory");
}
__device__ __forceinline__ void mbar_arrive(uint32_t bar) {
  asm volatile("mbarrier.arrive.shared::cta.b64 _, [%0];" ::"r"(bar) : "memory");
}
__device__ __forceinline__ void mbar_arrive_remote(uint32_t cluster_bar) {
  asm volatile("mbarrier.arrive.shared::cluster.b64 _, [%0];" ::"r"(cluster_bar) : "memory");
}
__device__ __forceinline__ void mbar_expect_tx(uint32_t bar, uint32_t bytes) {
  asm volatile("mbarrier.arrive.expect_tx.shared::cta.b64 _, [%0], %1;" ::"r"(bar), "r"(bytes) : "memory");
}
__device__ __forceinline__ void tma_load4(uint32_t dst, const CUtensorMap* map, uint32_t bar, int c0, int c1, int c2, int c3) {
  asm volatile("cp.async.bulk.tensor.4d.shared::cluster.global.mbarrier::complete_tx::bytes [%0], [%1, {%3,%4,%5,%6}], [%2];"
               ::"r"(dst), "l"(map), "r"(bar), "r"(c0), "r"(c1), "r"(c2), "r"(c3) : "memory");
}
__device__ __forceinline__ void st_async4(uint32_t cluster_addr, uint32_t cluster_bar, uint32_t a, uint32_t b, uint32_t c, uint32_t d) {
  asm volatile("st.async.shared::cluster.mbarrier::complete_tx::bytes.v4.b32 [%0], {%2,%3,%4,%5}, [%1];"
               ::"r"(cluster_addr), "r"(cluster_bar), "r"(a), "r"(b), "r"(c), "r"(d) : "memory");
}
__device__ __forceinline__ void lds4(uint32_t (&r)[4], uint32_t addr) {
  asm volatile("ld.shared.v4.b32 {%0,%1,%2,%3}, [%4];" : "=r"(r[0]), "=r"(r[1]), "=r"(r[2]), "=r"(r[3]) : "r"(addr) : "memory");
}
__device__ __forceinline__ void sts4(uint32_t addr, uint32_t a, uint32_t b, uint32_t c, uint32_t d) {
  asm volatile("st.shared.v4.b32 [%0], {%1,%2,%3,%4};" ::"r"(addr), "r"(a), "r"(b), "r"(c), "r"(d) : "memory");
}
__device__ __forceinline__ void stg4(void* p, uint32_t a, uint32_t b, uint32_t c, uint32_t d) {
  asm volatile("st.global.v4.b32 [%0], {%1,%2,%3,%4};" ::"l"(p), "r"(a), "r"(b), "r"(c), "r"(d) : "memory");
}
__device__ __forceinline__ uint32_t mapa(uint32_t addr, uint32_t rank) {
  uint32_t r; asm("mapa.shared::cluster.u32 %0, %1, %2;" : "=r"(r) : "r"(addr), "r"(rank)); return r;
}
__device__ __forceinline__ void cluster_sync() {
  asm volatile("barrier.cluster.arrive.release.aligned;\nbarrier.cluster.wait.acquire.aligned;" ::: "memory");
}

__device__ __forceinline__ void tr_sum(uint32_t (&t)[3][4], const uint32_t (&U)[3][4], const uint32_t (&V)[3][4]) {
#pragma unroll
  for (int k = 0; k < 3; k++)
#pragma unroll
    for (int i = 0; i < 4; i++) t[k][i] = badd(U[k][i], V[k][i]);
}
__device__ __forceinline__ void tr_dif(uint32_t (&t)[3][4], const uint32_t (&U)[3][4], const uint32_t (&V)[3][4]) {
#pragma unroll
  for (int k = 0; k < 3; k++)
#pragma unroll
    for (int i = 0; i < 4; i++) t[k][i] = bsub(V[k][i], U[k][i]);
}
__device__ __forceinline__ void tr_t0(uint32_t (&t)[3][4], const uint32_t (&V)[3][4], const uint32_t (&E)[3][4]) {
#pragma unroll
  for (int k = 0; k < 3; k++) {
    t[k][0] = bsub(E[k][0], V[k][0]); t[k][1] = bsub(V[k][0], V[k][1]);
    t[k][2] = bsub(E[k][2], V[k][2]); t[k][3] = bsub(V[k][2], V[k][3]);
  }
}
__device__ __forceinline__ void tr_t3(uint32_t (&t)[3][4], const uint32_t (&U)[3][4], const uint32_t (&E)[3][4]) {
#pragma unroll
  for (int k = 0; k < 3; k++) {
    t[k][0] = bsub(U[k][1], U[k][0]); t[k][1] = bsub(E[k][1], U[k][1]);
    t[k][2] = bsub(U[k][3], U[k][2]); t[k][3] = bsub(E[k][3], U[k][3]);
  }
}
__device__ __forceinline__ void ld3(uint32_t (&R)[3][4], uint32_t addr) {
#pragma unroll
  for (int k = 0; k < 3; k++) ldsm4(R[k], addr + 32 * k);
}
template <int COMP, int AGE, int FIRST>
__device__ __forceinline__ void batch(float (&acc)[48], const uint32_t (&t)[3][4], uint64_t bdesc) {
  constexpr int base = ((COMP * 3 + AGE) * 3) * BT_BYTES;
  wgmma96<FIRST ? 0 : 1>(acc, t[0], bdesc + ((base) >> 4));
  wgmma96<1>(acc, t[1], bdesc + ((base + BT_BYTES) >> 4));
  wgmma96<1>(acc, t[2], bdesc + ((base + 2 * BT_BYTES) >> 4));
  wg_commit();
}

struct Ctx {
  uint64_t bdesc;
  uint32_t aU, aE;
  uint32_t in_base;
  uint32_t bar_full, bar_empty;
  uint32_t xaddr, xfull, xempty;
  uint32_t rxaddr, rxfull, rxempty;
  char* out;
  int out_step;
  const CUtensorMap* map;
  int c0, u0, h0, hstep;
  bool lane0, producer;
};

__device__ __forceinline__ void issue_row(const Ctx& c, int m, int st) {
  const uint32_t bar = c.bar_full + 8 * st;
  const uint32_t dst = c.in_base + st * STAGE_BYTES;
  const int h = c.h0 + m * c.hstep;
  mbar_expect_tx(bar, 2 * BOX_BYTES);
  tma_load4(dst, c.map, bar, c.c0, c.u0, 0, h);
  tma_load4(dst + BOX_PITCH, c.map, bar, c.c0, c.u0 - 1, 4, h);
}

template <int C0, int C1>
__device__ __forceinline__ void finish_chunks(const Ctx& c, const float (&Y)[48], char* out) {
#pragma unroll
  for (int ch = C0; ch < C1; ch++) {
    const int m = ch >> 1, s = ch & 1;
    uint32_t p[4], o[4];
    lds4(p, c.xaddr + ch * 512);
#pragma unroll
    for (int ss = 0; ss < 4; ss++) o[ss] = badd(pack2(Y[16 * m + 4 * ss + 2 * s], Y[16 * m + 4 * ss + 2 * s + 1]), p[ss]);
    stg4(out + s * (4 * CH * 2) + m * 64, o[0], o[1], o[2], o[3]);
  }
}
__device__ __forceinline__ void send_all(const Ctx& c, const float (&X)[48]) {
#pragma unroll
  for (int ch = 0; ch < 6; ch++) {
    const int m = ch >> 1, s = ch & 1;
    uint32_t o[4];
#pragma unroll
    for (int ss = 0; ss < 4; ss++) o[ss] = pack2(X[16 * m + 4 * ss + 2 * s], X[16 * m + 4 * ss + 2 * s + 1]);
    st_async4(c.rxaddr + ch * 512, c.rxfull, o[0], o[1], o[2], o[3]);
  }
}

template <int RANK, int OLD>
__device__ __forceinline__ void unit(Ctx& c, int n, int& st, uint32_t& ph, float (&X)[48], float (&Y)[48],
                                     uint32_t (&T)[4][2][3][4], uint32_t (&U)[3][4], uint32_t (&V)[3][4]) {
  constexpr int MID = 1 - OLD;
  uint32_t E[3][4];
  wg_fence();
  batch<0, 0, 1>(X, T[0][OLD], c.bdesc);
  batch<0, 1, 0>(X, T[0][MID], c.bdesc);
  wg_wait<2>();
  if (n > 0) {
    mbar_wait(c.xfull, (n - 1) & 1);
    finish_chunks<0, 3>(c, Y, c.out);
  }
  wg_wait<1>();
  tr_sum(T[0][OLD], U, V);
  wg_fence();
  batch<0, 2, 0>(X, T[0][OLD], c.bdesc);
  if (n > 0) {
    finish_chunks<3, 6>(c, Y, c.out);
    c.out += c.out_step;
    __syncwarp();
    if (c.lane0) { mbar_expect_tx(c.xfull, X_BYTES); mbar_arrive_remote(c.rxempty); }
  }
  wg_fence();
  batch<1, 0, 1>(Y, T[1][OLD], c.bdesc);
  batch<1, 1, 0>(Y, T[1][MID], c.bdesc);
  ld3(E, c.aE + st * STAGE_BYTES);
  wg_wait<1>();
  tr_dif(T[1][OLD], U, V);
  wg_fence();
  batch<1, 2, 0>(Y, T[1][OLD], c.bdesc);
  wg_wait<0>();
#pragma unroll
  for (int i = 0; i < 48; i++) {
    const float a = X[i], b = Y[i];
    if (RANK == 0) { X[i] = a - b; Y[i] = a + b; } else { X[i] = a + b; Y[i] = a - b; }
  }
  wg_fence();
  batch<2, 0, 0>(X, T[2][OLD], c.bdesc);
  batch<2, 1, 0>(X, T[2][MID], c.bdesc);
  const int st_cur = st;
  const uint32_t ph_cur = ph;
  st = (st == NSTAGE - 1) ? 0 : st + 1;
  ph ^= (st == 0);
  const bool more = (n + 3 < ROWS_PER_STRIP + 2);
  wg_wait<1>();
  if (RANK == 0) tr_t3(T[2][OLD], U, E); else tr_t0(T[2][OLD], V, E);
  wg_fence();
  batch<2, 2, 0>(X, T[2][OLD], c.bdesc);
  batch<3, 0, 0>(Y, T[3][OLD], c.bdesc);
  batch<3, 1, 0>(Y, T[3][MID], c.bdesc);
  __syncwarp();
  if (c.lane0) mbar_arrive(c.bar_empty + 8 * st_cur);
  if (more) {
    mbar_wait(c.bar_full + 8 * st, ph);
    if (RANK == 0) ld3(U, c.aU + st * STAGE_BYTES); else ld3(V, c.aU + 2 * PLANE + st * STAGE_BYTES);
  }
  wg_wait<2>();
  if (n > 0) mbar_wait(c.xempty, (n - 1) & 1);
  send_all(c, X);
  wg_wait<1>();
  if (RANK == 0) tr_t0(T[3][OLD], V, E); else tr_t3(T[3][OLD], U, E);
  wg_fence();
  batch<3, 2, 0>(Y, T[3][OLD], c.bdesc);
  if (more) {
    if (RANK == 0) ld3(V, c.aU + 2 * PLANE + st * STAGE_BYTES); else ld3(U, c.aU + st * STAGE_BYTES);
  }
  if (c.producer && n + 2 + NSTAGE < ROWS_PER_STRIP + 2) {
    mbar_wait(c.bar_empty + 8 * st_cur, ph_cur);
    issue_row(c, n + 2 + NSTAGE, st_cur);
  }
  __syncwarp();
}

template <int RANK>
__device__ __forceinline__ void run_strip(Ctx& c) {
  float X[48], Y[48];
  uint32_t T[4][2][3][4], U[3][4], V[3][4];
#pragma unroll
  for (int i = 0; i < 48; i++) { X[i] = 0.f; Y[i] = 0.f; }
#pragma unroll
  for (int m = 0; m < 2; m++) {
    uint32_t E[3][4];
    mbar_wait(c.bar_full + 8 * m, 0);
    ld3(U, c.aU + m * STAGE_BYTES);
    ld3(V, c.aU + 2 * PLANE + m * STAGE_BYTES);
    ld3(E, c.aE + m * STAGE_BYTES);
    tr_sum(T[0][m], U, V);
    tr_dif(T[1][m], U, V);
    if (RANK == 0) { tr_t3(T[2][m], U, E); tr_t0(T[3][m], V, E); }
    else           { tr_t0(T[2][m], V, E); tr_t3(T[3][m], U, E); }
    __syncwarp();
    if (c.lane0) mbar_arrive(c.bar_empty + 8 * m);
  }
  if (c.producer) {
#pragma unroll
    for (int m = 0; m < 2; m++) {
      mbar_wait(c.bar_empty + 8 * m, 0);
      issue_row(c, m + NSTAGE, m);
    }
  }
  __syncwarp();
  mbar_wait(c.bar_full + 8 * 2, 0);
  ld3(U, c.aU + 2 * STAGE_BYTES);
  ld3(V, c.aU + 2 * PLANE + 2 * STAGE_BYTES);
  int st = 2;
  uint32_t ph = 0;
#pragma unroll 1
  for (int n = 0; n < ROWS_PER_STRIP; n += 2) {
    unit<RANK, 0>(c, n, st, ph, X, Y, T, U, V);
    unit<RANK, 1>(c, n + 1, st, ph, X, Y, T, U, V);
  }
  wg_wait<0>();
  mbar_wait(c.xfull, (ROWS_PER_STRIP - 1) & 1);
  finish_chunks<0, 6>(c, Y, c.out);
}

__global__ void __cluster_dims__(2, 1, 1) __launch_bounds__(256, 1)
dilated_conv_wino_kernel(const __grid_constant__ CUtensorMap xmap, const __nv_bfloat16* __restrict__ w,
                         __nv_bfloat16* __restrict__ out) {
  extern __shared__ uint8_t smem_raw[];
  const uint32_t sbase = ((uint32_t)__cvta_generic_to_shared(smem_raw) + 127) & ~127u;
  const int tid = threadIdx.x;
  const int wg = __shfl_sync(0xffffffff, tid >> 7, 0);
  const int warp = __shfl_sync(0xffffffff, (tid >> 5) & 3, 0);
  const int lane = tid & 31;
  const int rank = blockIdx.x & 1;
  const int sid = (blockIdx.x >> 1) * 2 + wg;
  const int seg = sid & 3, par = (sid >> 2) & 1, strip = sid >> 3;
  const bool down = (strip & 1) == 0;
  const int r0 = strip * ROWS_PER_STRIP;

  Ctx c;
  c.map = &xmap;
  c.in_base = sbase + OFF_IN + wg * NSTAGE * STAGE_BYTES;
  c.bar_full = sbase + OFF_BAR + 8 * (BAR_FULL + wg * NSTAGE);
  c.bar_empty = sbase + OFF_BAR + 8 * (BAR_EMPTY + wg * NSTAGE);
  c.c0 = rank ? 48 : -8;
  c.u0 = seg * 16;
  c.h0 = 2 * (down ? r0 - 1 : r0 + ROWS_PER_STRIP) + par;
  c.hstep = down ? 2 : -2;
  c.lane0 = lane == 0;
  c.producer = (tid & 127) == 0;
  c.xfull = sbase + OFF_BAR + 8 * (BAR_XFULL + wg * 4 + warp);
  c.xempty = sbase + OFF_BAR + 8 * (BAR_XEMPTY + wg * 4 + warp);

  if (c.producer) {
    for (int s = 0; s < NSTAGE; s++) { mbar_init(c.bar_full + 8 * s, 1); mbar_init(c.bar_empty + 8 * s, 4); }
    asm volatile("fence.mbarrier_init.release.cluster;" ::: "memory");
    asm volatile("fence.proxy.async.shared::cta;" ::: "memory");
    for (int s = 0; s < NSTAGE; s++) issue_row(c, s, s);
  }
  if (c.lane0) {
    mbar_init(c.xfull, 1);
    mbar_init(c.xempty, 1);
    mbar_expect_tx(c.xfull, X_BYTES);
    asm volatile("fence.mbarrier_init.release.cluster;" ::: "memory");
  }
  __syncwarp();

  for (int item = tid; item < 432; item += 256) {
    const int ci = item % 48, m = (item / 48) % 3, age = item / 144;
    const int i = down ? age : 2 - age;
    const uint4* src = reinterpret_cast<const uint4*>(w + ((size_t)(i * 3) * CH + rank * 48 + ci) * CH + m * 32);
    uint32_t wv[3][4][4];
#pragma unroll
    for (int j = 0; j < 3; j++)
#pragma unroll
      for (int q = 0; q < 4; q++) {
        const uint4 v = __ldg(src + j * (CH * CH / 8) + q);
        wv[j][q][0] = v.x; wv[j][q][1] = v.y; wv[j][q][2] = v.z; wv[j][q][3] = v.w;
      }
    const uint32_t dst = sbase + OFF_W + (age * 3 + (ci >> 4)) * BT_BYTES + ((ci >> 3) & 1) * 1536 + (ci & 7) * 16 + m * 512;
    const int c_w0 = rank ? 2 : 3, c_w2 = rank ? 3 : 2;
#pragma unroll
    for (int ss = 0; ss < 4; ss++) {
      uint32_t g1[4], g2[4];
#pragma unroll
      for (int q = 0; q < 4; q++) {
        const uint32_t a = wv[0][q][ss], b = wv[1][q][ss], d = wv[2][q][ss];
        const float slo = __uint_as_float(a << 16) + __uint_as_float(d << 16);
        const float shi = __uint_as_float(a & 0xffff0000u) + __uint_as_float(d & 0xffff0000u);
        const float blo = __uint_as_float(b << 16), bhi = __uint_as_float(b & 0xffff0000u);
        g1[q] = pack2(0.5f * (slo + blo), 0.5f * (shi + bhi));
        g2[q] = pack2(0.5f * (slo - blo), 0.5f * (shi - bhi));
      }
      sts4(dst + ss * 128 + 0 * 9 * BT_BYTES, g1[0], g1[1], g1[2], g1[3]);
      sts4(dst + ss * 128 + 1 * 9 * BT_BYTES, g2[0], g2[1], g2[2], g2[3]);
      sts4(dst + ss * 128 + c_w0 * 9 * BT_BYTES, wv[0][0][ss], wv[0][1][ss], wv[0][2][ss], wv[0][3][ss]);
      sts4(dst + ss * 128 + c_w2 * 9 * BT_BYTES, wv[2][0][ss], wv[2][1][ss], wv[2][2][ss], wv[2][3][ss]);
    }
  }
  asm volatile("fence.proxy.async.shared::cta;" ::: "memory");
  cluster_sync();

  c.bdesc = (uint64_t)(((sbase + OFF_W) & 0x3FFFF) >> 4) | ((uint64_t)(1536 >> 4) << 16) | ((uint64_t)(128 >> 4) << 32);
  const int b = warp & 1, uh = warp >> 1;
  {
    const int g = lane & 7, mi = lane >> 3;
    const uint32_t a0 = c.in_base + b * PLANE + (8 * uh + g) * PIX_PITCH + (mi >> 1) * 16 + (rank ? 0 : 16);
    c.aU = a0 + ((mi & 1) ? BOX_PITCH + PIX_PITCH : 0);
    c.aE = a0 + ((mi & 1) ? PIX_PITCH : BOX_PITCH + 2 * PLANE);
  }
  c.xaddr = sbase + OFF_X + (wg * 4 + warp) * X_BYTES + lane * 16;
  c.rxaddr = mapa(c.xaddr, rank ^ 1);
  c.rxfull = mapa(c.xfull, rank ^ 1);
  c.rxempty = mapa(c.xempty, rank ^ 1);
  {
    const int g = lane >> 2, q = lane & 3;
    const int px = 8 * (c.u0 + 8 * uh + g) + b + 2 * rank;
    const int h = c.h0 + c.hstep;
    c.out = reinterpret_cast<char*>(out) + ((size_t)h * IMG_W + px) * (CH * 2) + q * 16;
    c.out_step = c.hstep * IMG_W * CH * 2;
  }
  if (rank == 0) run_strip<0>(c); else run_strip<1>(c);
}

typedef CUresult (*EncodeTiledFn)(CUtensorMap*, CUtensorMapDataType, cuuint32_t, void*, const cuuint64_t*, const cuuint64_t*,
                                  const cuuint32_t*, const cuuint32_t*, CUtensorMapInterleave, CUtensorMapSwizzle,
                                  CUtensorMapL2promotion, CUtensorMapFloatOOBfill);

}

extern "C" void kernel_launch(void* const* d_in, const int* in_sizes, int n_in, void* d_out, int out_size) {
  (void)in_sizes; (void)n_in; (void)out_size;
  static EncodeTiledFn encode = nullptr;
  if (!encode) {
    void* fn = nullptr;
    cudaDriverEntryPointQueryResult qr;
    cudaGetDriverEntryPoint("cuTensorMapEncodeTiled", &fn, cudaEnableDefault, &qr);
    encode = (EncodeTiledFn)fn;
    cudaFuncSetAttribute(dilated_conv_wino_kernel, cudaFuncAttributeMaxDynamicSharedMemorySize, SMEM_BYTES);
  }
  CUtensorMap xmap;
  const cuuint64_t dims[4] = {CH, IMG_W / 8, 8, IMG_H};
  const cuuint64_t strides[3] = {8 * CH * 2, CH * 2, IMG_W * CH * 2};
  const cuuint32_t box[4] = {56, 17, 4, 1};
  const cuuint32_t estr[4] = {1, 1, 1, 1};
  encode(&xmap, CU_TENSOR_MAP_DATA_TYPE_BFLOAT16, 4, d_in[0], dims, strides, box, estr, CU_TENSOR_MAP_INTERLEAVE_NONE,
         CU_TENSOR_MAP_SWIZZLE_NONE, CU_TENSOR_MAP_L2_PROMOTION_L2_256B, CU_TENSOR_MAP_FLOAT_OOB_FILL_NONE);
  dilated_conv_wino_kernel<<<128, 256, SMEM_BYTES>>>(xmap, (const __nv_bfloat16*)d_in[1], (__nv_bfloat16*)d_out);
}
```

```cpp
#include <cuda_runtime.h>
#include <cuda_bf16.h>
#include <cuda.h>
#include <stdint.h>

namespace {

constexpr int IMG_H = 512, IMG_W = 512, CH = 96;
constexpr int ROWS_PER_STRIP = 16;
constexpr int NSTAGE = 2;

constexpr int BT_BYTES   = 3072;
constexpr int W_BYTES    = 36 * BT_BYTES;
constexpr int BOX_BYTES  = 4 * 17 * 96;
constexpr int OFF_BOXB   = 71 * 128;
constexpr int STAGE_BYTES = 144 * 128;
constexpr int OFF_V      = 72 * 128;
constexpr int OFF_P5 = 0, OFF_P0 = 104 * 128;
constexpr int OFF_W      = 0;
constexpr int OFF_IN     = OFF_W + W_BYTES;
constexpr int OFF_X      = OFF_IN + 2 * NSTAGE * STAGE_BYTES;
constexpr int X_BYTES    = 3072;
constexpr int OFF_BAR    = OFF_X + 8 * X_BYTES;
constexpr int BAR_FULL = 0, BAR_XFULL = 8, BAR_W = 24, NBAR = 28;
constexpr int EMPTY_OFF = 32;
constexpr int SMEM_BYTES = OFF_BAR + NBAR * 8;
constexpr uint32_t SMEM_BASE = 1024;
constexpr uint64_t BDESC = (uint64_t)((SMEM_BASE + OFF_W) >> 4) | ((uint64_t)(1536 >> 4) << 16) | ((uint64_t)(128 >> 4) << 32);

__device__ __forceinline__ void wg_fence()  { asm volatile("wgmma.fence.sync.aligned;" ::: "memory"); }
__device__ __forceinline__ void wg_commit() { asm volatile("wgmma.commit_group.sync.aligned;" ::: "memory"); }
template <int N> __device__ __forceinline__ void wg_wait() { asm volatile("wgmma.wait_group.sync.aligned %0;" ::"n"(N) : "memory"); }

template <int SCALE_D, uint64_t DESC>
__device__ __forceinline__ void wgmma96(float (&d)[48], const uint32_t (&a)[4]) {
  asm volatile(
      "{\n.reg .pred p;\nsetp.ne.b32 p, %53, 0;\n"
      "wgmma.mma_async.sync.aligned.m64n96k16.f32.bf16.bf16 "
      "{%0,%1,%2,%3,%4,%5,%6,%7,%8,%9,%10,%11,%12,%13,%14,%15,%16,%17,%18,%19,%20,%21,%22,%23,"
      "%24,%25,%26,%27,%28,%29,%30,%31,%32,%33,%34,%35,%36,%37,%38,%39,%40,%41,%42,%43,%44,%45,%46,%47}, "
      "{%48,%49,%50,%51}, %52, p, 1, 1, 1;\n}\n"
      : "+f"(d[0]), "+f"(d[1]), "+f"(d[2]), "+f"(d[3]), "+f"(d[4]), "+f"(d[5]), "+f"(d[6]), "+f"(d[7]),
        "+f"(d[8]), "+f"(d[9]), "+f"(d[10]), "+f"(d[11]), "+f"(d[12]), "+f"(d[13]), "+f"(d[14]), "+f"(d[15]),
        "+f"(d[16]), "+f"(d[17]), "+f"(d[18]), "+f"(d[19]), "+f"(d[20]), "+f"(d[21]), "+f"(d[22]), "+f"(d[23]),
        "+f"(d[24]), "+f"(d[25]), "+f"(d[26]), "+f"(d[27]), "+f"(d[28]), "+f"(d[29]), "+f"(d[30]), "+f"(d[31]),
        "+f"(d[32]), "+f"(d[33]), "+f"(d[34]), "+f"(d[35]), "+f"(d[36]), "+f"(d[37]), "+f"(d[38]), "+f"(d[39]),
        "+f"(d[40]), "+f"(d[41]), "+f"(d[42]), "+f"(d[43]), "+f"(d[44]), "+f"(d[45]), "+f"(d[46]), "+f"(d[47])
      : "r"(a[0]), "r"(a[1]), "r"(a[2]), "r"(a[3]), "l"(DESC), "n"(SCALE_D));
}

__device__ __forceinline__ void ldsm4(uint32_t (&r)[4], uint32_t addr) {
  asm volatile("ldmatrix.sync.aligned.m8n8.x4.shared.b16 {%0,%1,%2,%3}, [%4];"
               : "=r"(r[0]), "=r"(r[1]), "=r"(r[2]), "=r"(r[3]) : "r"(addr) : "memory");
}
__device__ __forceinline__ uint32_t badd(uint32_t a, uint32_t b) {
  uint32_t d; asm volatile("add.rn.bf16x2 %0, %1, %2;" : "=r"(d) : "r"(a), "r"(b)); return d;
}
__device__ __forceinline__ uint32_t bsub(uint32_t a, uint32_t b) {
  uint32_t d; asm volatile("sub.rn.bf16x2 %0, %1, %2;" : "=r"(d) : "r"(a), "r"(b)); return d;
}
__device__ __forceinline__ uint32_t pack2(float lo, float hi) {
  uint32_t d; asm volatile("cvt.rn.bf16x2.f32 %0, %1, %2;" : "=r"(d) : "f"(hi), "f"(lo)); return d;
}

__device__ __forceinline__ void mbar_wait(uint32_t bar, uint32_t parity) {
  asm volatile(
      "{\n.reg .pred p;\n.reg .u32 it;\n"
      "mbarrier.try_wait.parity.shared::cta.b64 p, [%0], %1;\n"
      "@p bra WAIT_DONE;\n"
      "mov.u32 it, 0;\n"
      "WAIT_LOOP:\n"
      ".pragma \"nounroll\";\n"
      "mbarrier.try_wait.parity.shared::cta.b64 p, [%0], %1;\n"
      "@p bra WAIT_DONE;\n"
      "add.u32 it, it, 1;\n"
      "setp.lt.u32 p, it, 4194304;\n"
      "@p bra WAIT_LOOP;\n"
      "trap;\n"
      "WAIT_DONE:\n}\n" ::"r"(bar), "r"(parity) : "memory");
}
__device__ __forceinline__ void mbar_init(uint32_t bar, uint32_t count) {
  asm volatile("mbarrier.init.shared::cta.b64 [%0], %1;" ::"r"(bar), "r"(count) : "memory");
}
__device__ __forceinline__ void mbar_arrive(uint32_t bar) {
  asm volatile("mbarrier.arrive.shared::cta.b64 _, [%0];" ::"r"(bar) : "memory");
}
__device__ __forceinline__ void mbar_arrive_remote(uint32_t cluster_bar) {
  asm volatile("mbarrier.arrive.shared::cluster.b64 _, [%0];" ::"r"(cluster_bar) : "memory");
}
__device__ __forceinline__ void mbar_expect_tx(uint32_t bar, uint32_t bytes) {
  asm volatile("mbarrier.arrive.expect_tx.shared::cta.b64 _, [%0], %1;" ::"r"(bar), "r"(bytes) : "memory");
}
__device__ __forceinline__ void tma_load5(uint32_t dst, const CUtensorMap* map, uint32_t bar, int c0, int c1, int c2, int c3, int c4) {
  asm volatile("cp.async.bulk.tensor.5d.shared::cluster.global.mbarrier::complete_tx::bytes [%0], [%1, {%3,%4,%5,%6,%7}], [%2];"
               ::"r"(dst), "l"(map), "r"(bar), "r"(c0), "r"(c1), "r"(c2), "r"(c3), "r"(c4) : "memory");
}
__device__ __forceinline__ void bulk_load(uint32_t dst, const void* src, uint32_t bytes, uint32_t bar) {
  asm volatile("cp.async.bulk.shared::cluster.global.mbarrier::complete_tx::bytes [%0], [%1], %2, [%3];"
               ::"r"(dst), "l"(src), "r"(bytes), "r"(bar) : "memory");
}
__device__ __forceinline__ void st_async4(uint32_t cluster_addr, uint32_t cluster_bar, uint32_t a, uint32_t b, uint32_t c, uint32_t d) {
  asm volatile("st.async.shared::cluster.mbarrier::complete_tx::bytes.v4.b32 [%0], {%2,%3,%4,%5}, [%1];"
               ::"r"(cluster_addr), "r"(cluster_bar), "r"(a), "r"(b), "r"(c), "r"(d) : "memory");
}
__device__ __forceinline__ void lds4(uint32_t (&r)[4], uint32_t addr) {
  asm volatile("ld.shared.v4.b32 {%0,%1,%2,%3}, [%4];" : "=r"(r[0]), "=r"(r[1]), "=r"(r[2]), "=r"(r[3]) : "r"(addr) : "memory");
}
__device__ __forceinline__ void sts1(uint32_t addr, uint32_t a) {
  asm volatile("st.shared.b32 [%0], %1;" ::"r"(addr), "r"(a) : "memory");
}
__device__ __forceinline__ void stg4(void* p, uint32_t a, uint32_t b, uint32_t c, uint32_t d) {
  asm volatile("st.global.v4.b32 [%0], {%1,%2,%3,%4};" ::"l"(p), "r"(a), "r"(b), "r"(c), "r"(d) : "memory");
}
__device__ __forceinline__ uint32_t mapa(uint32_t addr, uint32_t rank) {
  uint32_t r; asm("mapa.shared::cluster.u32 %0, %1, %2;" : "=r"(r) : "r"(addr), "r"(rank)); return r;
}

__device__ __forceinline__ void tr_sum(uint32_t (&t)[3][4], const uint32_t (&U)[3][4], const uint32_t (&V)[3][4]) {
#pragma unroll
  for (int k = 0; k < 3; k++)
#pragma unroll
    for (int i = 0; i < 4; i++) t[k][i] = badd(U[k][i], V[k][i]);
}
__device__ __forceinline__ void tr_dif(uint32_t (&t)[3][4], const uint32_t (&U)[3][4], const uint32_t (&V)[3][4]) {
#pragma unroll
  for (int k = 0; k < 3; k++)
#pragma unroll
    for (int i = 0; i < 4; i++) t[k][i] = bsub(V[k][i], U[k][i]);
}
__device__ __forceinline__ void tr_t0(uint32_t (&t)[3][4], const uint32_t (&V)[3][4], const uint32_t (&E)[6]) {
#pragma unroll
  for (int k = 0; k < 3; k++) {
    t[k][0] = bsub(E[2 * k], V[k][0]);     t[k][1] = bsub(V[k][0], V[k][1]);
    t[k][2] = bsub(E[2 * k + 1], V[k][2]); t[k][3] = bsub(V[k][2], V[k][3]);
  }
}
__device__ __forceinline__ void tr_t3(uint32_t (&t)[3][4], const uint32_t (&U)[3][4], const uint32_t (&E)[6]) {
#pragma unroll
  for (int k = 0; k < 3; k++) {
    t[k][0] = bsub(U[k][1], U[k][0]); t[k][1] = bsub(E[2 * k], U[k][1]);
    t[k][2] = bsub(U[k][3], U[k][2]); t[k][3] = bsub(E[2 * k + 1], U[k][3]);
  }
}
__device__ __forceinline__ void ldE(uint32_t (&E)[6], uint32_t aE, int off) {
  asm volatile("ldmatrix.sync.aligned.m8n8.x4.shared.b16 {%0,%1,%2,%3}, [%4];"
               : "=r"(E[0]), "=r"(E[1]), "=r"(E[2]), "=r"(E[3]) : "r"(aE + off) : "memory");
  asm volatile("ldmatrix.sync.aligned.m8n8.x2.shared.b16 {%0,%1}, [%2];"
               : "=r"(E[4]), "=r"(E[5]) : "r"((aE ^ 64) + off) : "memory");
}
__device__ __forceinline__ void ld3(uint32_t (&R)[3][4], uint32_t aU, int off) {
#pragma unroll
  for (int k = 0; k < 3; k++) ldsm4(R[k], (aU ^ (32 * k)) + off);
}
template <int COMP, int AGE, int FIRST>
__device__ __forceinline__ void batch(float (&acc)[48], const uint32_t (&t)[3][4]) {
  constexpr int base = ((COMP * 3 + AGE) * 3) * BT_BYTES;
  wgmma96<FIRST ? 0 : 1, BDESC + ((base) >> 4)>(acc, t[0]);
  wgmma96<1, BDESC + ((base + BT_BYTES) >> 4)>(acc, t[1]);
  wgmma96<1, BDESC + ((base + 2 * BT_BYTES) >> 4)>(acc, t[2]);
  wg_commit();
}

#define DBG_T(c, idx)
#define DBG_TA(idx)
#define DBG_FLUSH(c)
#define DBG_G(c, idx)

struct Ctx {
  uint32_t aU, aE;
  uint32_t in_base;
  uint32_t bar_full;
  uint32_t xaddr, xfull;
  char* out;
  int out_step;
  const CUtensorMap* map;
  int c0, u0, h0, hstep;
  bool lane0, producer;
};

__device__ __forceinline__ void issue_row(const Ctx& c, int m, int st) {
  const uint32_t bar = c.bar_full + 8 * st;
  const uint32_t dst = c.in_base + st * STAGE_BYTES;
  const int h = c.h0 + m * c.hstep;
  mbar_expect_tx(bar, 2 * BOX_BYTES);
  tma_load5(dst, c.map, bar, c.c0, c.u0, 0, 0, h);
  tma_load5(dst + OFF_BOXB, c.map, bar, c.c0, c.u0 - 1, 2, 0, h);
}

template <int C0, int C1>
__device__ __forceinline__ void finish_chunks(const Ctx& c, const float (&Y)[48], char* out) {
#pragma unroll
  for (int ch = C0; ch < C1; ch++) {
    const int m = ch >> 1, s = ch & 1;
    uint32_t p[4], o[4];
    lds4(p, c.xaddr + ch * 512);
#pragma unroll
    for (int ss = 0; ss < 4; ss++) o[ss] = badd(pack2(Y[16 * m + 4 * ss + 2 * s], Y[16 * m + 4 * ss + 2 * s + 1]), p[ss]);
    stg4(out + s * (4 * CH * 2) + m * 64, o[0], o[1], o[2], o[3]);
  }
}
template <int RANK>
__device__ __forceinline__ void send_all(const Ctx& c, const float (&X)[48]) {
  constexpr uint32_t RDELTA = RANK ? 0xFF000000u : 0x01000000u;
#pragma unroll
  for (int ch = 0; ch < 6; ch++) {
    const int m = ch >> 1, s = ch & 1;
    uint32_t o[4];
#pragma unroll
    for (int ss = 0; ss < 4; ss++) o[ss] = pack2(X[16 * m + 4 * ss + 2 * s], X[16 * m + 4 * ss + 2 * s + 1]);
    st_async4(c.xaddr + RDELTA + ch * 512, c.xfull + RDELTA, o[0], o[1], o[2], o[3]);
  }
}

template <int RANK, int OLD>
__device__ __forceinline__ void unit(Ctx& c, int n, float (&X)[48], float (&Y)[48],
                                     uint32_t (&T)[4][2][3][4], uint32_t (&U)[3][4], uint32_t (&V)[3][4]) {
  constexpr int MID = 1 - OLD;
  constexpr uint32_t RDELTA = RANK ? 0xFF000000u : 0x01000000u;
  uint32_t E[6];
  const bool not_first = (OLD == 1) || (n > 0);
  const bool not_last = (OLD == 0) || (n < ROWS_PER_STRIP - 1);
  wg_fence();
  batch<0, 0, 1>(X, T[0][OLD]);
  batch<0, 1, 0>(X, T[0][MID]);
  wg_wait<2>();
  if (not_first) {
    mbar_wait(c.xfull, MID);
    finish_chunks<0, 3>(c, Y, c.out);
  }
  wg_wait<1>();
  tr_sum(T[0][OLD], U, V);
  wg_fence();
  batch<0, 2, 0>(X, T[0][OLD]);
  if (not_first) {
    finish_chunks<3, 6>(c, Y, c.out);
    c.out += c.out_step;
    __syncwarp();
    if (c.lane0) { mbar_expect_tx(c.xfull, X_BYTES); mbar_arrive_remote(c.xfull + 64 + RDELTA); }
  }
  wg_fence();
  batch<1, 0, 1>(Y, T[1][OLD]);
  batch<1, 1, 0>(Y, T[1][MID]);
  ldE(E, c.aE, OLD * STAGE_BYTES + (RANK == 0 ? OFF_P5 : OFF_P0));
  wg_wait<1>();
  tr_dif(T[1][OLD], U, V);
  wg_fence();
  batch<1, 2, 0>(Y, T[1][OLD]);
  wg_wait<0>();
  DBG_T(c, 4 + 2 * n);
#pragma unroll
  for (int i = 0; i < 48; i++) {
    if (RANK == 0) asm volatile("sub.rn.f32 %0, %0, %1;\nfma.rn.f32 %1, %1, 0f40000000, %0;" : "+f"(X[i]), "+f"(Y[i]));
    else           asm volatile("add.rn.f32 %0, %0, %1;\nfma.rn.f32 %1, %1, 0fC0000000, %0;" : "+f"(X[i]), "+f"(Y[i]));
  }
  wg_fence();
  batch<2, 0, 0>(X, T[2][OLD]);
  batch<2, 1, 0>(X, T[2][MID]);
  wg_wait<1>();
  if (RANK == 0) tr_t3(T[2][OLD], U, E); else tr_t0(T[2][OLD], V, E);
  wg_fence();
  batch<2, 2, 0>(X, T[2][OLD]);
  batch<3, 0, 0>(Y, T[3][OLD]);
  batch<3, 1, 0>(Y, T[3][MID]);
  ldE(E, c.aE, OLD * STAGE_BYTES + (RANK == 0 ? OFF_P0 : OFF_P5));
  if (not_last) mbar_wait(c.bar_full + 8 * MID, ((n + 3) >> 1) & 1);
  if (RANK == 0) ld3(U, c.aU, MID * STAGE_BYTES); else ld3(V, c.aU, MID * STAGE_BYTES + OFF_V);
  wg_wait<2>();
  if (not_first) mbar_wait(c.xfull + 64, MID);
  send_all<RANK>(c, X);
  wg_wait<1>();
  if (RANK == 0) tr_t0(T[3][OLD], V, E); else tr_t3(T[3][OLD], U, E);
  wg_fence();
  batch<3, 2, 0>(Y, T[3][OLD]);
  __syncwarp();
  if (c.lane0) mbar_arrive(c.bar_full + EMPTY_OFF + 8 * OLD);
  if (RANK == 0) ld3(V, c.aU, MID * STAGE_BYTES + OFF_V); else ld3(U, c.aU, MID * STAGE_BYTES);
  if (c.producer && n + 4 < ROWS_PER_STRIP + 2) {
    mbar_wait(c.bar_full + EMPTY_OFF + 8 * OLD, ((n + 2) >> 1) & 1);
    issue_row(c, n + 4, OLD);
  }
  DBG_T(c, 5 + 2 * n);
  __syncwarp();
}

template <int RANK>
__device__ __forceinline__ void run_strip(Ctx& c) {
  float X[48], Y[48];
  uint32_t T[4][2][3][4], U[3][4], V[3][4];
#pragma unroll
  for (int i = 0; i < 48; i++) { X[i] = 0.f; Y[i] = 0.f; }
#pragma unroll
  for (int m = 0; m < 2; m++) {
    uint32_t E0[6], E5[6];
    mbar_wait(c.bar_full + 8 * m, 0);
    DBG_T(c, 50 + m);
    ld3(U, c.aU, m * STAGE_BYTES);
    ld3(V, c.aU, m * STAGE_BYTES + OFF_V);
    ldE(E0, c.aE, m * STAGE_BYTES + OFF_P0);
    ldE(E5, c.aE, m * STAGE_BYTES + OFF_P5);
    tr_sum(T[0][m], U, V);
    tr_dif(T[1][m], U, V);
    tr_t3(T[RANK == 0 ? 2 : 3][m], U, E5);
    tr_t0(T[RANK == 0 ? 3 : 2][m], V, E0);
    __syncwarp();
    if (c.lane0) mbar_arrive(c.bar_full + EMPTY_OFF + 8 * m);
    if (c.producer) {
      mbar_wait(c.bar_full + EMPTY_OFF + 8 * m, 0);
      issue_row(c, m + 2, m);
    }
    __syncwarp();
  }
  DBG_T(c, 46);
  mbar_wait(c.bar_full, 1);
  DBG_T(c, 52);
  ld3(U, c.aU, 0);
  ld3(V, c.aU, OFF_V);
  DBG_T(c, 2);
  asm volatile("barrier.cluster.wait.acquire.aligned;" ::: "memory");
  mbar_wait(SMEM_BASE + (RANK << 24) + OFF_BAR + 8 * BAR_W + 24, 0);
  DBG_T(c, 3);
#pragma unroll 1
  for (int n = 0; n < ROWS_PER_STRIP; n += 2) {
    unit<RANK, 0>(c, n, X, Y, T, U, V);
    unit<RANK, 1>(c, n + 1, X, Y, T, U, V);
  }
  wg_wait<0>();
  mbar_wait(c.xfull, (ROWS_PER_STRIP - 1) & 1);
  finish_chunks<0, 6>(c, Y, c.out);
  DBG_T(c, 40); DBG_G(c, 1); DBG_FLUSH(c);
}

__global__ void __cluster_dims__(2, 1, 1) __launch_bounds__(256, 1)
dilated_conv_wino_kernel(const __grid_constant__ CUtensorMap xmap, const __nv_bfloat16* __restrict__ x, const __nv_bfloat16* __restrict__ w,
                         __nv_bfloat16* __restrict__ out) {
  extern __shared__ uint8_t smem_raw[];
  const int tid = threadIdx.x;
  const int wg = __shfl_sync(0xffffffff, tid >> 7, 0);
  const int warp = __shfl_sync(0xffffffff, (tid >> 5) & 3, 0);
  const int lane = tid & 31;
  const int rank = blockIdx.x & 1;
  const uint32_t sbase = SMEM_BASE + (rank << 24);
  if ((uint32_t)__cvta_generic_to_shared(smem_raw) != sbase || mapa(sbase, rank ^ 1) != (sbase ^ 0x01000000u)) __trap();
  const int sid = (blockIdx.x >> 1) * 2 + wg;
  const int seg = sid & 3, par = (sid >> 2) & 1, strip = sid >> 3;
  const bool down = (strip & 1) == 0;
  const int r0 = strip * ROWS_PER_STRIP;

  Ctx c;
  c.map = &xmap;
  c.in_base = sbase + OFF_IN + wg * NSTAGE * STAGE_BYTES;
  c.bar_full = sbase + OFF_BAR + 8 * (BAR_FULL + wg * NSTAGE);
  c.c0 = rank * 48;
  c.u0 = seg * 16;
  c.h0 = 2 * (down ? r0 - 1 : r0 + ROWS_PER_STRIP) + par;
  c.hstep = down ? 2 : -2;
  c.lane0 = lane == 0;
  c.producer = (tid & 127) == 0;
  c.xfull = sbase + OFF_BAR + 8 * (BAR_XFULL + wg * 4 + warp);

  DBG_G(c, 0); DBG_T(c, 0);
  const uint32_t bar_w = sbase + OFF_BAR + 8 * BAR_W;
  const uint32_t o_w0 = (rank ? 2 : 3) * 9 * BT_BYTES, o_w2 = (rank ? 3 : 2) * 9 * BT_BYTES;
  if (tid == 0) {
    for (int i = 0; i < 4; i++) { mbar_init(sbase + OFF_BAR + 8 * i, 1); mbar_init(sbase + OFF_BAR + EMPTY_OFF + 8 * i, 4); }
    for (int a = 0; a < 3; a++) mbar_init(bar_w + 8 * a, 1);
    mbar_init(bar_w + 24, 8);
  }
  if (c.lane0) {
    mbar_init(c.xfull, 1);
    mbar_init(c.xfull + 64, 1);
    mbar_expect_tx(c.xfull, X_BYTES);
    asm volatile("fence.mbarrier_init.release.cluster;" ::: "memory");
    asm volatile("fence.proxy.async.shared::cta;" ::: "memory");
  }
  DBG_T(c, 45);
  __syncthreads();
  asm volatile("barrier.cluster.arrive.relaxed.aligned;" ::: "memory");
  DBG_T(c, 41);
  if (tid == 64) {
#pragma unroll 1
    for (int a = 0; a < 3; a++) {
      const int i = down ? a : 2 - a;
      const __nv_bfloat16* src = w + ((size_t)(i * 3) * CH + rank * 48) * CH;
      const uint32_t dst = sbase + OFF_W + a * 3 * BT_BYTES;
      mbar_expect_tx(bar_w + 8 * a, 9 * BT_BYTES);
      bulk_load(dst + o_w0, src, 3 * BT_BYTES, bar_w + 8 * a);
      bulk_load(dst, src + CH * CH, 3 * BT_BYTES, bar_w + 8 * a);
      bulk_load(dst + o_w2, src + 2 * CH * CH, 3 * BT_BYTES, bar_w + 8 * a);
      DBG_TA(53 + a);
    }
  }
  if ((tid & 127) == 96) {
#pragma unroll 1
    for (int s = 0; s < NSTAGE; s++) { issue_row(c, s, s); DBG_TA(47 + s); }
  }
  __syncwarp();

#pragma unroll 1
  for (int item = tid >> 5; item < 18; item += 8) {
    const int age = item / 6;
    const uint32_t base = sbase + OFF_W + item * 1536;
    mbar_wait(bar_w + 8 * age, 0);
    DBG_T(c, 42 + (item >> 3));
    uint32_t wa[3][4], wb[3][4], wd[3][4];
    const uint32_t src = base + (lane >> 2) * 192 + (lane & 3) * 16;
#pragma unroll
    for (int m = 0; m < 3; m++) {
      lds4(wa[m], src + o_w0 + m * 64);
      lds4(wb[m], src + m * 64);
      lds4(wd[m], src + o_w2 + m * 64);
    }
    __syncwarp();
    const uint32_t dst = base + lane * 4;
#pragma unroll
    for (int m = 0; m < 3; m++)
#pragma unroll
      for (int ss = 0; ss < 4; ss++) {
        const uint32_t a = wa[m][ss], b = wb[m][ss], d = wd[m][ss];
        const float slo = __uint_as_float(a << 16) + __uint_as_float(d << 16);
        const float shi = __uint_as_float(a & 0xffff0000u) + __uint_as_float(d & 0xffff0000u);
        const float blo = 0.5f * __uint_as_float(b << 16), bhi = 0.5f * __uint_as_float(b & 0xffff0000u);
        const uint32_t o = dst + m * 512 + ss * 128;
        sts1(o, pack2(fmaf(slo, 0.5f, blo), fmaf(shi, 0.5f, bhi)));
        sts1(o + 9 * BT_BYTES, pack2(fmaf(slo, 0.5f, -blo), fmaf(shi, 0.5f, -bhi)));
        sts1(o + o_w0, a);
        sts1(o + o_w2, d);
      }
  }
  asm volatile("fence.proxy.async.shared::cta;" ::: "memory");
  __syncwarp();
  if (c.lane0) mbar_arrive(bar_w + 24);
  DBG_T(c, 1);

  const int b = warp & 1, uh = warp >> 1;
  {
    const int g = lane & 7, mi = lane >> 3;
    const int rU = ((mi & 1) * 2 + b) * 17 + 8 * uh + g;
    const int rE = b * 17 + 8 * uh + g + 1;
    c.aU = c.in_base + rU * 128 + (((mi >> 1) ^ (rU & 7)) << 4);
    c.aE = c.in_base + rE * 128 + ((mi ^ (rE & 7)) << 4);
  }
  c.xaddr = sbase + OFF_X + (wg * 4 + warp) * X_BYTES + lane * 16;
  {
    const int g = lane >> 2, q = lane & 3;
    const int px = 8 * (c.u0 + 8 * uh + g) + b + 2 * rank;
    const int h = c.h0 + c.hstep;
    c.out = reinterpret_cast<char*>(out) + ((size_t)h * IMG_W + px) * (CH * 2) + q * 16;
    c.out_step = c.hstep * IMG_W * CH * 2;
  }
  if (rank == 0) run_strip<0>(c); else run_strip<1>(c);
}

typedef CUresult (*EncodeTiledFn)(CUtensorMap*, CUtensorMapDataType, cuuint32_t, void*, const cuuint64_t*, const cuuint64_t*,
                                  const cuuint32_t*, const cuuint32_t*, CUtensorMapInterleave, CUtensorMapSwizzle,
                                  CUtensorMapL2promotion, CUtensorMapFloatOOBfill);

}

extern "C" void kernel_launch(void* const* d_in, const int* in_sizes, int n_in, void* d_out, int out_size) {
  (void)in_sizes; (void)n_in; (void)out_size;
  static EncodeTiledFn encode = nullptr;
  if (!encode) {
    void* fn = nullptr;
    cudaDriverEntryPointQueryResult qr;
    cudaGetDriverEntryPoint("cuTensorMapEncodeTiled", &fn, cudaEnableDefault, &qr);
    encode = (EncodeTiledFn)fn;
    cudaFuncSetAttribute(dilated_conv_wino_kernel, cudaFuncAttributeMaxDynamicSharedMemorySize, SMEM_BYTES);
  }
  CUtensorMap xmap;
  const cuuint64_t dims[5] = {CH, IMG_W / 8, 4, 2, IMG_H};
  const cuuint64_t strides[4] = {8 * CH * 2, CH * 2, 4 * CH * 2, IMG_W * CH * 2};
  const cuuint32_t box[5] = {48, 17, 2, 2, 1};
  const cuuint32_t estr[5] = {1, 1, 1, 1, 1};
#define PROMO CU_TENSOR_MAP_L2_PROMOTION_L2_128B
  encode(&xmap, CU_TENSOR_MAP_DATA_TYPE_BFLOAT16, 5, d_in[0], dims, strides, box, estr, CU_TENSOR_MAP_INTERLEAVE_NONE,
         CU_TENSOR_MAP_SWIZZLE_128B, PROMO, CU_TENSOR_MAP_FLOAT_OOB_FILL_NONE);
  dilated_conv_wino_kernel<<<128, 256, SMEM_BYTES>>>(xmap, (const __nv_bfloat16*)d_in[0], (const __nv_bfloat16*)d_in[1], (__nv_bfloat16*)d_out);
}
```

```cpp
#include <cuda_runtime.h>
#include <cuda_bf16.h>
#include <cuda.h>
#include <stdint.h>

namespace {

constexpr int IMG_H = 512, IMG_W = 512, CH = 96;
constexpr int ROWS_PER_STRIP = 16;
constexpr int NSTAGE = 2;

constexpr int BT_BYTES   = 3072;
constexpr int W_BYTES    = 36 * BT_BYTES;
constexpr int BOX_BYTES  = 4 * 17 * 96;
constexpr int OFF_BOXB   = 71 * 128;
constexpr int STAGE_BYTES = 144 * 128;
constexpr int OFF_V      = 72 * 128;
constexpr int OFF_P5 = 0, OFF_P0 = 104 * 128;
constexpr int OFF_W      = 0;
constexpr int OFF_IN     = OFF_W + W_BYTES;
constexpr int OFF_X      = OFF_IN + 2 * NSTAGE * STAGE_BYTES;
constexpr int X_BYTES    = 3072;
constexpr int OFF_TMP    = OFF_X + 8 * X_BYTES;
constexpr int OFF_BAR    = OFF_TMP + STAGE_BYTES;
constexpr int BAR_FULL = 0, BAR_XFULL = 8, BAR_W = 24, BAR_ROW0 = 28, NBAR = 30;
constexpr int EMPTY_OFF = 32;
constexpr int SMEM_BYTES = OFF_BAR + NBAR * 8;
constexpr uint32_t SMEM_BASE = 1024;
constexpr uint64_t BDESC = (uint64_t)((SMEM_BASE + OFF_W) >> 4) | ((uint64_t)(1536 >> 4) << 16) | ((uint64_t)(128 >> 4) << 32);

__device__ __forceinline__ void wg_fence()  { asm volatile("wgmma.fence.sync.aligned;" ::: "memory"); }
__device__ __forceinline__ void wg_commit() { asm volatile("wgmma.commit_group.sync.aligned;" ::: "memory"); }
template <int N> __device__ __forceinline__ void wg_wait() { asm volatile("wgmma.wait_group.sync.aligned %0;" ::"n"(N) : "memory"); }

template <int SCALE_D, uint64_t DESC>
__device__ __forceinline__ void wgmma96(float (&d)[48], const uint32_t (&a)[4]) {
  asm volatile(
      "{\n.reg .pred p;\nsetp.ne.b32 p, %53, 0;\n"
      "wgmma.mma_async.sync.aligned.m64n96k16.f32.bf16.bf16 "
      "{%0,%1,%2,%3,%4,%5,%6,%7,%8,%9,%10,%11,%12,%13,%14,%15,%16,%17,%18,%19,%20,%21,%22,%23,"
      "%24,%25,%26,%27,%28,%29,%30,%31,%32,%33,%34,%35,%36,%37,%38,%39,%40,%41,%42,%43,%44,%45,%46,%47}, "
      "{%48,%49,%50,%51}, %52, p, 1, 1, 1;\n}\n"
      : "+f"(d[0]), "+f"(d[1]), "+f"(d[2]), "+f"(d[3]), "+f"(d[4]), "+f"(d[5]), "+f"(d[6]), "+f"(d[7]),
        "+f"(d[8]), "+f"(d[9]), "+f"(d[10]), "+f"(d[11]), "+f"(d[12]), "+f"(d[13]), "+f"(d[14]), "+f"(d[15]),
        "+f"(d[16]), "+f"(d[17]), "+f"(d[18]), "+f"(d[19]), "+f"(d[20]), "+f"(d[21]), "+f"(d[22]), "+f"(d[23]),
        "+f"(d[24]), "+f"(d[25]), "+f"(d[26]), "+f"(d[27]), "+f"(d[28]), "+f"(d[29]), "+f"(d[30]), "+f"(d[31]),
        "+f"(d[32]), "+f"(d[33]), "+f"(d[34]), "+f"(d[35]), "+f"(d[36]), "+f"(d[37]), "+f"(d[38]), "+f"(d[39]),
        "+f"(d[40]), "+f"(d[41]), "+f"(d[42]), "+f"(d[43]), "+f"(d[44]), "+f"(d[45]), "+f"(d[46]), "+f"(d[47])
      : "r"(a[0]), "r"(a[1]), "r"(a[2]), "r"(a[3]), "l"(DESC), "n"(SCALE_D));
}

__device__ __forceinline__ void ldsm4(uint32_t (&r)[4], uint32_t addr) {
  asm volatile("ldmatrix.sync.aligned.m8n8.x4.shared.b16 {%0,%1,%2,%3}, [%4];"
               : "=r"(r[0]), "=r"(r[1]), "=r"(r[2]), "=r"(r[3]) : "r"(addr) : "memory");
}
__device__ __forceinline__ uint32_t badd(uint32_t a, uint32_t b) {
  uint32_t d; asm volatile("add.rn.bf16x2 %0, %1, %2;" : "=r"(d) : "r"(a), "r"(b)); return d;
}
__device__ __forceinline__ uint32_t bsub(uint32_t a, uint32_t b) {
  uint32_t d; asm volatile("sub.rn.bf16x2 %0, %1, %2;" : "=r"(d) : "r"(a), "r"(b)); return d;
}
__device__ __forceinline__ uint32_t pack2(float lo, float hi) {
  uint32_t d; asm volatile("cvt.rn.bf16x2.f32 %0, %1, %2;" : "=r"(d) : "f"(hi), "f"(lo)); return d;
}

__device__ __forceinline__ void mbar_wait(uint32_t bar, uint32_t parity) {
  asm volatile(
      "{\n.reg .pred p;\n.reg .u32 it;\n"
      "mbarrier.try_wait.parity.shared::cta.b64 p, [%0], %1;\n"
      "@p bra WAIT_DONE;\n"
      "mov.u32 it, 0;\n"
      "WAIT_LOOP:\n"
      ".pragma \"nounroll\";\n"
      "mbarrier.try_wait.parity.shared::cta.b64 p, [%0], %1;\n"
      "@p bra WAIT_DONE;\n"
      "add.u32 it, it, 1;\n"
      "setp.lt.u32 p, it, 4194304;\n"
      "@p bra WAIT_LOOP;\n"
      "trap;\n"
      "WAIT_DONE:\n}\n" ::"r"(bar), "r"(parity) : "memory");
}
__device__ __forceinline__ void mbar_init(uint32_t bar, uint32_t count) {
  asm volatile("mbarrier.init.shared::cta.b64 [%0], %1;" ::"r"(bar), "r"(count) : "memory");
}
__device__ __forceinline__ void mbar_arrive(uint32_t bar) {
  asm volatile("mbarrier.arrive.shared::cta.b64 _, [%0];" ::"r"(bar) : "memory");
}
__device__ __forceinline__ void mbar_arrive_remote(uint32_t cluster_bar) {
  asm volatile("mbarrier.arrive.shared::cluster.b64 _, [%0];" ::"r"(cluster_bar) : "memory");
}
__device__ __forceinline__ void mbar_expect_tx(uint32_t bar, uint32_t bytes) {
  asm volatile("mbarrier.arrive.expect_tx.shared::cta.b64 _, [%0], %1;" ::"r"(bar), "r"(bytes) : "memory");
}
__device__ __forceinline__ void tma_load5(uint32_t dst, const CUtensorMap* map, uint32_t bar, int c0, int c1, int c2, int c3, int c4) {
  asm volatile("cp.async.bulk.tensor.5d.shared::cluster.global.mbarrier::complete_tx::bytes [%0], [%1, {%3,%4,%5,%6,%7}], [%2];"
               ::"r"(dst), "l"(map), "r"(bar), "r"(c0), "r"(c1), "r"(c2), "r"(c3), "r"(c4) : "memory");
}
__device__ __forceinline__ void bulk_load(uint32_t dst, const void* src, uint32_t bytes, uint32_t bar) {
  asm volatile("cp.async.bulk.shared::cluster.global.mbarrier::complete_tx::bytes [%0], [%1], %2, [%3];"
               ::"r"(dst), "l"(src), "r"(bytes), "r"(bar) : "memory");
}
template <int OFF>
__device__ __forceinline__ void st_async4(uint32_t cluster_addr, uint32_t cluster_bar, uint32_t a, uint32_t b, uint32_t c, uint32_t d) {
  asm volatile("st.async.shared::cluster.mbarrier::complete_tx::bytes.v4.b32 [%0+%6], {%2,%3,%4,%5}, [%1];"
               ::"r"(cluster_addr), "r"(cluster_bar), "r"(a), "r"(b), "r"(c), "r"(d), "n"(OFF) : "memory");
}
__device__ __forceinline__ void stsm4(uint32_t addr, uint32_t a, uint32_t b, uint32_t c, uint32_t d) {
  asm volatile("stmatrix.sync.aligned.m8n8.x4.shared.b16 [%0], {%1,%2,%3,%4};" ::"r"(addr), "r"(a), "r"(b), "r"(c), "r"(d) : "memory");
}
__device__ __forceinline__ uint32_t bfma(uint32_t a, uint32_t b, uint32_t c) {
  uint32_t d; asm volatile("fma.rn.bf16x2 %0, %1, %2, %3;" : "=r"(d) : "r"(a), "r"(b), "r"(c)); return d;
}
__device__ __forceinline__ void lds4(uint32_t (&r)[4], uint32_t addr) {
  asm volatile("ld.shared.v4.b32 {%0,%1,%2,%3}, [%4];" : "=r"(r[0]), "=r"(r[1]), "=r"(r[2]), "=r"(r[3]) : "r"(addr) : "memory");
}
__device__ __forceinline__ void sts4(uint32_t addr, const uint32_t (&r)[4]) {
  asm volatile("st.shared.v4.b32 [%0], {%1,%2,%3,%4};" ::"r"(addr), "r"(r[0]), "r"(r[1]), "r"(r[2]), "r"(r[3]) : "memory");
}
__device__ __forceinline__ void tma_store5(const CUtensorMap* map, uint32_t src, int c0, int c1, int c2, int c3, int c4) {
  asm volatile("cp.async.bulk.tensor.5d.global.shared::cta.bulk_group [%0, {%2,%3,%4,%5,%6}], [%1];"
               ::"l"(map), "r"(src), "r"(c0), "r"(c1), "r"(c2), "r"(c3), "r"(c4) : "memory");
  asm volatile("cp.async.bulk.commit_group;" ::: "memory");
}
__device__ __forceinline__ bool elect_one() {
  uint32_t p;
  asm volatile("{\n.reg .pred P;\nelect.sync _|P, 0xffffffff;\nselp.u32 %0, 1, 0, P;\n}\n" : "=r"(p));
  return p;
}
__device__ __forceinline__ uint32_t mapa(uint32_t addr, uint32_t rank) {
  uint32_t r; asm("mapa.shared::cluster.u32 %0, %1, %2;" : "=r"(r) : "r"(addr), "r"(rank)); return r;
}

__device__ __forceinline__ void tr_sum(uint32_t (&t)[3][4], const uint32_t (&U)[3][4], const uint32_t (&V)[3][4]) {
#pragma unroll
  for (int k = 0; k < 3; k++)
#pragma unroll
    for (int i = 0; i < 4; i++) t[k][i] = badd(U[k][i], V[k][i]);
}
__device__ __forceinline__ void tr_dif(uint32_t (&t)[3][4], const uint32_t (&U)[3][4], const uint32_t (&V)[3][4]) {
#pragma unroll
  for (int k = 0; k < 3; k++)
#pragma unroll
    for (int i = 0; i < 4; i++) t[k][i] = bsub(V[k][i], U[k][i]);
}
__device__ __forceinline__ void tr_t0(uint32_t (&t)[3][4], const uint32_t (&V)[3][4], const uint32_t (&E)[6]) {
#pragma unroll
  for (int k = 0; k < 3; k++) {
    t[k][0] = bsub(E[2 * k], V[k][0]);     t[k][1] = bsub(V[k][0], V[k][1]);
    t[k][2] = bsub(E[2 * k + 1], V[k][2]); t[k][3] = bsub(V[k][2], V[k][3]);
  }
}
__device__ __forceinline__ void tr_t3(uint32_t (&t)[3][4], const uint32_t (&U)[3][4], const uint32_t (&E)[6]) {
#pragma unroll
  for (int k = 0; k < 3; k++) {
    t[k][0] = bsub(U[k][1], U[k][0]); t[k][1] = bsub(E[2 * k], U[k][1]);
    t[k][2] = bsub(U[k][3], U[k][2]); t[k][3] = bsub(E[2 * k + 1], U[k][3]);
  }
}
__device__ __forceinline__ void ldE(uint32_t (&E)[6], uint32_t aE, int off) {
  asm volatile("ldmatrix.sync.aligned.m8n8.x4.shared.b16 {%0,%1,%2,%3}, [%4];"
               : "=r"(E[0]), "=r"(E[1]), "=r"(E[2]), "=r"(E[3]) : "r"(aE + off) : "memory");
  asm volatile("ldmatrix.sync.aligned.m8n8.x2.shared.b16 {%0,%1}, [%2];"
               : "=r"(E[4]), "=r"(E[5]) : "r"((aE ^ 64) + off) : "memory");
}
__device__ __forceinline__ void ld3(uint32_t (&R)[3][4], uint32_t aU, int off) {
#pragma unroll
  for (int k = 0; k < 3; k++) ldsm4(R[k], (aU ^ (32 * k)) + off);
}
template <int COMP, int AGE, int FIRST>
__device__ __forceinline__ void batch(float (&acc)[48], const uint32_t (&t)[3][4]) {
  constexpr int base = ((COMP * 3 + AGE) * 3) * BT_BYTES;
  wgmma96<FIRST ? 0 : 1, BDESC + ((base) >> 4)>(acc, t[0]);
  wgmma96<1, BDESC + ((base + BT_BYTES) >> 4)>(acc, t[1]);
  wgmma96<1, BDESC + ((base + 2 * BT_BYTES) >> 4)>(acc, t[2]);
  wg_commit();
}

#define DBG_T(c, idx)
#define DBG_TA(idx)
#define DBG_FLUSH(c)
#define DBG_G(c, idx)

struct Ctx {
  uint32_t aU, aE;
  uint32_t in_base;
  uint32_t bar_full;
  uint32_t xaddr, xfull;
  uint32_t xbase;
  const CUtensorMap* omap;
  int ou, ob;
  const CUtensorMap* map;
  const char* xseg;
  int wg;
  int c0, u0, h0, hstep;
  bool lane0, producer, warp0;
};

__device__ __forceinline__ void issue_row(const CUtensorMap* map, uint32_t dst, uint32_t bar, int c0, int u0, int h) {
  mbar_expect_tx(bar, 2 * BOX_BYTES);
  tma_load5(dst, map, bar, c0, u0, 0, 0, h);
  tma_load5(dst + OFF_BOXB, map, bar, c0, u0 - 1, 2, 0, h);
}
__device__ __forceinline__ void prefetch_row(const Ctx& c, int h) {
  if ((unsigned)h < (unsigned)IMG_H)
    asm volatile("cp.async.bulk.prefetch.L2.global [%0], %1;" ::"l"(c.xseg + (size_t)h * (IMG_W * CH * 2)), "r"(64 * CH * 2) : "memory");
}

template <int C0, int C1>
__device__ __forceinline__ void load_partner(const Ctx& c, uint32_t (&P)[6][4]) {
#pragma unroll
  for (int ch = C0; ch < C1; ch++) lds4(P[ch], c.xaddr + (ch & 1) * 1536 + (ch >> 1) * 64);
}
template <int C0, int C1>
__device__ __forceinline__ void finish_chunks(const Ctx& c, const float (&Y)[48], uint32_t (&P)[6][4]) {
#pragma unroll
  for (int ch = C0; ch < C1; ch++) {
    const int m = ch >> 1, s = ch & 1;
#pragma unroll
    for (int ss = 0; ss < 4; ss++) P[ch][ss] = badd(pack2(Y[16 * m + 4 * ss + 2 * s], Y[16 * m + 4 * ss + 2 * s + 1]), P[ch][ss]);
    sts4(c.xaddr + s * 1536 + m * 64, P[ch]);
  }
}
__device__ __forceinline__ void store_row(const Ctx& c, int h) {
  asm volatile("fence.proxy.async.shared::cta;" ::: "memory");
  __syncwarp();
  if (elect_one()) tma_store5(c.omap, c.xbase, 0, c.ou, 0, c.ob, h);
}
template <int RANK, int CH0>
__device__ __forceinline__ void send_chunk(const Ctx& c, const float (&X)[48]) {
  constexpr uint32_t RDELTA = RANK ? 0xFF000000u : 0x01000000u;
  constexpr int m = CH0 >> 1, s = CH0 & 1;
  uint32_t o[4];
#pragma unroll
  for (int ss = 0; ss < 4; ss++) o[ss] = pack2(X[16 * m + 4 * ss + 2 * s], X[16 * m + 4 * ss + 2 * s + 1]);
  st_async4<s * 1536 + m * 64>(c.xaddr + RDELTA, c.xfull + RDELTA, o[0], o[1], o[2], o[3]);
}

#define PF_DIST 0
#define NPRE 6

template <int RANK, int OLD>
__device__ __forceinline__ void unit(Ctx& c, int n, float (&X)[48], float (&Y)[48],
                                     uint32_t (&T)[4][2][3][4], uint32_t (&U)[3][4], uint32_t (&V)[3][4]) {
  constexpr int MID = 1 - OLD;
  constexpr uint32_t RDELTA = RANK ? 0xFF000000u : 0x01000000u;
  uint32_t E[6];
  const bool not_first = (OLD == 1) || (n > 0);
  const bool not_last = (OLD == 0) || (n < ROWS_PER_STRIP - 1);
  wg_fence();
  batch<0, 0, 1>(X, T[0][OLD]);
  batch<0, 1, 0>(X, T[0][MID]);
  {
    uint32_t P[6][4];
    if (not_first) mbar_wait(c.xfull, MID);
    load_partner<0, NPRE>(c, P);
    wg_wait<2>();
    if (not_first) finish_chunks<0, 3>(c, Y, P);
    load_partner<NPRE, 6>(c, P);
    wg_wait<1>();
    tr_sum(T[0][OLD], U, V);
    wg_fence();
    batch<0, 2, 0>(X, T[0][OLD]);
    if (not_first) finish_chunks<3, 6>(c, Y, P);
  }
  wg_fence();
  batch<1, 0, 1>(Y, T[1][OLD]);
  batch<1, 1, 0>(Y, T[1][MID]);
  ldE(E, c.aE, OLD * STAGE_BYTES + (RANK == 0 ? OFF_P5 : OFF_P0));
  if (not_first) store_row(c, c.h0 + n * c.hstep);
  wg_wait<1>();
  tr_dif(T[1][OLD], U, V);
  wg_fence();
  batch<1, 2, 0>(Y, T[1][OLD]);
  wg_wait<0>();
  DBG_T(c, 4 + 2 * n);
#pragma unroll
  for (int i = 0; i < 48; i++) {
    if (RANK == 0) asm volatile("sub.rn.f32 %0, %0, %1;\nfma.rn.f32 %1, %1, 0f40000000, %0;" : "+f"(X[i]), "+f"(Y[i]));
    else           asm volatile("add.rn.f32 %0, %0, %1;\nfma.rn.f32 %1, %1, 0fC0000000, %0;" : "+f"(X[i]), "+f"(Y[i]));
  }
  wg_fence();
  batch<2, 0, 0>(X, T[2][OLD]);
  batch<2, 1, 0>(X, T[2][MID]);
  if (not_first && elect_one()) {
    asm volatile("cp.async.bulk.wait_group.read 0;" ::: "memory");
    mbar_expect_tx(c.xfull, X_BYTES);
    mbar_arrive_remote(c.xfull + 64 + RDELTA);
  }
  if (not_last) mbar_wait(c.bar_full + 8 * MID, ((n + 2 + MID) >> 1) & 1);
  wg_wait<1>();
  if (RANK == 0) tr_t3(T[2][OLD], U, E); else tr_t0(T[2][OLD], V, E);
  ldE(E, c.aE, OLD * STAGE_BYTES + (RANK == 0 ? OFF_P0 : OFF_P5));
  __syncwarp();
  if (elect_one()) mbar_arrive(c.bar_full + EMPTY_OFF + 8 * OLD);
  wg_fence();
  batch<2, 2, 0>(X, T[2][OLD]);
  batch<3, 0, 0>(Y, T[3][OLD]);
  batch<3, 1, 0>(Y, T[3][MID]);
  if (RANK == 0) ld3(U, c.aU, MID * STAGE_BYTES); else ld3(V, c.aU, MID * STAGE_BYTES + OFF_V);
  if (c.warp0 && n + 4 < ROWS_PER_STRIP + 2 && elect_one()) {
    mbar_wait(c.bar_full + EMPTY_OFF + 8 * OLD, ((n + 1) >> 1) & 1);
    issue_row(c.map, c.in_base + OLD * STAGE_BYTES, c.bar_full + 8 * OLD, c.c0, c.u0, c.h0 + (n + 4) * c.hstep);
    if (PF_DIST > 0 && n + 4 + PF_DIST < ROWS_PER_STRIP + 2) prefetch_row(c, c.h0 + (n + 4 + PF_DIST) * c.hstep);
  }
  __syncwarp();
  if (not_first) mbar_wait(c.xfull + 64, MID);
  wg_wait<2>();
  send_chunk<RANK, 0>(c, X); send_chunk<RANK, 1>(c, X); send_chunk<RANK, 2>(c, X);
  send_chunk<RANK, 3>(c, X); send_chunk<RANK, 4>(c, X); send_chunk<RANK, 5>(c, X);
  wg_wait<1>();
  if (RANK == 0) tr_t0(T[3][OLD], V, E); else tr_t3(T[3][OLD], U, E);
  if (RANK == 0) ld3(V, c.aU, MID * STAGE_BYTES + OFF_V); else ld3(U, c.aU, MID * STAGE_BYTES);
  wg_fence();
  batch<3, 2, 0>(Y, T[3][OLD]);
  DBG_T(c, 5 + 2 * n);
}

template <int RANK>
__device__ __forceinline__ void run_strip(Ctx& c, uint32_t row0_off, uint32_t bar_row0) {
  float X[48], Y[48];
  uint32_t T[4][2][3][4], U[3][4], V[3][4];
#pragma unroll
  for (int i = 0; i < 48; i++) { X[i] = 0.f; Y[i] = 0.f; }
#pragma unroll
  for (int m = 0; m < 2; m++) {
    uint32_t E0[6], E5[6];
    const uint32_t off = m ? STAGE_BYTES : row0_off;
    mbar_wait(m ? c.bar_full + 8 : bar_row0, 0);
    DBG_T(c, 50 + m);
    ld3(U, c.aU, off);
    ld3(V, c.aU, off + OFF_V);
    ldE(E0, c.aE, off + OFF_P0);
    ldE(E5, c.aE, off + OFF_P5);
    if (m) {
      __syncwarp();
      if (c.lane0) mbar_arrive(c.bar_full + EMPTY_OFF + 8);
    }
    tr_sum(T[0][m], U, V);
    tr_dif(T[1][m], U, V);
    tr_t3(T[RANK == 0 ? 2 : 3][m], U, E5);
    tr_t0(T[RANK == 0 ? 3 : 2][m], V, E0);
  }
  asm volatile("barrier.cluster.arrive.relaxed.aligned;" ::: "memory");
  if (c.warp0 && elect_one()) {
    mbar_wait(c.bar_full + EMPTY_OFF + 8, 0);
    issue_row(c.map, c.in_base + STAGE_BYTES, c.bar_full + 8, c.c0, c.u0, c.h0 + 3 * c.hstep);
#pragma unroll
    for (int d = 0; d < PF_DIST; d++) prefetch_row(c, c.h0 + (4 + d) * c.hstep);
  }
  __syncwarp();
  DBG_T(c, 46);
  mbar_wait(c.bar_full, 0);
  DBG_T(c, 52);
  ld3(U, c.aU, 0);
  ld3(V, c.aU, OFF_V);
  DBG_T(c, 2);
  mbar_wait(SMEM_BASE + (RANK << 24) + OFF_BAR + 8 * BAR_W + 24, 0);
  asm volatile("barrier.cluster.wait.acquire.aligned;" ::: "memory");
  DBG_T(c, 3);
#pragma unroll 1
  for (int n = 0; n < ROWS_PER_STRIP; n += 2) {
    unit<RANK, 0>(c, n, X, Y, T, U, V);
    unit<RANK, 1>(c, n + 1, X, Y, T, U, V);
  }
  uint32_t P[6][4];
  mbar_wait(c.xfull, (ROWS_PER_STRIP - 1) & 1);
  load_partner<0, 6>(c, P);
  wg_wait<0>();
  finish_chunks<0, 6>(c, Y, P);
  store_row(c, c.h0 + ROWS_PER_STRIP * c.hstep);
  asm volatile("cp.async.bulk.wait_group.read 0;" ::: "memory");
  DBG_T(c, 40); DBG_G(c, 1); DBG_FLUSH(c);
}

__global__ void __cluster_dims__(2, 1, 1) __launch_bounds__(256, 1)
dilated_conv_wino_kernel(const __grid_constant__ CUtensorMap xmap, const __grid_constant__ CUtensorMap omap,
                         const __nv_bfloat16* __restrict__ x, const __nv_bfloat16* __restrict__ w) {
  extern __shared__ uint8_t smem_raw[];
  const int tid = threadIdx.x;
  const int wg = __shfl_sync(0xffffffff, tid >> 7, 0);
  const int warp = __shfl_sync(0xffffffff, (tid >> 5) & 3, 0);
  const int lane = tid & 31;
  const int rank = blockIdx.x & 1;
  const uint32_t sbase = SMEM_BASE + (rank << 24);
  if ((uint32_t)__cvta_generic_to_shared(smem_raw) != sbase || mapa(sbase, rank ^ 1) != (sbase ^ 0x01000000u)) __trap();
  const int sid = (blockIdx.x >> 1) * 2 + wg;
  const int seg = sid & 3, par = (sid >> 2) & 1, strip = sid >> 3;
  const bool down = (strip & 1) == 0;
  const int r0 = strip * ROWS_PER_STRIP;

  Ctx c;
  c.map = &xmap;
  c.wg = wg;
  c.in_base = sbase + OFF_IN + wg * NSTAGE * STAGE_BYTES;
  c.bar_full = sbase + OFF_BAR + 8 * (BAR_FULL + wg * NSTAGE);
  c.c0 = rank * 48;
  c.u0 = seg * 16;
  c.h0 = 2 * (down ? r0 - 1 : r0 + ROWS_PER_STRIP) + par;
  c.hstep = down ? 2 : -2;
  c.lane0 = lane == 0;
  c.producer = (tid & 127) == 0;
  c.warp0 = warp == 0;
  c.xfull = sbase + OFF_BAR + 8 * (BAR_XFULL + wg * 4 + warp);
  c.xseg = reinterpret_cast<const char*>(x) + (seg * 128 + rank * 64) * (CH * 2);

  DBG_G(c, 0); DBG_T(c, 0);
  const uint32_t bar_w = sbase + OFF_BAR + 8 * BAR_W;
  const uint32_t o_w0 = (rank ? 2 : 3) * 9 * BT_BYTES, o_w2 = (rank ? 3 : 2) * 9 * BT_BYTES;
  if (tid == 224) {
    for (int a = 0; a < 3; a++) mbar_init(bar_w + 8 * a, 1);
    asm volatile("fence.proxy.async.shared::cta;" ::: "memory");
#pragma unroll 1
    for (int a = 0; a < 3; a++) {
      const int i = down ? a : 2 - a;
      const __nv_bfloat16* src = w + ((size_t)(i * 3) * CH + rank * 48) * CH;
      const uint32_t dst = sbase + OFF_W + a * 3 * BT_BYTES;
      mbar_expect_tx(bar_w + 8 * a, 9 * BT_BYTES);
      bulk_load(dst + o_w0, src, 3 * BT_BYTES, bar_w + 8 * a);
      bulk_load(dst, src + CH * CH, 3 * BT_BYTES, bar_w + 8 * a);
      bulk_load(dst + o_w2, src + 2 * CH * CH, 3 * BT_BYTES, bar_w + 8 * a);
      DBG_TA(53 + a);
    }
  } else if (tid == 0) {
    asm volatile("prefetch.tensormap [%0];" ::"l"(&xmap) : "memory");
    asm volatile("prefetch.tensormap [%0];" ::"l"(&omap) : "memory");
    for (int i = 0; i < 4; i++) { mbar_init(sbase + OFF_BAR + 8 * i, 1); mbar_init(sbase + OFF_BAR + EMPTY_OFF + 8 * i, 4); }
    mbar_init(bar_w + 24, 6);
    mbar_init(sbase + OFF_BAR + 8 * BAR_ROW0, 1);
    mbar_init(sbase + OFF_BAR + 8 * BAR_ROW0 + 8, 1);
  }
  if (c.lane0) {
    mbar_init(c.xfull, 1);
    mbar_init(c.xfull + 64, 1);
    mbar_expect_tx(c.xfull, X_BYTES);
    asm volatile("fence.mbarrier_init.release.cluster;" ::: "memory");
    asm volatile("fence.proxy.async.shared::cta;" ::: "memory");
  }
  DBG_T(c, 45);
  __syncthreads();
  DBG_T(c, 41);
  const uint32_t row0 = sbase + (wg ? OFF_TMP : OFF_X);
  const uint32_t bar_row0 = sbase + OFF_BAR + 8 * (BAR_ROW0 + wg);
  if (warp == 3) {
    if (c.lane0) {
      issue_row(&xmap, row0, bar_row0, c.c0, c.u0, c.h0);
      DBG_TA(47);
      issue_row(&xmap, c.in_base + STAGE_BYTES, c.bar_full + 8, c.c0, c.u0, c.h0 + c.hstep);
      DBG_TA(48);
      issue_row(&xmap, c.in_base, c.bar_full, c.c0, c.u0, c.h0 + 2 * c.hstep);
      DBG_TA(49);
    }
    __syncwarp();
  } else {
#pragma unroll 1
    for (int age = 0; age < 3; age++) {
      const uint32_t base = sbase + OFF_W + (age * 6 + wg * 3 + warp) * 1536;
      mbar_wait(bar_w + 8 * age, 0);
      DBG_T(c, 42 + age);
      uint32_t wa[3][4], wb[3][4], wd[3][4];
      const uint32_t src = base + (lane >> 2) * 192 + (lane & 3) * 16;
#pragma unroll
      for (int m = 0; m < 3; m++) {
        lds4(wa[m], src + o_w0 + m * 64);
        lds4(wb[m], src + m * 64);
        lds4(wd[m], src + o_w2 + m * 64);
      }
      __syncwarp();
      const uint32_t dst = base + lane * 16;
#pragma unroll
      for (int m = 0; m < 3; m++) {
        uint32_t g1[4], g2[4];
        stsm4(dst + m * 512 + o_w0, wa[m][0], wa[m][1], wa[m][2], wa[m][3]);
        stsm4(dst + m * 512 + o_w2, wd[m][0], wd[m][1], wd[m][2], wd[m][3]);
#pragma unroll
        for (int ss = 0; ss < 4; ss++) {
          const uint32_t a = wa[m][ss], b = wb[m][ss], d = wd[m][ss];
          const float slo = __uint_as_float(a << 16) + __uint_as_float(d << 16);
          const float shi = __uint_as_float(a & 0xffff0000u) + __uint_as_float(d & 0xffff0000u);
          const float blo = 0.5f * __uint_as_float(b << 16), bhi = 0.5f * __uint_as_float(b & 0xffff0000u);
          g1[ss] = pack2(fmaf(slo, 0.5f, blo), fmaf(shi, 0.5f, bhi));
          g2[ss] = pack2(fmaf(slo, 0.5f, -blo), fmaf(shi, 0.5f, -bhi));
        }
        stsm4(dst + m * 512, g1[0], g1[1], g1[2], g1[3]);
        stsm4(dst + m * 512 + 9 * BT_BYTES, g2[0], g2[1], g2[2], g2[3]);
      }
    }
    asm volatile("fence.proxy.async.shared::cta;" ::: "memory");
    __syncwarp();
    if (c.lane0) mbar_arrive(bar_w + 24);
  }
  DBG_T(c, 1);

  const int b = warp & 1, uh = warp >> 1;
  {
    const int g = lane & 7, mi = lane >> 3;
    const int rU = ((mi & 1) * 2 + b) * 17 + 8 * uh + g;
    const int rE = b * 17 + 8 * uh + g + 1;
    c.aU = c.in_base + rU * 128 + (((mi >> 1) ^ (rU & 7)) << 4);
    c.aE = c.in_base + rE * 128 + ((mi ^ (rE & 7)) << 4);
  }
  c.xbase = sbase + OFF_X + (wg * 4 + warp) * X_BYTES;
  c.xaddr = c.xbase + (lane >> 2) * 192 + (lane & 3) * 16;
  c.omap = &omap;
  c.ou = c.u0 + 8 * uh;
  c.ob = b + 2 * rank;
  if (rank == 0) run_strip<0>(c, row0 - c.in_base, bar_row0); else run_strip<1>(c, row0 - c.in_base, bar_row0);
}

typedef CUresult (*EncodeTiledFn)(CUtensorMap*, CUtensorMapDataType, cuuint32_t, void*, const cuuint64_t*, const cuuint64_t*,
                                  const cuuint32_t*, const cuuint32_t*, CUtensorMapInterleave, CUtensorMapSwizzle,
                                  CUtensorMapL2promotion, CUtensorMapFloatOOBfill);

}

extern "C" void kernel_launch(void* const* d_in, const int* in_sizes, int n_in, void* d_out, int out_size) {
  (void)in_sizes; (void)n_in; (void)out_size;
  static EncodeTiledFn encode = nullptr;
  if (!encode) {
    void* fn = nullptr;
    cudaDriverEntryPointQueryResult qr;
    cudaGetDriverEntryPoint("cuTensorMapEncodeTiled", &fn, cudaEnableDefault, &qr);
    encode = (EncodeTiledFn)fn;
    cudaFuncSetAttribute(dilated_conv_wino_kernel, cudaFuncAttributeMaxDynamicSharedMemorySize, SMEM_BYTES);
  }
  CUtensorMap xmap;
  const cuuint64_t dims[5] = {CH, IMG_W / 8, 4, 2, IMG_H};
  const cuuint64_t strides[4] = {8 * CH * 2, CH * 2, 4 * CH * 2, IMG_W * CH * 2};
  const cuuint32_t box[5] = {48, 17, 2, 2, 1};
  const cuuint32_t estr[5] = {1, 1, 1, 1, 1};
#define PROMO CU_TENSOR_MAP_L2_PROMOTION_L2_128B
  encode(&xmap, CU_TENSOR_MAP_DATA_TYPE_BFLOAT16, 5, d_in[0], dims, strides, box, estr, CU_TENSOR_MAP_INTERLEAVE_NONE,
         CU_TENSOR_MAP_SWIZZLE_128B, PROMO, CU_TENSOR_MAP_FLOAT_OOB_FILL_NONE);
  CUtensorMap omap;
  const cuuint64_t odims[5] = {CH, IMG_W / 8, 2, 4, IMG_H};
  const cuuint64_t ostrides[4] = {8 * CH * 2, 4 * CH * 2, CH * 2, IMG_W * CH * 2};
  const cuuint32_t obox[5] = {CH, 8, 2, 1, 1};
  encode(&omap, CU_TENSOR_MAP_DATA_TYPE_BFLOAT16, 5, d_out, odims, ostrides, obox, estr, CU_TENSOR_MAP_INTERLEAVE_NONE,
         CU_TENSOR_MAP_SWIZZLE_NONE, CU_TENSOR_MAP_L2_PROMOTION_NONE, CU_TENSOR_MAP_FLOAT_OOB_FILL_NONE);
  dilated_conv_wino_kernel<<<128, 256, SMEM_BYTES>>>(xmap, omap, (const __nv_bfloat16*)d_in[0], (const __nv_bfloat16*)d_in[1]);
}
```

```cpp
#include <cuda_runtime.h>
#include <cuda_bf16.h>
#include <cuda.h>
#include <stdint.h>

namespace {

constexpr int IMG_H = 512, IMG_W = 512, CH = 96;
constexpr int ROWS_PER_STRIP = 16;
constexpr int NSTAGE = 2;

constexpr int BT_BYTES   = 3072;
constexpr int W_BYTES    = 36 * BT_BYTES;
constexpr int BOX_BYTES  = 68 * 96;
constexpr int OFF_BOXB   = 70 * 128;
constexpr int STAGE_BYTES = 144 * 128;
constexpr int OFF_V      = 72 * 128;
constexpr int WG_IN_BYTES = STAGE_BYTES + 138 * 128;
constexpr int OFF_W      = 0;
constexpr int OFF_IN     = OFF_W + W_BYTES;
constexpr int OFF_X      = OFF_IN + 2 * WG_IN_BYTES;
constexpr int X_BYTES    = 3072;
constexpr int XBUF_BYTES = 4 * X_BYTES;
constexpr int SMEM_BYTES = OFF_X + 4 * XBUF_BYTES;
constexpr int OFF_ROW0_0 = OFF_X + ((OFF_IN - OFF_X) & 1023);
constexpr int OFF_ROW0_1 = OFF_X + 2 * XBUF_BYTES + ((OFF_IN + WG_IN_BYTES - OFF_X) & 1023);
constexpr int OFF_BAR    = OFF_IN + 68 * 128;
constexpr int BAR_FULL = 0, BAR_XFULL = 8, BAR_W = 24, BAR_ROW0 = 28, BAR_READY = 30;
constexpr int OFF_DBG    = OFF_IN + 138 * 128;
static_assert(SMEM_BYTES <= 232448, "shared memory");
constexpr uint32_t SMEM_BASE = 1024;
constexpr uint64_t BDESC = (uint64_t)((SMEM_BASE + OFF_W) >> 4) | ((uint64_t)(1536 >> 4) << 16) | ((uint64_t)(128 >> 4) << 32);

__device__ __forceinline__ void wg_fence()  { asm volatile("wgmma.fence.sync.aligned;" ::: "memory"); }
__device__ __forceinline__ void wg_commit() { asm volatile("wgmma.commit_group.sync.aligned;" ::: "memory"); }
template <int N> __device__ __forceinline__ void wg_wait() { asm volatile("wgmma.wait_group.sync.aligned %0;" ::"n"(N) : "memory"); }

template <int SCALE_D, uint64_t DESC>
__device__ __forceinline__ void wgmma96(float (&d)[48], const uint32_t (&a)[4]) {
  asm volatile(
      "{\n.reg .pred p;\nsetp.ne.b32 p, %53, 0;\n"
      "wgmma.mma_async.sync.aligned.m64n96k16.f32.bf16.bf16 "
      "{%0,%1,%2,%3,%4,%5,%6,%7,%8,%9,%10,%11,%12,%13,%14,%15,%16,%17,%18,%19,%20,%21,%22,%23,"
      "%24,%25,%26,%27,%28,%29,%30,%31,%32,%33,%34,%35,%36,%37,%38,%39,%40,%41,%42,%43,%44,%45,%46,%47}, "
      "{%48,%49,%50,%51}, %52, p, 1, 1, 1;\n}\n"
      : "+f"(d[0]), "+f"(d[1]), "+f"(d[2]), "+f"(d[3]), "+f"(d[4]), "+f"(d[5]), "+f"(d[6]), "+f"(d[7]),
        "+f"(d[8]), "+f"(d[9]), "+f"(d[10]), "+f"(d[11]), "+f"(d[12]), "+f"(d[13]), "+f"(d[14]), "+f"(d[15]),
        "+f"(d[16]), "+f"(d[17]), "+f"(d[18]), "+f"(d[19]), "+f"(d[20]), "+f"(d[21]), "+f"(d[22]), "+f"(d[23]),
        "+f"(d[24]), "+f"(d[25]), "+f"(d[26]), "+f"(d[27]), "+f"(d[28]), "+f"(d[29]), "+f"(d[30]), "+f"(d[31]),
        "+f"(d[32]), "+f"(d[33]), "+f"(d[34]), "+f"(d[35]), "+f"(d[36]), "+f"(d[37]), "+f"(d[38]), "+f"(d[39]),
        "+f"(d[40]), "+f"(d[41]), "+f"(d[42]), "+f"(d[43]), "+f"(d[44]), "+f"(d[45]), "+f"(d[46]), "+f"(d[47])
      : "r"(a[0]), "r"(a[1]), "r"(a[2]), "r"(a[3]), "l"(DESC), "n"(SCALE_D));
}

__device__ __forceinline__ void ldsm4(uint32_t (&r)[4], uint32_t addr) {
  asm volatile("ldmatrix.sync.aligned.m8n8.x4.shared.b16 {%0,%1,%2,%3}, [%4];"
               : "=r"(r[0]), "=r"(r[1]), "=r"(r[2]), "=r"(r[3]) : "r"(addr) : "memory");
}
__device__ __forceinline__ uint32_t badd(uint32_t a, uint32_t b) {
  uint32_t d; asm volatile("add.rn.bf16x2 %0, %1, %2;" : "=r"(d) : "r"(a), "r"(b)); return d;
}
__device__ __forceinline__ uint32_t bsub(uint32_t a, uint32_t b) {
  uint32_t d; asm volatile("sub.rn.bf16x2 %0, %1, %2;" : "=r"(d) : "r"(a), "r"(b)); return d;
}
__device__ __forceinline__ uint32_t pack2(float lo, float hi) {
  uint32_t d; asm volatile("cvt.rn.bf16x2.f32 %0, %1, %2;" : "=r"(d) : "f"(hi), "f"(lo)); return d;
}

__device__ __forceinline__ void mbar_wait(uint32_t bar, uint32_t parity) {
  asm volatile(
      "{\n.reg .pred p;\n.reg .u32 it;\n"
      "mbarrier.try_wait.parity.shared::cta.b64 p, [%0], %1;\n"
      "@p bra WAIT_DONE;\n"
      "mov.u32 it, 0;\n"
      "WAIT_LOOP:\n"
      ".pragma \"nounroll\";\n"
      "mbarrier.try_wait.parity.shared::cta.b64 p, [%0], %1;\n"
      "@p bra WAIT_DONE;\n"
      "add.u32 it, it, 1;\n"
      "setp.lt.u32 p, it, 4194304;\n"
      "@p bra WAIT_LOOP;\n"
      "trap;\n"
      "WAIT_DONE:\n}\n" ::"r"(bar), "r"(parity) : "memory");
}
__device__ __forceinline__ bool mbar_try(uint32_t bar, uint32_t parity) {
  uint32_t ok;
  asm volatile("{\n.reg .pred p;\nmbarrier.test_wait.parity.shared::cta.b64 p, [%1], %2;\nselp.u32 %0, 1, 0, p;\n}\n"
               : "=r"(ok) : "r"(bar), "r"(parity) : "memory");
  return ok;
}
__device__ __forceinline__ void mbar_init(uint32_t bar, uint32_t count) {
  asm volatile("mbarrier.init.shared::cta.b64 [%0], %1;" ::"r"(bar), "r"(count) : "memory");
}
__device__ __forceinline__ void mbar_arrive(uint32_t bar) {
  asm volatile("mbarrier.arrive.shared::cta.b64 _, [%0];" ::"r"(bar) : "memory");
}
__device__ __forceinline__ void mbar_expect_tx(uint32_t bar, uint32_t bytes) {
  asm volatile("mbarrier.arrive.expect_tx.shared::cta.b64 _, [%0], %1;" ::"r"(bar), "r"(bytes) : "memory");
}
__device__ __forceinline__ void tma_load5(uint32_t dst, const CUtensorMap* map, uint32_t bar, int c0, int c1, int c2, int c3, int c4) {
  asm volatile("cp.async.bulk.tensor.5d.shared::cluster.global.mbarrier::complete_tx::bytes [%0], [%1, {%3,%4,%5,%6,%7}], [%2];"
               ::"r"(dst), "l"(map), "r"(bar), "r"(c0), "r"(c1), "r"(c2), "r"(c3), "r"(c4) : "memory");
}
__device__ __forceinline__ void bulk_load(uint32_t dst, const void* src, uint32_t bytes, uint32_t bar) {
  asm volatile("cp.async.bulk.shared::cluster.global.mbarrier::complete_tx::bytes [%0], [%1], %2, [%3];"
               ::"r"(dst), "l"(src), "r"(bytes), "r"(bar) : "memory");
}
template <int OFF>
__device__ __forceinline__ void st_async4(uint32_t cluster_addr, uint32_t cluster_bar, uint32_t a, uint32_t b, uint32_t c, uint32_t d) {
  asm volatile("st.async.shared::cluster.mbarrier::complete_tx::bytes.v4.b32 [%0+%6], {%2,%3,%4,%5}, [%1];"
               ::"r"(cluster_addr), "r"(cluster_bar), "r"(a), "r"(b), "r"(c), "r"(d), "n"(OFF) : "memory");
}
__device__ __forceinline__ void stsm4(uint32_t addr, uint32_t a, uint32_t b, uint32_t c, uint32_t d) {
  asm volatile("stmatrix.sync.aligned.m8n8.x4.shared.b16 [%0], {%1,%2,%3,%4};" ::"r"(addr), "r"(a), "r"(b), "r"(c), "r"(d) : "memory");
}
__device__ __forceinline__ uint32_t bfma(uint32_t a, uint32_t b, uint32_t c) {
  uint32_t d; asm volatile("fma.rn.bf16x2 %0, %1, %2, %3;" : "=r"(d) : "r"(a), "r"(b), "r"(c)); return d;
}
__device__ __forceinline__ void lds4(uint32_t (&r)[4], uint32_t addr) {
  asm volatile("ld.shared.v4.b32 {%0,%1,%2,%3}, [%4];" : "=r"(r[0]), "=r"(r[1]), "=r"(r[2]), "=r"(r[3]) : "r"(addr) : "memory");
}
__device__ __forceinline__ void sts4(uint32_t addr, const uint32_t (&r)[4]) {
  asm volatile("st.shared.v4.b32 [%0], {%1,%2,%3,%4};" ::"r"(addr), "r"(r[0]), "r"(r[1]), "r"(r[2]), "r"(r[3]) : "memory");
}
__device__ __forceinline__ void tma_store5(const CUtensorMap* map, uint32_t src, int c0, int c1, int c2, int c3, int c4) {
  asm volatile("cp.async.bulk.tensor.5d.global.shared::cta.bulk_group [%0, {%2,%3,%4,%5,%6}], [%1];"
               ::"l"(map), "r"(src), "r"(c0), "r"(c1), "r"(c2), "r"(c3), "r"(c4) : "memory");
  asm volatile("cp.async.bulk.commit_group;" ::: "memory");
}
__device__ __forceinline__ bool elect_one() {
  uint32_t p;
  asm volatile("{\n.reg .pred P;\nelect.sync _|P, 0xffffffff;\nselp.u32 %0, 1, 0, P;\n}\n" : "=r"(p));
  return p;
}
__device__ __forceinline__ uint32_t mapa(uint32_t addr, uint32_t rank) {
  uint32_t r; asm("mapa.shared::cluster.u32 %0, %1, %2;" : "=r"(r) : "r"(addr), "r"(rank)); return r;
}

__device__ __forceinline__ void tr_sum(uint32_t (&t)[3][4], const uint32_t (&U)[3][4], const uint32_t (&V)[3][4]) {
#pragma unroll
  for (int k = 0; k < 3; k++)
#pragma unroll
    for (int i = 0; i < 4; i++) t[k][i] = badd(U[k][i], V[k][i]);
}
__device__ __forceinline__ void tr_dif(uint32_t (&t)[3][4], const uint32_t (&U)[3][4], const uint32_t (&V)[3][4]) {
#pragma unroll
  for (int k = 0; k < 3; k++)
#pragma unroll
    for (int i = 0; i < 4; i++) t[k][i] = bsub(V[k][i], U[k][i]);
}
__device__ __forceinline__ void tr_t0(uint32_t (&t)[3][4], const uint32_t (&V)[3][4], const uint32_t (&E)[3][4]) {
#pragma unroll
  for (int k = 0; k < 3; k++) {
    t[k][0] = bsub(E[k][0], V[k][0]); t[k][1] = bsub(V[k][0], V[k][1]);
    t[k][2] = bsub(E[k][2], V[k][2]); t[k][3] = bsub(V[k][2], V[k][3]);
  }
}
__device__ __forceinline__ void tr_t3(uint32_t (&t)[3][4], const uint32_t (&U)[3][4], const uint32_t (&E)[3][4]) {
#pragma unroll
  for (int k = 0; k < 3; k++) {
    t[k][0] = bsub(U[k][1], U[k][0]); t[k][1] = bsub(E[k][1], U[k][1]);
    t[k][2] = bsub(U[k][3], U[k][2]); t[k][3] = bsub(E[k][3], U[k][3]);
  }
}
__device__ __forceinline__ void ld3(uint32_t (&R)[3][4], uint32_t aU, int off) {
#pragma unroll
  for (int k = 0; k < 3; k++) ldsm4(R[k], (aU ^ (32 * k)) + off);
}
template <int COMP, int AGE, int FIRST>
__device__ __forceinline__ void batch(float (&acc)[48], const uint32_t (&t)[3][4]) {
  constexpr int base = ((COMP * 3 + AGE) * 3) * BT_BYTES;
  wgmma96<FIRST ? 0 : 1, BDESC + ((base) >> 4)>(acc, t[0]);
  wgmma96<1, BDESC + ((base + BT_BYTES) >> 4)>(acc, t[1]);
  wgmma96<1, BDESC + ((base + 2 * BT_BYTES) >> 4)>(acc, t[2]);
  wg_commit();
}

#define DBG_T(c, idx)
#define DBG_TA(idx)
#define TL(c, k)
#define DBG_U(c, idx)
#define DBG_FLUSH(c)
#define DBG_G(c, idx)

struct Ctx {
  uint32_t aU, aE;
  uint32_t in_base;
  uint32_t bar_full;
  uint32_t xaddr, xfull;
  uint32_t xbase;
  const CUtensorMap* omap;
  const CUtensorMap* map;
  const char* xseg;
  int wg, warp;
  int c0, u0, h0, hstep;
  bool producer;
};

__device__ __forceinline__ void prefetch_row(const Ctx& c, int h) {
  if ((unsigned)h < (unsigned)IMG_H)
    asm volatile("cp.async.bulk.prefetch.L2.global [%0], %1;" ::"l"(c.xseg + (size_t)h * (IMG_W * CH * 2)), "r"(64 * CH * 2) : "memory");
}

template <int BUF, int C0, int C1>
__device__ __forceinline__ void load_partner(const Ctx& c, uint32_t (&P)[6][4]) {
#pragma unroll
  for (int ch = C0; ch < C1; ch++) lds4(P[ch], c.xaddr + BUF * XBUF_BYTES + (ch & 1) * 6144 + (ch >> 1) * 64);
}
template <int BUF, int C0, int C1>
__device__ __forceinline__ void finish_chunks(const Ctx& c, const float (&Y)[48], uint32_t (&P)[6][4]) {
#pragma unroll
  for (int ch = C0; ch < C1; ch++) {
    const int m = ch >> 1, s = ch & 1;
#pragma unroll
    for (int ss = 0; ss < 4; ss++) P[ch][ss] = badd(pack2(Y[16 * m + 4 * ss + 2 * s], Y[16 * m + 4 * ss + 2 * s + 1]), P[ch][ss]);
    sts4(c.xaddr + BUF * XBUF_BYTES + s * 6144 + m * 64, P[ch]);
  }
}
template <int RANK, int BUF, int CH0>
__device__ __forceinline__ void send_chunk(const Ctx& c, const float (&X)[48]) {
  constexpr uint32_t RDELTA = RANK ? 0xFF000000u : 0x01000000u;
  constexpr int m = CH0 >> 1, s = CH0 & 1;
  uint32_t o[4];
#pragma unroll
  for (int ss = 0; ss < 4; ss++) o[ss] = pack2(X[16 * m + 4 * ss + 2 * s], X[16 * m + 4 * ss + 2 * s + 1]);
  st_async4<BUF * XBUF_BYTES + s * 6144 + m * 64>(c.xaddr + RDELTA, c.xfull + BUF * 64 + RDELTA, o[0], o[1], o[2], o[3]);
}

#define PF_DIST 1
#define ORD1 0
#define ORD2 0

struct Regs {
  float X[48], Y[48];
  uint32_t T[4][2][3][4];
  uint32_t U[3][4], V[3][4], E[3][4];
};

template <int RANK, int OLD, bool FIRST>
__device__ __forceinline__ void phase1(const Ctx& c, int n, Regs& r) {
  constexpr int MID = 1 - OLD;
  if (FIRST) {
    wg_fence();
    batch<0, 0, 1>(r.X, r.T[0][OLD]);
    batch<0, 1, 0>(r.X, r.T[0][MID]);
    mbar_wait(c.bar_full + 8 * OLD, 0);
    ld3(r.U, c.aU, OLD * STAGE_BYTES);
    ld3(r.V, c.aU, OLD * STAGE_BYTES + OFF_V);
    wg_wait<1>();
  } else {
    uint32_t P[6][4];
    wg_fence();
    batch<0, 0, 1>(r.X, r.T[0][OLD]);
    if (ORD1 == 1) batch<0, 1, 0>(r.X, r.T[0][MID]);
    mbar_wait(c.xfull + MID * 64, ((n - 1) >> 1) & 1);
    load_partner<MID, 0, 3>(c, P);
    if (RANK == 0) ld3(r.V, c.aU, OLD * STAGE_BYTES + OFF_V); else ld3(r.U, c.aU, OLD * STAGE_BYTES);
    load_partner<MID, 3, 6>(c, P);
    if (elect_one()) mbar_expect_tx(c.xfull + MID * 64, X_BYTES);
    wg_wait<ORD1 == 1 ? 2 : 1>();
    finish_chunks<MID, 0, 3>(c, r.Y, P);
    if (ORD1 != 1) { wg_fence(); batch<0, 1, 0>(r.X, r.T[0][MID]); }
    finish_chunks<MID, 3, 6>(c, r.Y, P);
    wg_wait<1>();
  }
  tr_sum(r.T[0][OLD], r.U, r.V);
  wg_fence();
  batch<0, 2, 0>(r.X, r.T[0][OLD]);
  if (c.wg == 1) asm volatile("bar.sync 1, 256;" ::: "memory");
  batch<1, 0, 1>(r.Y, r.T[1][OLD]);
  batch<1, 1, 0>(r.Y, r.T[1][MID]);
  ld3(r.E, c.aE, OLD * STAGE_BYTES);
  wg_wait<1>();
  tr_dif(r.T[1][OLD], r.U, r.V);
  wg_fence();
  batch<1, 2, 0>(r.Y, r.T[1][OLD]);
  asm volatile("fence.proxy.async.shared::cta;" ::: "memory");
  asm volatile("bar.sync %0, %1;" ::"r"(1 + c.wg), "r"(256 - 128 * c.wg) : "memory");
  if (elect_one()) {
    const int h = c.h0 + n * c.hstep;
    if (c.warp < 2) {
      if (n + 4 < ROWS_PER_STRIP + 2) {
        mbar_expect_tx(c.bar_full + 8 * OLD, BOX_BYTES);
        tma_load5(c.in_base + OLD * STAGE_BYTES + c.warp * OFF_BOXB, c.map, c.bar_full + 8 * OLD, c.c0, 2 * c.warp, c.u0 - c.warp, 0,
                  h + 4 * c.hstep);
      }
    } else if (c.warp == 2) {
      if (!FIRST) tma_store5(c.omap, c.xbase + MID * XBUF_BYTES, 0, c.u0, 0, RANK, h);
    } else {
      if (PF_DIST > 0 && n + 4 + PF_DIST < ROWS_PER_STRIP + 2) prefetch_row(c, h + (4 + PF_DIST) * c.hstep);
    }
  }
  __syncwarp();
  wg_wait<0>();
}

template <int RANK, int OLD, bool LAST>
__device__ __forceinline__ void phase2(const Ctx& c, int n, Regs& r) {
  constexpr int MID = 1 - OLD;
#pragma unroll
  for (int i = 0; i < 48; i++) {
    if (RANK == 0) asm volatile("sub.rn.f32 %0, %0, %1;\nfma.rn.f32 %1, %1, 0f40000000, %0;" : "+f"(r.X[i]), "+f"(r.Y[i]));
    else           asm volatile("add.rn.f32 %0, %0, %1;\nfma.rn.f32 %1, %1, 0fC0000000, %0;" : "+f"(r.X[i]), "+f"(r.Y[i]));
  }
  wg_fence();
  batch<2, 0, 0>(r.X, r.T[2][OLD]);
  batch<2, 1, 0>(r.X, r.T[2][MID]);
  if (!LAST) mbar_wait(c.bar_full + 8 * MID, ((n + 2 + MID) >> 1) & 1);
  wg_wait<1>();
  if (RANK == 0) tr_t3(r.T[2][OLD], r.U, r.E); else tr_t0(r.T[2][OLD], r.V, r.E);
  if (!LAST) { if (RANK == 0) ld3(r.U, c.aU, MID * STAGE_BYTES); else ld3(r.V, c.aU, MID * STAGE_BYTES + OFF_V); }
  wg_fence();
  batch<2, 2, 0>(r.X, r.T[2][OLD]);
  batch<3, 0, 0>(r.Y, r.T[3][OLD]);
  if (ORD2 == 1) batch<3, 1, 0>(r.Y, r.T[3][MID]);
  asm volatile("cp.async.bulk.wait_group.read 0;" ::: "memory");
  wg_wait<ORD2 == 1 ? 2 : 1>();
  send_chunk<RANK, OLD, 0>(c, r.X); send_chunk<RANK, OLD, 1>(c, r.X); send_chunk<RANK, OLD, 2>(c, r.X);
  if (ORD2 == 2) { wg_fence(); batch<3, 1, 0>(r.Y, r.T[3][MID]); }
  send_chunk<RANK, OLD, 3>(c, r.X); send_chunk<RANK, OLD, 4>(c, r.X); send_chunk<RANK, OLD, 5>(c, r.X);
  if (ORD2 == 0) { wg_fence(); batch<3, 1, 0>(r.Y, r.T[3][MID]); }
  wg_wait<1>();
  if (RANK == 0) tr_t0(r.T[3][OLD], r.V, r.E); else tr_t3(r.T[3][OLD], r.U, r.E);
  wg_fence();
  batch<3, 2, 0>(r.Y, r.T[3][OLD]);
}

template <int RANK>
__device__ __forceinline__ void run_strip(const Ctx& c, uint32_t row0_off, uint32_t bar_row0) {
  Regs r;
#pragma unroll
  for (int m = 0; m < 2; m++) {
    const uint32_t off = m ? STAGE_BYTES : row0_off;
    mbar_wait(m ? c.bar_full + 8 : bar_row0, 0);
    DBG_T(c, 50 + m);
    ld3(r.U, c.aU, off);
    ld3(r.V, c.aU, off + OFF_V);
    ld3(r.E, c.aE, off);
    tr_sum(r.T[0][m], r.U, r.V);
    tr_dif(r.T[1][m], r.U, r.V);
    tr_t3(r.T[RANK == 0 ? 2 : 3][m], r.U, r.E);
    tr_t0(r.T[RANK == 0 ? 3 : 2][m], r.V, r.E);
  }
  asm volatile("bar.sync %0, 128;" ::"r"(3 + c.wg) : "memory");
  asm volatile("barrier.cluster.wait.aligned;" ::: "memory");
  if (elect_one()) {
    if (c.warp < 2) {
      mbar_expect_tx(c.bar_full + 8, BOX_BYTES);
      tma_load5(c.in_base + STAGE_BYTES + c.warp * OFF_BOXB, c.map, c.bar_full + 8, c.c0, 2 * c.warp, c.u0 - c.warp, 0, c.h0 + 3 * c.hstep);
    } else if (c.warp == 2) {
      asm volatile("mbarrier.arrive.shared::cluster.b64 _, [%0];" ::"r"((bar_row0 + (BAR_READY - BAR_ROW0) * 8) ^ 0x01000000u) : "memory");
    }
  }
  __syncwarp();
  DBG_T(c, 46);
  mbar_wait(SMEM_BASE + (RANK << 24) + OFF_BAR + 8 * BAR_W + 24, 0);
  DBG_T(c, 3);
#pragma unroll
  for (int i = 0; i < 48; i++) { r.X[i] = 0.f; r.Y[i] = 0.f; }
  phase1<RANK, 0, true>(c, 0, r);
  mbar_wait(bar_row0 + (BAR_READY - BAR_ROW0) * 8, 0);
#pragma unroll 1
  for (int n = 0;; n += 2) {
    phase2<RANK, 0, false>(c, n, r);
    phase1<RANK, 1, false>(c, n + 1, r);
    if (n + 2 == ROWS_PER_STRIP) break;
    phase2<RANK, 1, false>(c, n + 1, r);
    phase1<RANK, 0, false>(c, n + 2, r);
  }
  phase2<RANK, 1, true>(c, ROWS_PER_STRIP - 1, r);
  DBG_T(c, 35);
  uint32_t P[6][4];
  mbar_wait(c.xfull + 64, ((ROWS_PER_STRIP - 1) >> 1) & 1);
  load_partner<1, 0, 6>(c, P);
  wg_wait<0>();
  finish_chunks<1, 0, 6>(c, r.Y, P);
  asm volatile("fence.proxy.async.shared::cta;" ::: "memory");
  asm volatile("bar.sync %0, 128;" ::"r"(3 + c.wg) : "memory");
  if (c.warp == 2 && elect_one()) {
    tma_store5(c.omap, c.xbase + XBUF_BYTES, 0, c.u0, 0, RANK, c.h0 + ROWS_PER_STRIP * c.hstep);
    asm volatile("cp.async.bulk.wait_group.read 0;" ::: "memory");
  }
  DBG_T(c, 40); DBG_G(c, 1); DBG_FLUSH(c);
}

__global__ void __cluster_dims__(2, 1, 1) __launch_bounds__(256, 1)
dilated_conv_wino_kernel(const __grid_constant__ CUtensorMap xmap, const __grid_constant__ CUtensorMap omap,
                         const __nv_bfloat16* __restrict__ x, const __nv_bfloat16* __restrict__ w) {
  extern __shared__ uint8_t smem_raw[];
  const int tid = threadIdx.x;
  const int wg = __shfl_sync(0xffffffff, tid >> 7, 0);
  const int warp = __shfl_sync(0xffffffff, (tid >> 5) & 3, 0);
  const int lane = tid & 31;
  const int rank = blockIdx.x & 1;
  const uint32_t sbase = SMEM_BASE + (rank << 24);
  if ((uint32_t)__cvta_generic_to_shared(smem_raw) != sbase || mapa(sbase, rank ^ 1) != (sbase ^ 0x01000000u)) __trap();
  const int sid = (blockIdx.x >> 1) * 2 + wg;
  const int seg = sid & 3, par = (sid >> 2) & 1, strip = sid >> 3;
  const bool down = (strip & 1) == 0;
  const int r0 = strip * ROWS_PER_STRIP;

  Ctx c;
  c.map = &xmap;
  c.wg = wg;
  c.warp = warp;
  c.in_base = sbase + OFF_IN + wg * WG_IN_BYTES;
  c.bar_full = sbase + OFF_BAR + 8 * (BAR_FULL + wg * NSTAGE);
  c.c0 = rank * 48;
  c.u0 = seg * 16;
  c.h0 = 2 * (down ? r0 - 1 : r0 + ROWS_PER_STRIP) + par;
  c.hstep = down ? 2 : -2;
  c.producer = (tid & 127) == 0;
  c.xfull = sbase + OFF_BAR + 8 * (BAR_XFULL + wg * 4 + warp);
  c.xseg = reinterpret_cast<const char*>(x) + (seg * 128 + rank * 64) * (CH * 2);

  DBG_G(c, 0); DBG_T(c, 0);
  const uint32_t bar_w = sbase + OFF_BAR + 8 * BAR_W;
  const uint32_t o_w0 = (rank ? 2 : 3) * 9 * BT_BYTES, o_w2 = (rank ? 3 : 2) * 9 * BT_BYTES;
  if (elect_one()) {
    const uint32_t b0 = sbase + OFF_BAR;
    const int w8 = wg * 4 + warp;
    if (w8 >= 5) {
      const int a = w8 - 5, i = down ? a : 2 - a;
      const __nv_bfloat16* src = w + ((size_t)(i * 3) * CH + rank * 48) * CH;
      const uint32_t dst = sbase + OFF_W + a * 3 * BT_BYTES;
      mbar_init(bar_w + 8 * a, 1);
      asm volatile("fence.proxy.async.shared::cta;" ::: "memory");
      mbar_expect_tx(bar_w + 8 * a, 9 * BT_BYTES);
      bulk_load(dst + o_w0, src, 3 * BT_BYTES, bar_w + 8 * a);
      bulk_load(dst, src + CH * CH, 3 * BT_BYTES, bar_w + 8 * a);
      bulk_load(dst + o_w2, src + 2 * CH * CH, 3 * BT_BYTES, bar_w + 8 * a);
      DBG_TA(53 + a);
    } else {
      if (w8 < 4) {
        mbar_init(b0 + 8 * w8, 2);
#pragma unroll
        for (int q = 0; q < 4; q++) mbar_init(b0 + 8 * (BAR_XFULL + 4 * w8 + q), 1);
        mbar_expect_tx(b0 + 8 * w8, BOX_BYTES);
        mbar_expect_tx(b0 + 8 * w8, BOX_BYTES);
      } else {
        asm volatile("prefetch.tensormap [%0];" ::"l"(&xmap) : "memory");
#pragma unroll
        for (int q = 0; q < 2; q++) {
          mbar_init(b0 + 8 * (BAR_ROW0 + q), 1);
          mbar_init(b0 + 8 * (BAR_READY + q), 1);
          mbar_expect_tx(b0 + 8 * (BAR_ROW0 + q), 2 * BOX_BYTES);
        }
        mbar_init(bar_w + 24, 6);
      }
      asm volatile("fence.mbarrier_init.release.cluster;" ::: "memory");
      asm volatile("fence.proxy.async.shared::cta;" ::: "memory");
    }
  }
  DBG_T(c, 45);
  __syncthreads();
  asm volatile("barrier.cluster.arrive.relaxed.aligned;" ::: "memory");
  DBG_T(c, 41);
  const uint32_t row0 = sbase + (wg ? OFF_ROW0_1 : OFF_ROW0_0);
  const uint32_t bar_row0 = sbase + OFF_BAR + 8 * (BAR_ROW0 + wg);
  if (warp == 3) {
    if (elect_one()) {
#pragma unroll 1
      for (int k = 0; k < 6; k++) {
        const int g = k & 1, m = k >> 1;
        const uint32_t dst = m == 0 ? sbase + (g ? OFF_ROW0_1 : OFF_ROW0_0) : sbase + OFF_IN + g * WG_IN_BYTES + (m & 1) * STAGE_BYTES;
        const uint32_t bar = sbase + OFF_BAR + 8 * (m == 0 ? BAR_ROW0 + g : BAR_FULL + 2 * g + (m & 1));
        tma_load5(dst + wg * OFF_BOXB, &xmap, bar, c.c0, 2 * wg, ((seg & 2) + g) * 16 - wg, 0, c.h0 + m * c.hstep);
      }
      asm volatile("prefetch.tensormap [%0];" ::"l"(&omap) : "memory");
      DBG_TA(49);
    }
    __syncwarp();
  } else {
#pragma unroll 1
    for (int age = 0; age < 3; age++) {
      const uint32_t base = sbase + OFF_W + (age * 6 + wg * 3 + warp) * 1536;
      mbar_wait(bar_w + 8 * age, 0);
      DBG_T(c, 42 + age);
      uint32_t wa[3][4], wb[3][4], wd[3][4];
      const uint32_t src = base + (lane >> 2) * 192 + (lane & 3) * 16;
#pragma unroll
      for (int m = 0; m < 3; m++) {
        lds4(wa[m], src + o_w0 + m * 64);
        lds4(wb[m], src + m * 64);
        lds4(wd[m], src + o_w2 + m * 64);
      }
      __syncwarp();
      const uint32_t dst = base + lane * 16;
#pragma unroll
      for (int m = 0; m < 3; m++) {
        uint32_t g1[4], g2[4];
        stsm4(dst + m * 512 + o_w0, wa[m][0], wa[m][1], wa[m][2], wa[m][3]);
        stsm4(dst + m * 512 + o_w2, wd[m][0], wd[m][1], wd[m][2], wd[m][3]);
#pragma unroll
        for (int ss = 0; ss < 4; ss++) {
          const uint32_t a = wa[m][ss], b = wb[m][ss], d = wd[m][ss];
          const float slo = __uint_as_float(a << 16) + __uint_as_float(d << 16);
          const float shi = __uint_as_float(a & 0xffff0000u) + __uint_as_float(d & 0xffff0000u);
          const float blo = 0.5f * __uint_as_float(b << 16), bhi = 0.5f * __uint_as_float(b & 0xffff0000u);
          g1[ss] = pack2(fmaf(slo, 0.5f, blo), fmaf(shi, 0.5f, bhi));
          g2[ss] = pack2(fmaf(slo, 0.5f, -blo), fmaf(shi, 0.5f, -bhi));
        }
        stsm4(dst + m * 512, g1[0], g1[1], g1[2], g1[3]);
        stsm4(dst + m * 512 + 9 * BT_BYTES, g2[0], g2[1], g2[2], g2[3]);
      }
    }
    asm volatile("fence.proxy.async.shared::cta;" ::: "memory");
    __syncwarp();
    if (elect_one()) mbar_arrive(bar_w + 24);
  }
  if (elect_one()) { mbar_expect_tx(c.xfull, X_BYTES); mbar_expect_tx(c.xfull + 64, X_BYTES); }
  DBG_T(c, 1);

  {
    const int g = lane & 7, mi = lane >> 3;
    const int rU = 8 * warp + g + ((mi & 1) ? 34 : 0);
    const int rE = 8 * warp + g + ((mi & 1) ? 2 : 70 + 34);
    const uint32_t pU = c.in_base + rU * 128, pE = c.in_base + rE * 128;
    c.aU = pU + (((mi >> 1) ^ ((pU >> 7) & 7)) << 4);
    c.aE = pE + (((mi >> 1) ^ ((pE >> 7) & 7)) << 4);
  }
  c.xbase = sbase + OFF_X + wg * 2 * XBUF_BYTES;
  c.xaddr = c.xbase + (warp * 8 + (lane >> 2)) * 192 + (lane & 3) * 16;
  c.omap = &omap;
  if (rank == 0) run_strip<0>(c, row0 - c.in_base, bar_row0); else run_strip<1>(c, row0 - c.in_base, bar_row0);
}

typedef CUresult (*EncodeTiledFn)(CUtensorMap*, CUtensorMapDataType, cuuint32_t, void*, const cuuint64_t*, const cuuint64_t*,
                                  const cuuint32_t*, const cuuint32_t*, CUtensorMapInterleave, CUtensorMapSwizzle,
                                  CUtensorMapL2promotion, CUtensorMapFloatOOBfill);

}

extern "C" void kernel_launch(void* const* d_in, const int* in_sizes, int n_in, void* d_out, int out_size) {
  (void)in_sizes; (void)n_in; (void)out_size;
  static EncodeTiledFn encode = nullptr;
  if (!encode) {
    void* fn = nullptr;
    cudaDriverEntryPointQueryResult qr;
    cudaGetDriverEntryPoint("cuTensorMapEncodeTiled", &fn, cudaEnableDefault, &qr);
    encode = (EncodeTiledFn)fn;
    cudaFuncSetAttribute(dilated_conv_wino_kernel, cudaFuncAttributeMaxDynamicSharedMemorySize, SMEM_BYTES);
  }
  CUtensorMap xmap;
  const cuuint64_t dims[5] = {CH, 4, IMG_W / 8, 2, IMG_H};
  const cuuint64_t strides[4] = {CH * 2, 8 * CH * 2, 4 * CH * 2, IMG_W * CH * 2};
  const cuuint32_t box[5] = {48, 2, 17, 2, 1};
  const cuuint32_t estr[5] = {1, 1, 1, 1, 1};
#define PROMO CU_TENSOR_MAP_L2_PROMOTION_L2_128B
  encode(&xmap, CU_TENSOR_MAP_DATA_TYPE_BFLOAT16, 5, d_in[0], dims, strides, box, estr, CU_TENSOR_MAP_INTERLEAVE_NONE,
         CU_TENSOR_MAP_SWIZZLE_128B, PROMO, CU_TENSOR_MAP_FLOAT_OOB_FILL_NONE);
  CUtensorMap omap;
  const cuuint64_t odims[5] = {2 * CH, IMG_W / 8, 2, 2, IMG_H};
  const cuuint64_t ostrides[4] = {8 * CH * 2, 4 * CH * 2, 2 * CH * 2, IMG_W * CH * 2};
  const cuuint32_t obox[5] = {2 * CH, 16, 2, 1, 1};
  encode(&omap, CU_TENSOR_MAP_DATA_TYPE_BFLOAT16, 5, d_out, odims, ostrides, obox, estr, CU_TENSOR_MAP_INTERLEAVE_NONE,
         CU_TENSOR_MAP_SWIZZLE_NONE, CU_TENSOR_MAP_L2_PROMOTION_NONE, CU_TENSOR_MAP_FLOAT_OOB_FILL_NONE);
  dilated_conv_wino_kernel<<<128, 256, SMEM_BYTES>>>(xmap, omap, (const __nv_bfloat16*)d_in[0], (const __nv_bfloat16*)d_in[1]);
}
```

```cpp
#include <cuda_runtime.h>
#include <cuda_bf16.h>
#include <cuda.h>
#include <stdint.h>

namespace {

constexpr int IMG_H = 512, IMG_W = 512, CH = 96;
constexpr int ROWS_PER_STRIP = 16;
constexpr int NSTAGE = 2;

constexpr int BT_BYTES   = 3072;
constexpr int W_BYTES    = 36 * BT_BYTES;
constexpr int BOX_BYTES  = 68 * 96;
constexpr int OFF_BOXB   = 70 * 128;
constexpr int STAGE_BYTES = 144 * 128;
constexpr int OFF_V      = 72 * 128;
constexpr int WG_IN_BYTES = STAGE_BYTES + 138 * 128;
constexpr int OFF_W      = 0;
constexpr int OFF_IN     = OFF_W + W_BYTES;
constexpr int OFF_X      = OFF_IN + 2 * WG_IN_BYTES;
constexpr int X_BYTES    = 3072;
constexpr int XBUF_BYTES = 4 * X_BYTES;
constexpr int SMEM_BYTES = OFF_X + 4 * XBUF_BYTES;
constexpr int OFF_ROW0_0 = OFF_X + ((OFF_IN - OFF_X) & 1023);
constexpr int OFF_ROW0_1 = OFF_X + 2 * XBUF_BYTES + ((OFF_IN + WG_IN_BYTES - OFF_X) & 1023);
constexpr int OFF_BAR    = OFF_IN + 68 * 128;
constexpr int BAR_FULL = 0, BAR_XFULL = 8, BAR_W = 24, BAR_ROW0 = 28, BAR_READY = 30;
constexpr int OFF_DBG    = OFF_IN + 138 * 128;
static_assert(SMEM_BYTES <= 232448, "shared memory");
constexpr uint32_t SMEM_BASE = 1024;
constexpr uint64_t BDESC = (uint64_t)((SMEM_BASE + OFF_W) >> 4) | ((uint64_t)(1536 >> 4) << 16) | ((uint64_t)(128 >> 4) << 32);

__device__ __forceinline__ void wg_fence()  { asm volatile("wgmma.fence.sync.aligned;" ::: "memory"); }
__device__ __forceinline__ void wg_commit() { asm volatile("wgmma.commit_group.sync.aligned;" ::: "memory"); }
template <int N> __device__ __forceinline__ void wg_wait() { asm volatile("wgmma.wait_group.sync.aligned %0;" ::"n"(N) : "memory"); }

template <int SCALE_D, uint64_t DESC>
__device__ __forceinline__ void wgmma96(float (&d)[48], const uint32_t (&a)[4]) {
  asm volatile(
      "{\n.reg .pred p;\nsetp.ne.b32 p, %53, 0;\n"
      "wgmma.mma_async.sync.aligned.m64n96k16.f32.bf16.bf16 "
      "{%0,%1,%2,%3,%4,%5,%6,%7,%8,%9,%10,%11,%12,%13,%14,%15,%16,%17,%18,%19,%20,%21,%22,%23,"
      "%24,%25,%26,%27,%28,%29,%30,%31,%32,%33,%34,%35,%36,%37,%38,%39,%40,%41,%42,%43,%44,%45,%46,%47}, "
      "{%48,%49,%50,%51}, %52, p, 1, 1, 1;\n}\n"
      : "+f"(d[0]), "+f"(d[1]), "+f"(d[2]), "+f"(d[3]), "+f"(d[4]), "+f"(d[5]), "+f"(d[6]), "+f"(d[7]),
        "+f"(d[8]), "+f"(d[9]), "+f"(d[10]), "+f"(d[11]), "+f"(d[12]), "+f"(d[13]), "+f"(d[14]), "+f"(d[15]),
        "+f"(d[16]), "+f"(d[17]), "+f"(d[18]), "+f"(d[19]), "+f"(d[20]), "+f"(d[21]), "+f"(d[22]), "+f"(d[23]),
        "+f"(d[24]), "+f"(d[25]), "+f"(d[26]), "+f"(d[27]), "+f"(d[28]), "+f"(d[29]), "+f"(d[30]), "+f"(d[31]),
        "+f"(d[32]), "+f"(d[33]), "+f"(d[34]), "+f"(d[35]), "+f"(d[36]), "+f"(d[37]), "+f"(d[38]), "+f"(d[39]),
        "+f"(d[40]), "+f"(d[41]), "+f"(d[42]), "+f"(d[43]), "+f"(d[44]), "+f"(d[45]), "+f"(d[46]), "+f"(d[47])
      : "r"(a[0]), "r"(a[1]), "r"(a[2]), "r"(a[3]), "l"(DESC), "n"(SCALE_D));
}

__device__ __forceinline__ void ldsm4(uint32_t (&r)[4], uint32_t addr) {
  asm volatile("ldmatrix.sync.aligned.m8n8.x4.shared.b16 {%0,%1,%2,%3}, [%4];"
               : "=r"(r[0]), "=r"(r[1]), "=r"(r[2]), "=r"(r[3]) : "r"(addr) : "memory");
}
__device__ __forceinline__ uint32_t badd(uint32_t a, uint32_t b) {
  uint32_t d; asm volatile("add.rn.bf16x2 %0, %1, %2;" : "=r"(d) : "r"(a), "r"(b)); return d;
}
__device__ __forceinline__ uint32_t bsub(uint32_t a, uint32_t b) {
  uint32_t d; asm volatile("sub.rn.bf16x2 %0, %1, %2;" : "=r"(d) : "r"(a), "r"(b)); return d;
}
__device__ __forceinline__ uint32_t pack2(float lo, float hi) {
  uint32_t d; asm volatile("cvt.rn.bf16x2.f32 %0, %1, %2;" : "=r"(d) : "f"(hi), "f"(lo)); return d;
}

__device__ __forceinline__ void mbar_wait(uint32_t bar, uint32_t parity) {
  asm volatile(
      "{\n.reg .pred p;\n.reg .u32 it;\n"
      "mbarrier.try_wait.parity.shared::cta.b64 p, [%0], %1;\n"
      "@p bra WAIT_DONE;\n"
      "mov.u32 it, 0;\n"
      "WAIT_LOOP:\n"
      ".pragma \"nounroll\";\n"
      "mbarrier.try_wait.parity.shared::cta.b64 p, [%0], %1;\n"
      "@p bra WAIT_DONE;\n"
      "add.u32 it, it, 1;\n"
      "setp.lt.u32 p, it, 4194304;\n"
      "@p bra WAIT_LOOP;\n"
      "trap;\n"
      "WAIT_DONE:\n}\n" ::"r"(bar), "r"(parity) : "memory");
}
__device__ __forceinline__ bool mbar_try(uint32_t bar, uint32_t parity) {
  uint32_t ok;
  asm volatile("{\n.reg .pred p;\nmbarrier.test_wait.parity.shared::cta.b64 p, [%1], %2;\nselp.u32 %0, 1, 0, p;\n}\n"
               : "=r"(ok) : "r"(bar), "r"(parity) : "memory");
  return ok;
}
__device__ __forceinline__ void mbar_init(uint32_t bar, uint32_t count) {
  asm volatile("mbarrier.init.shared::cta.b64 [%0], %1;" ::"r"(bar), "r"(count) : "memory");
}
__device__ __forceinline__ void mbar_arrive(uint32_t bar) {
  asm volatile("mbarrier.arrive.shared::cta.b64 _, [%0];" ::"r"(bar) : "memory");
}
__device__ __forceinline__ void mbar_expect_tx(uint32_t bar, uint32_t bytes) {
  asm volatile("mbarrier.arrive.expect_tx.shared::cta.b64 _, [%0], %1;" ::"r"(bar), "r"(bytes) : "memory");
}
__device__ __forceinline__ void tma_load5(uint32_t dst, const CUtensorMap* map, uint32_t bar, int c0, int c1, int c2, int c3, int c4) {
  asm volatile("cp.async.bulk.tensor.5d.shared::cluster.global.mbarrier::complete_tx::bytes [%0], [%1, {%3,%4,%5,%6,%7}], [%2];"
               ::"r"(dst), "l"(map), "r"(bar), "r"(c0), "r"(c1), "r"(c2), "r"(c3), "r"(c4) : "memory");
}
__device__ __forceinline__ void bulk_load(uint32_t dst, const void* src, uint32_t bytes, uint32_t bar) {
  asm volatile("cp.async.bulk.shared::cluster.global.mbarrier::complete_tx::bytes [%0], [%1], %2, [%3];"
               ::"r"(dst), "l"(src), "r"(bytes), "r"(bar) : "memory");
}
template <int OFF>
__device__ __forceinline__ void st_async4(uint32_t cluster_addr, uint32_t cluster_bar, uint32_t a, uint32_t b, uint32_t c, uint32_t d) {
  asm volatile("st.async.shared::cluster.mbarrier::complete_tx::bytes.v4.b32 [%0+%6], {%2,%3,%4,%5}, [%1];"
               ::"r"(cluster_addr), "r"(cluster_bar), "r"(a), "r"(b), "r"(c), "r"(d), "n"(OFF) : "memory");
}
__device__ __forceinline__ void stsm4(uint32_t addr, uint32_t a, uint32_t b, uint32_t c, uint32_t d) {
  asm volatile("stmatrix.sync.aligned.m8n8.x4.shared.b16 [%0], {%1,%2,%3,%4};" ::"r"(addr), "r"(a), "r"(b), "r"(c), "r"(d) : "memory");
}
__device__ __forceinline__ uint32_t bfma(uint32_t a, uint32_t b, uint32_t c) {
  uint32_t d; asm volatile("fma.rn.bf16x2 %0, %1, %2, %3;" : "=r"(d) : "r"(a), "r"(b), "r"(c)); return d;
}
__device__ __forceinline__ void lds4(uint32_t (&r)[4], uint32_t addr) {
  asm volatile("ld.shared.v4.b32 {%0,%1,%2,%3}, [%4];" : "=r"(r[0]), "=r"(r[1]), "=r"(r[2]), "=r"(r[3]) : "r"(addr) : "memory");
}
__device__ __forceinline__ void sts4(uint32_t addr, const uint32_t (&r)[4]) {
  asm volatile("st.shared.v4.b32 [%0], {%1,%2,%3,%4};" ::"r"(addr), "r"(r[0]), "r"(r[1]), "r"(r[2]), "r"(r[3]) : "memory");
}
__device__ __forceinline__ void tma_store5(const CUtensorMap* map, uint32_t src, int c0, int c1, int c2, int c3, int c4) {
  asm volatile("cp.async.bulk.tensor.5d.global.shared::cta.bulk_group [%0, {%2,%3,%4,%5,%6}], [%1];"
               ::"l"(map), "r"(src), "r"(c0), "r"(c1), "r"(c2), "r"(c3), "r"(c4) : "memory");
  asm volatile("cp.async.bulk.commit_group;" ::: "memory");
}
__device__ __forceinline__ bool elect_one() {
  uint32_t p;
  asm volatile("{\n.reg .pred P;\nelect.sync _|P, 0xffffffff;\nselp.u32 %0, 1, 0, P;\n}\n" : "=r"(p));
  return p;
}
__device__ __forceinline__ uint32_t mapa(uint32_t addr, uint32_t rank) {
  uint32_t r; asm("mapa.shared::cluster.u32 %0, %1, %2;" : "=r"(r) : "r"(addr), "r"(rank)); return r;
}

__device__ __forceinline__ void tr_sum(uint32_t (&t)[3][4], const uint32_t (&U)[3][4], const uint32_t (&V)[3][4]) {
#pragma unroll
  for (int k = 0; k < 3; k++)
#pragma unroll
    for (int i = 0; i < 4; i++) t[k][i] = badd(U[k][i], V[k][i]);
}
__device__ __forceinline__ void tr_dif(uint32_t (&t)[3][4], const uint32_t (&U)[3][4], const uint32_t (&V)[3][4]) {
#pragma unroll
  for (int k = 0; k < 3; k++)
#pragma unroll
    for (int i = 0; i < 4; i++) t[k][i] = bsub(V[k][i], U[k][i]);
}
__device__ __forceinline__ void tr_t0(uint32_t (&t)[3][4], const uint32_t (&V)[3][4], const uint32_t (&E)[3][4]) {
#pragma unroll
  for (int k = 0; k < 3; k++) {
    t[k][0] = bsub(E[k][0], V[k][0]); t[k][1] = bsub(V[k][0], V[k][1]);
    t[k][2] = bsub(E[k][2], V[k][2]); t[k][3] = bsub(V[k][2], V[k][3]);
  }
}
__device__ __forceinline__ void tr_t3(uint32_t (&t)[3][4], const uint32_t (&U)[3][4], const uint32_t (&E)[3][4]) {
#pragma unroll
  for (int k = 0; k < 3; k++) {
    t[k][0] = bsub(U[k][1], U[k][0]); t[k][1] = bsub(E[k][1], U[k][1]);
    t[k][2] = bsub(U[k][3], U[k][2]); t[k][3] = bsub(E[k][3], U[k][3]);
  }
}
__device__ __forceinline__ void ld3(uint32_t (&R)[3][4], uint32_t aU, int off) {
#pragma unroll
  for (int k = 0; k < 3; k++) ldsm4(R[k], (aU ^ (32 * k)) + off);
}
template <int COMP, int AGE, int FIRST>
__device__ __forceinline__ void batch(float (&acc)[48], const uint32_t (&t)[3][4]) {
  constexpr int base = ((COMP * 3 + AGE) * 3) * BT_BYTES;
  wgmma96<FIRST ? 0 : 1, BDESC + ((base) >> 4)>(acc, t[0]);
  wgmma96<1, BDESC + ((base + BT_BYTES) >> 4)>(acc, t[1]);
  wgmma96<1, BDESC + ((base + 2 * BT_BYTES) >> 4)>(acc, t[2]);
  wg_commit();
}

#define DBG_T(c, idx)
#define DBG_TA(idx)
#define TL(c, k)
#define DBG_U(c, idx)
#define DBG_FLUSH(c)
#define DBG_G(c, idx)

struct Ctx {
  uint32_t aU, aE;
  uint32_t in_base;
  uint32_t bar_full;
  uint32_t xaddr, xfull;
  uint32_t xbase;
  const CUtensorMap* omap;
  const CUtensorMap* map;
  const char* xseg;
  int wg, warp;
  int c0, u0, h0, hstep;
  bool producer;
};

__device__ __forceinline__ void prefetch_row(const Ctx& c, int h) {
  if ((unsigned)h < (unsigned)IMG_H)
    asm volatile("cp.async.bulk.prefetch.L2.global [%0], %1;" ::"l"(c.xseg + (size_t)h * (IMG_W * CH * 2)), "r"(64 * CH * 2) : "memory");
}

template <int BUF, int C0, int C1>
__device__ __forceinline__ void load_partner(const Ctx& c, uint32_t (&P)[6][4]) {
#pragma unroll
  for (int ch = C0; ch < C1; ch++) lds4(P[ch], c.xaddr + BUF * XBUF_BYTES + (ch & 1) * 6144 + (ch >> 1) * 64);
}
template <int BUF, int C0, int C1>
__device__ __forceinline__ void finish_chunks(const Ctx& c, const float (&Y)[48], uint32_t (&P)[6][4]) {
#pragma unroll
  for (int ch = C0; ch < C1; ch++) {
    const int m = ch >> 1, s = ch & 1;
#pragma unroll
    for (int ss = 0; ss < 4; ss++) P[ch][ss] = badd(pack2(Y[16 * m + 4 * ss + 2 * s], Y[16 * m + 4 * ss + 2 * s + 1]), P[ch][ss]);
    sts4(c.xaddr + BUF * XBUF_BYTES + s * 6144 + m * 64, P[ch]);
  }
}
template <int RANK, int BUF, int CH0>
__device__ __forceinline__ void send_chunk(const Ctx& c, const float (&X)[48]) {
  constexpr uint32_t RDELTA = RANK ? 0xFF000000u : 0x01000000u;
  constexpr int m = CH0 >> 1, s = CH0 & 1;
  uint32_t o[4];
#pragma unroll
  for (int ss = 0; ss < 4; ss++) o[ss] = pack2(X[16 * m + 4 * ss + 2 * s], X[16 * m + 4 * ss + 2 * s + 1]);
  st_async4<BUF * XBUF_BYTES + s * 6144 + m * 64>(c.xaddr + RDELTA, c.xfull + BUF * 64 + RDELTA, o[0], o[1], o[2], o[3]);
}

#define PF_DIST 1
#define ORD1 0
#define RORD 0
#define REL 0
#define ORD3 2
#define SLOT 0
#define ORD2 1

struct Regs {
  float X[48], Y[48];
  uint32_t T[4][2][3][4];
  uint32_t U[3][4], V[3][4], E[3][4];
};

template <int RANK, int OLD>
__device__ __forceinline__ void tma_slot(const Ctx& c, int n) {
  constexpr int MID = 1 - OLD;
  asm volatile("fence.proxy.async.shared::cta;" ::: "memory");
  asm volatile("bar.sync %0, 128;" ::"r"(2 + c.wg) : "memory");
  if (elect_one()) {
    const int h = c.h0 + n * c.hstep;
    if (c.warp < 2) {
      if (n + 4 < ROWS_PER_STRIP + 2) {
        mbar_expect_tx(c.bar_full + 8 * OLD, BOX_BYTES);
        tma_load5(c.in_base + OLD * STAGE_BYTES + c.warp * OFF_BOXB, c.map, c.bar_full + 8 * OLD, c.c0, 2 * c.warp, c.u0 - c.warp, 0,
                  h + 4 * c.hstep);
      } else {
        mbar_arrive(c.bar_full + 8 * OLD);
      }
    } else if (c.warp == 2) {
      if (OLD == 1 || n > 0) tma_store5(c.omap, c.xbase + MID * XBUF_BYTES, 0, c.u0, 0, RANK, h);
    } else {
      if (PF_DIST > 0 && n + 4 + PF_DIST < ROWS_PER_STRIP + 2) prefetch_row(c, h + (4 + PF_DIST) * c.hstep);
    }
  }
  __syncwarp();
}
template <int RANK, int OLD>
__device__ __forceinline__ void release_xbuf(const Ctx& c) {
  constexpr uint32_t RDELTA = RANK ? 0xFF000000u : 0x01000000u;
  asm volatile("cp.async.bulk.wait_group.read 0;" ::: "memory");
  asm volatile("{\n.reg .pred p;\nsetp.eq.u32 p, %1, 64;\n@p mbarrier.arrive.shared::cluster.b64 _, [%0];\n}\n"
               ::"r"(c.bar_full + 8 * (1 - OLD) + RDELTA), "r"(threadIdx.x & 127) : "memory");
}
template <int P>
__device__ __forceinline__ void wg_lock(const Ctx& c) {
}
__device__ __forceinline__ void pack_acc(uint32_t (&Z)[6][4], const float (&Y)[48]) {
#pragma unroll
  for (int ch = 0; ch < 6; ch++)
#pragma unroll
    for (int ss = 0; ss < 4; ss++) {
      const int i = 16 * (ch >> 1) + 4 * ss + 2 * (ch & 1);
      Z[ch][ss] = pack2(Y[i], Y[i + 1]);
    }
}
template <int BUF, int C0, int C1>
__device__ __forceinline__ void add_stage(const Ctx& c, uint32_t (&Z)[6][4], const uint32_t (&P)[6][4]) {
#pragma unroll
  for (int ch = C0; ch < C1; ch++)
#pragma unroll
    for (int ss = 0; ss < 4; ss++) Z[ch][ss] = badd(Z[ch][ss], P[ch][ss]);
#pragma unroll
  for (int ch = C0; ch < C1; ch++) sts4(c.xaddr + BUF * XBUF_BYTES + (ch & 1) * 6144 + (ch >> 1) * 64, Z[ch]);
}

template <int RANK, int OLD, bool FIRST>
__device__ __forceinline__ void phase1(const Ctx& c, int n, Regs& r) {
  constexpr int MID = 1 - OLD;
  uint32_t Z[6][4], P[6][4];
  wg_fence();
  batch<0, 0, 1>(r.X, r.T[0][OLD]);
  if (ORD1 == 0 || FIRST) batch<0, 1, 0>(r.X, r.T[0][MID]);
  wg_lock<0>(c);
  if (!FIRST) {
    wg_wait<ORD1 == 0 ? 2 : 1>();
    pack_acc(Z, r.Y);
  }
  wg_fence();
  batch<1, 0, 1>(r.Y, r.T[1][OLD]);
  if (ORD1 == 1 && !FIRST) batch<0, 1, 0>(r.X, r.T[0][MID]);
  if (ORD3 == 0 || FIRST) batch<1, 1, 0>(r.Y, r.T[1][MID]);
  wg_lock<1>(c);
  if (FIRST) {
    mbar_wait(c.bar_full + 8 * OLD, 0);
    ld3(r.U, c.aU, OLD * STAGE_BYTES);
    ld3(r.V, c.aU, OLD * STAGE_BYTES + OFF_V);
  } else {
    mbar_wait(c.xfull + MID * 64, ((n - 1) >> 1) & 1);
    load_partner<MID, 0, 3>(c, P);
    if (elect_one()) mbar_expect_tx(c.xfull + MID * 64, X_BYTES);
    if (REL == 0) release_xbuf<RANK, OLD>(c);
    if (ORD3 == 1) { wg_fence(); batch<1, 1, 0>(r.Y, r.T[1][MID]); }
    add_stage<MID, 0, 3>(c, Z, P);
    if (RANK == 0) ld3(r.V, c.aU, OLD * STAGE_BYTES + OFF_V); else ld3(r.U, c.aU, OLD * STAGE_BYTES);
    load_partner<MID, 3, 6>(c, P);
    if (ORD3 == 2) { wg_fence(); batch<1, 1, 0>(r.Y, r.T[1][MID]); }
    if (REL == 1) release_xbuf<RANK, OLD>(c);
  }
  wg_wait<3>();
  tr_sum(r.T[0][OLD], r.U, r.V);
  wg_fence();
  batch<0, 2, 0>(r.X, r.T[0][OLD]);
  if (REL == 2 && !FIRST) release_xbuf<RANK, OLD>(c);
  wg_wait<2>();
  tr_dif(r.T[1][OLD], r.U, r.V);
  wg_fence();
  batch<1, 2, 0>(r.Y, r.T[1][OLD]);
  wg_lock<2>(c);
  if (!FIRST) add_stage<MID, 3, 6>(c, Z, P);
  ld3(r.E, c.aE, OLD * STAGE_BYTES);
  if (SLOT == 0) tma_slot<RANK, OLD>(c, n);
  wg_wait<0>();
}

template <int RANK, int OLD, bool LAST>
__device__ __forceinline__ void phase2(const Ctx& c, int n, Regs& r) {
  constexpr int MID = 1 - OLD;
#pragma unroll
  for (int i = 0; i < 48; i++) {
    if (RANK == 0) asm volatile("sub.rn.f32 %0, %0, %1;\nfma.rn.f32 %1, %1, 0f40000000, %0;" : "+f"(r.X[i]), "+f"(r.Y[i]));
    else           asm volatile("add.rn.f32 %0, %0, %1;\nfma.rn.f32 %1, %1, 0fC0000000, %0;" : "+f"(r.X[i]), "+f"(r.Y[i]));
  }
  wg_fence();
  batch<2, 0, 0>(r.X, r.T[2][OLD]);
  batch<2, 1, 0>(r.X, r.T[2][MID]);
  wg_lock<3>(c);
  if (SLOT == 1) tma_slot<RANK, OLD>(c, n);
  mbar_wait(c.bar_full + 8 * MID, ((n + 2 + MID) >> 1) & 1);
  wg_wait<1>();
  if (RANK == 0) tr_t3(r.T[2][OLD], r.U, r.E); else tr_t0(r.T[2][OLD], r.V, r.E);
  if (!LAST) { if (RANK == 0) ld3(r.U, c.aU, MID * STAGE_BYTES); else ld3(r.V, c.aU, MID * STAGE_BYTES + OFF_V); }
  wg_fence();
  batch<2, 2, 0>(r.X, r.T[2][OLD]);
  batch<3, 0, 0>(r.Y, r.T[3][OLD]);
  if (ORD2 == 1) batch<3, 1, 0>(r.Y, r.T[3][MID]);
  wg_lock<4>(c);
  wg_wait<ORD2 == 1 ? 2 : 1>();
  send_chunk<RANK, OLD, 0>(c, r.X); send_chunk<RANK, OLD, 1>(c, r.X); send_chunk<RANK, OLD, 2>(c, r.X);
  if (ORD2 == 2) { wg_fence(); batch<3, 1, 0>(r.Y, r.T[3][MID]); }
  send_chunk<RANK, OLD, 3>(c, r.X); send_chunk<RANK, OLD, 4>(c, r.X); send_chunk<RANK, OLD, 5>(c, r.X);
  if (ORD2 == 0) { wg_fence(); batch<3, 1, 0>(r.Y, r.T[3][MID]); }
  wg_lock<5>(c);
  wg_wait<1>();
  if (RANK == 0) tr_t0(r.T[3][OLD], r.V, r.E); else tr_t3(r.T[3][OLD], r.U, r.E);
  wg_fence();
  batch<3, 2, 0>(r.Y, r.T[3][OLD]);
}

template <int RANK>
__device__ __forceinline__ void run_strip(const Ctx& c, uint32_t row0_off, uint32_t bar_row0) {
  Regs r;
#pragma unroll
  for (int m = 0; m < 2; m++) {
    const uint32_t off = m ? STAGE_BYTES : row0_off;
    mbar_wait(m ? c.bar_full + 8 : bar_row0, 0);
    DBG_T(c, 50 + m);
    ld3(r.U, c.aU, off);
    ld3(r.V, c.aU, off + OFF_V);
    ld3(r.E, c.aE, off);
    tr_sum(r.T[0][m], r.U, r.V);
    tr_dif(r.T[1][m], r.U, r.V);
    tr_t3(r.T[RANK == 0 ? 2 : 3][m], r.U, r.E);
    tr_t0(r.T[RANK == 0 ? 3 : 2][m], r.V, r.E);
  }
  asm volatile("bar.sync %0, 128;" ::"r"(2 + c.wg) : "memory");
  asm volatile("barrier.cluster.wait.aligned;" ::: "memory");
  if (elect_one()) {
    if (c.warp < 2) {
      mbar_expect_tx(c.bar_full + 8, BOX_BYTES);
      tma_load5(c.in_base + STAGE_BYTES + c.warp * OFF_BOXB, c.map, c.bar_full + 8, c.c0, 2 * c.warp, c.u0 - c.warp, 0, c.h0 + 3 * c.hstep);
    } else if (c.warp == 2) {
      asm volatile("mbarrier.arrive.shared::cluster.b64 _, [%0];" ::"r"((bar_row0 + (BAR_READY - BAR_ROW0) * 8) ^ 0x01000000u) : "memory");
    } else {
      mbar_arrive(c.bar_full + 8);
    }
  }
  __syncwarp();
  DBG_T(c, 46);
  mbar_wait(SMEM_BASE + (RANK << 24) + OFF_BAR + 8 * BAR_W + 24, 0);
  DBG_T(c, 3);
#pragma unroll
  for (int i = 0; i < 48; i++) { r.X[i] = 0.f; r.Y[i] = 0.f; }
  phase1<RANK, 0, true>(c, 0, r);
  mbar_wait(bar_row0 + (BAR_READY - BAR_ROW0) * 8, 0);
#pragma unroll 1
  for (int n = 0;; n += 2) {
    phase2<RANK, 0, false>(c, n, r);
    phase1<RANK, 1, false>(c, n + 1, r);
    if (n + 2 == ROWS_PER_STRIP) break;
    phase2<RANK, 1, false>(c, n + 1, r);
    phase1<RANK, 0, false>(c, n + 2, r);
  }
  phase2<RANK, 1, true>(c, ROWS_PER_STRIP - 1, r);
  DBG_T(c, 35);
  uint32_t P[6][4];
  mbar_wait(c.xfull + 64, ((ROWS_PER_STRIP - 1) >> 1) & 1);
  load_partner<1, 0, 6>(c, P);
  wg_wait<0>();
  finish_chunks<1, 0, 6>(c, r.Y, P);
  asm volatile("fence.proxy.async.shared::cta;" ::: "memory");
  asm volatile("bar.sync %0, 128;" ::"r"(2 + c.wg) : "memory");
  if (c.warp == 2 && elect_one()) {
    tma_store5(c.omap, c.xbase + XBUF_BYTES, 0, c.u0, 0, RANK, c.h0 + ROWS_PER_STRIP * c.hstep);
    asm volatile("cp.async.bulk.wait_group.read 0;" ::: "memory");
  }
  DBG_T(c, 40); DBG_G(c, 1); DBG_FLUSH(c);
}

__global__ void __cluster_dims__(2, 1, 1) __launch_bounds__(256, 1)
dilated_conv_wino_kernel(const __grid_constant__ CUtensorMap xmap, const __grid_constant__ CUtensorMap omap,
                         const __nv_bfloat16* __restrict__ x, const __nv_bfloat16* __restrict__ w) {
  extern __shared__ uint8_t smem_raw[];
  const int tid = threadIdx.x;
  const int wg = __shfl_sync(0xffffffff, tid >> 7, 0);
  const int warp = __shfl_sync(0xffffffff, (tid >> 5) & 3, 0);
  const int lane = tid & 31;
  const int rank = blockIdx.x & 1;
  const uint32_t sbase = SMEM_BASE + (rank << 24);
  if ((uint32_t)__cvta_generic_to_shared(smem_raw) != sbase || mapa(sbase, rank ^ 1) != (sbase ^ 0x01000000u)) __trap();
  const int sid = (blockIdx.x >> 1) * 2 + wg;
  const int seg = sid & 3, par = (sid >> 2) & 1, strip = sid >> 3;
  const bool down = (strip & 1) == 0;
  const int r0 = strip * ROWS_PER_STRIP;

  Ctx c;
  c.map = &xmap;
  c.wg = wg;
  c.warp = warp;
  c.in_base = sbase + OFF_IN + wg * WG_IN_BYTES;
  c.bar_full = sbase + OFF_BAR + 8 * (BAR_FULL + wg * NSTAGE);
  c.c0 = rank * 48;
  c.u0 = seg * 16;
  c.h0 = 2 * (down ? r0 - 1 : r0 + ROWS_PER_STRIP) + par;
  c.hstep = down ? 2 : -2;
  c.producer = (tid & 127) == 0;
  c.xfull = sbase + OFF_BAR + 8 * (BAR_XFULL + wg * 4 + warp);
  c.xseg = reinterpret_cast<const char*>(x) + (seg * 128 + rank * 64) * (CH * 2);

  DBG_G(c, 0); DBG_T(c, 0);
  const uint32_t bar_w = sbase + OFF_BAR + 8 * BAR_W;
  const uint32_t o_w0 = (rank ? 2 : 3) * 9 * BT_BYTES, o_w2 = (rank ? 3 : 2) * 9 * BT_BYTES;
  if (elect_one()) {
    const uint32_t b0 = sbase + OFF_BAR;
    const int w8 = wg * 4 + warp;
    if (w8 >= 5) {
      const int a = w8 - 5, i = down ? a : 2 - a;
      const __nv_bfloat16* src = w + ((size_t)(i * 3) * CH + rank * 48) * CH;
      const uint32_t dst = sbase + OFF_W + a * 3 * BT_BYTES;
      mbar_init(bar_w + 8 * a, 1);
      asm volatile("fence.proxy.async.shared::cta;" ::: "memory");
      mbar_expect_tx(bar_w + 8 * a, 9 * BT_BYTES);
      bulk_load(dst + o_w0, src, 3 * BT_BYTES, bar_w + 8 * a);
      bulk_load(dst, src + CH * CH, 3 * BT_BYTES, bar_w + 8 * a);
      bulk_load(dst + o_w2, src + 2 * CH * CH, 3 * BT_BYTES, bar_w + 8 * a);
      DBG_TA(53 + a);
    } else {
      if (w8 < 4) {
        mbar_init(b0 + 8 * w8, 3);
#pragma unroll
        for (int q = 0; q < 4; q++) mbar_init(b0 + 8 * (BAR_XFULL + 4 * w8 + q), 1);
        mbar_expect_tx(b0 + 8 * w8, 2 * BOX_BYTES);
        asm volatile("mbarrier.arrive.shared::cta.b64 _, [%0], 2;" ::"r"(b0 + 8 * w8) : "memory");
      } else {
        asm volatile("prefetch.tensormap [%0];" ::"l"(&xmap) : "memory");
#pragma unroll
        for (int q = 0; q < 2; q++) {
          mbar_init(b0 + 8 * (BAR_ROW0 + q), 1);
          mbar_init(b0 + 8 * (BAR_READY + q), 1);
          mbar_expect_tx(b0 + 8 * (BAR_ROW0 + q), 2 * BOX_BYTES);
        }
        mbar_init(bar_w + 24, 6);
      }
      asm volatile("fence.mbarrier_init.release.cluster;" ::: "memory");
      asm volatile("fence.proxy.async.shared::cta;" ::: "memory");
    }
  }
  DBG_T(c, 45);
  __syncthreads();
  asm volatile("barrier.cluster.arrive.relaxed.aligned;" ::: "memory");
  DBG_T(c, 41);
  const uint32_t row0 = sbase + (wg ? OFF_ROW0_1 : OFF_ROW0_0);
  const uint32_t bar_row0 = sbase + OFF_BAR + 8 * (BAR_ROW0 + wg);
  if (warp == 3) {
    if (elect_one()) {
#pragma unroll 1
      for (int k = 0; k < 6; k++) {
        const int g = k < 4 ? (RORD ? k >> 1 : k & 1) : k & 1, m = k < 4 ? (RORD ? k & 1 : k >> 1) : 2;
        const uint32_t dst = m == 0 ? sbase + (g ? OFF_ROW0_1 : OFF_ROW0_0) : sbase + OFF_IN + g * WG_IN_BYTES + (m & 1) * STAGE_BYTES;
        const uint32_t bar = sbase + OFF_BAR + 8 * (m == 0 ? BAR_ROW0 + g : BAR_FULL + 2 * g + (m & 1));
        tma_load5(dst + wg * OFF_BOXB, &xmap, bar, c.c0, 2 * wg, ((seg & 2) + g) * 16 - wg, 0, c.h0 + m * c.hstep);
      }
      asm volatile("prefetch.tensormap [%0];" ::"l"(&omap) : "memory");
      DBG_TA(49);
    }
    __syncwarp();
  } else {
#pragma unroll 1
    for (int age = 0; age < 3; age++) {
      const uint32_t base = sbase + OFF_W + (age * 6 + wg * 3 + warp) * 1536;
      mbar_wait(bar_w + 8 * age, 0);
      DBG_T(c, 42 + age);
      uint32_t wa[3][4], wb[3][4], wd[3][4];
      const uint32_t src = base + (lane >> 2) * 192 + (lane & 3) * 16;
#pragma unroll
      for (int m = 0; m < 3; m++) {
        lds4(wa[m], src + o_w0 + m * 64);
        lds4(wb[m], src + m * 64);
        lds4(wd[m], src + o_w2 + m * 64);
      }
      __syncwarp();
      const uint32_t dst = base + lane * 16;
#pragma unroll
      for (int m = 0; m < 3; m++) {
        uint32_t g1[4], g2[4];
        stsm4(dst + m * 512 + o_w0, wa[m][0], wa[m][1], wa[m][2], wa[m][3]);
        stsm4(dst + m * 512 + o_w2, wd[m][0], wd[m][1], wd[m][2], wd[m][3]);
#pragma unroll
        for (int ss = 0; ss < 4; ss++) {
          const uint32_t a = wa[m][ss], b = wb[m][ss], d = wd[m][ss];
          const float slo = __uint_as_float(a << 16) + __uint_as_float(d << 16);
          const float shi = __uint_as_float(a & 0xffff0000u) + __uint_as_float(d & 0xffff0000u);
          const float blo = 0.5f * __uint_as_float(b << 16), bhi = 0.5f * __uint_as_float(b & 0xffff0000u);
          g1[ss] = pack2(fmaf(slo, 0.5f, blo), fmaf(shi, 0.5f, bhi));
          g2[ss] = pack2(fmaf(slo, 0.5f, -blo), fmaf(shi, 0.5f, -bhi));
        }
        stsm4(dst + m * 512, g1[0], g1[1], g1[2], g1[3]);
        stsm4(dst + m * 512 + 9 * BT_BYTES, g2[0], g2[1], g2[2], g2[3]);
      }
    }
    asm volatile("fence.proxy.async.shared::cta;" ::: "memory");
    __syncwarp();
    if (elect_one()) mbar_arrive(bar_w + 24);
  }
  if (elect_one()) { mbar_expect_tx(c.xfull, X_BYTES); mbar_expect_tx(c.xfull + 64, X_BYTES); }
  DBG_T(c, 1);

  {
    const int g = lane & 7, mi = lane >> 3;
    const int rU = 8 * warp + g + ((mi & 1) ? 34 : 0);
    const int rE = 8 * warp + g + ((mi & 1) ? 2 : 70 + 34);
    const uint32_t pU = c.in_base + rU * 128, pE = c.in_base + rE * 128;
    c.aU = pU + (((mi >> 1) ^ ((pU >> 7) & 7)) << 4);
    c.aE = pE + (((mi >> 1) ^ ((pE >> 7) & 7)) << 4);
  }
  c.xbase = sbase + OFF_X + wg * 2 * XBUF_BYTES;
  c.xaddr = c.xbase + (warp * 8 + (lane >> 2)) * 192 + (lane & 3) * 16;
  c.omap = &omap;
  if (rank == 0) run_strip<0>(c, row0 - c.in_base, bar_row0); else run_strip<1>(c, row0 - c.in_base, bar_row0);
}

typedef CUresult (*EncodeTiledFn)(CUtensorMap*, CUtensorMapDataType, cuuint32_t, void*, const cuuint64_t*, const cuuint64_t*,
                                  const cuuint32_t*, const cuuint32_t*, CUtensorMapInterleave, CUtensorMapSwizzle,
                                  CUtensorMapL2promotion, CUtensorMapFloatOOBfill);

}

extern "C" void kernel_launch(void* const* d_in, const int* in_sizes, int n_in, void* d_out, int out_size) {
  (void)in_sizes; (void)n_in; (void)out_size;
  static EncodeTiledFn encode = nullptr;
  if (!encode) {
    void* fn = nullptr;
    cudaDriverEntryPointQueryResult qr;
    cudaGetDriverEntryPoint("cuTensorMapEncodeTiled", &fn, cudaEnableDefault, &qr);
    encode = (EncodeTiledFn)fn;
    cudaFuncSetAttribute(dilated_conv_wino_kernel, cudaFuncAttributeMaxDynamicSharedMemorySize, SMEM_BYTES);
  }
  CUtensorMap xmap;
  const cuuint64_t dims[5] = {CH, 4, IMG_W / 8, 2, IMG_H};
  const cuuint64_t strides[4] = {CH * 2, 8 * CH * 2, 4 * CH * 2, IMG_W * CH * 2};
  const cuuint32_t box[5] = {48, 2, 17, 2, 1};
  const cuuint32_t estr[5] = {1, 1, 1, 1, 1};
#define PROMO CU_TENSOR_MAP_L2_PROMOTION_L2_128B
  encode(&xmap, CU_TENSOR_MAP_DATA_TYPE_BFLOAT16, 5, d_in[0], dims, strides, box, estr, CU_TENSOR_MAP_INTERLEAVE_NONE,
         CU_TENSOR_MAP_SWIZZLE_128B, PROMO, CU_TENSOR_MAP_FLOAT_OOB_FILL_NONE);
  CUtensorMap omap;
  const cuuint64_t odims[5] = {2 * CH, IMG_W / 8, 2, 2, IMG_H};
  const cuuint64_t ostrides[4] = {8 * CH * 2, 4 * CH * 2, 2 * CH * 2, IMG_W * CH * 2};
  const cuuint32_t obox[5] = {2 * CH, 16, 2, 1, 1};
  encode(&omap, CU_TENSOR_MAP_DATA_TYPE_BFLOAT16, 5, d_out, odims, ostrides, obox, estr, CU_TENSOR_MAP_INTERLEAVE_NONE,
         CU_TENSOR_MAP_SWIZZLE_NONE, CU_TENSOR_MAP_L2_PROMOTION_NONE, CU_TENSOR_MAP_FLOAT_OOB_FILL_NONE);
  dilated_conv_wino_kernel<<<128, 256, SMEM_BYTES>>>(xmap, omap, (const __nv_bfloat16*)d_in[0], (const __nv_bfloat16*)d_in[1]);
}
```

```cpp
#include <cuda_runtime.h>
#include <cuda_bf16.h>
#include <cuda.h>
#include <stdint.h>

namespace {

constexpr int IMG_H = 512, IMG_W = 512, CH = 96;
constexpr int NSTAGE = 2;

constexpr int BT_BYTES   = 3072;
constexpr int W_BYTES    = 36 * BT_BYTES;
constexpr int BOX_BYTES  = 68 * 96;
constexpr int OFF_BOXB   = 70 * 128;
constexpr int STAGE_BYTES = 144 * 128;
constexpr int OFF_V      = 72 * 128;
constexpr int WG_IN_BYTES = STAGE_BYTES + 138 * 128;
constexpr int OFF_W      = 0;
constexpr int OFF_IN     = OFF_W + W_BYTES;
constexpr int OFF_X      = OFF_IN + 2 * WG_IN_BYTES;
constexpr int X_BYTES    = 3072;
constexpr int XBUF_BYTES = 4 * X_BYTES;
constexpr int SMEM_BYTES = OFF_X + 4 * XBUF_BYTES;
constexpr int OFF_ROW0_0 = OFF_X + ((OFF_IN - OFF_X) & 1023);
constexpr int OFF_ROW0_1 = OFF_X + 2 * XBUF_BYTES + ((OFF_IN + WG_IN_BYTES - OFF_X) & 1023);
constexpr int OFF_BAR    = OFF_IN + 68 * 128;
constexpr int BAR_FULL = 0, BAR_XFULL = 8, BAR_W = 24, BAR_ROW0 = 28, BAR_READY = 30;
constexpr int OFF_DBG    = OFF_IN + 138 * 128;
static_assert(SMEM_BYTES <= 232448, "shared memory");
constexpr uint32_t SMEM_BASE = 1024;
constexpr uint64_t BDESC = (uint64_t)((SMEM_BASE + OFF_W) >> 4) | ((uint64_t)(1536 >> 4) << 16) | ((uint64_t)(128 >> 4) << 32);

__device__ __forceinline__ void wg_fence()  { asm volatile("wgmma.fence.sync.aligned;" ::: "memory"); }
__device__ __forceinline__ void wg_commit() { asm volatile("wgmma.commit_group.sync.aligned;" ::: "memory"); }
template <int N> __device__ __forceinline__ void wg_wait() { asm volatile("wgmma.wait_group.sync.aligned %0;" ::"n"(N) : "memory"); }

template <int SCALE_D, uint64_t DESC>
__device__ __forceinline__ void wgmma96(float (&d)[48], const uint32_t (&a)[4]) {
  asm volatile(
      "{\n.reg .pred p;\nsetp.ne.b32 p, %53, 0;\n"
      "wgmma.mma_async.sync.aligned.m64n96k16.f32.bf16.bf16 "
      "{%0,%1,%2,%3,%4,%5,%6,%7,%8,%9,%10,%11,%12,%13,%14,%15,%16,%17,%18,%19,%20,%21,%22,%23,"
      "%24,%25,%26,%27,%28,%29,%30,%31,%32,%33,%34,%35,%36,%37,%38,%39,%40,%41,%42,%43,%44,%45,%46,%47}, "
      "{%48,%49,%50,%51}, %52, p, 1, 1, 1;\n}\n"
      : "+f"(d[0]), "+f"(d[1]), "+f"(d[2]), "+f"(d[3]), "+f"(d[4]), "+f"(d[5]), "+f"(d[6]), "+f"(d[7]),
        "+f"(d[8]), "+f"(d[9]), "+f"(d[10]), "+f"(d[11]), "+f"(d[12]), "+f"(d[13]), "+f"(d[14]), "+f"(d[15]),
        "+f"(d[16]), "+f"(d[17]), "+f"(d[18]), "+f"(d[19]), "+f"(d[20]), "+f"(d[21]), "+f"(d[22]), "+f"(d[23]),
        "+f"(d[24]), "+f"(d[25]), "+f"(d[26]), "+f"(d[27]), "+f"(d[28]), "+f"(d[29]), "+f"(d[30]), "+f"(d[31]),
        "+f"(d[32]), "+f"(d[33]), "+f"(d[34]), "+f"(d[35]), "+f"(d[36]), "+f"(d[37]), "+f"(d[38]), "+f"(d[39]),
        "+f"(d[40]), "+f"(d[41]), "+f"(d[42]), "+f"(d[43]), "+f"(d[44]), "+f"(d[45]), "+f"(d[46]), "+f"(d[47])
      : "r"(a[0]), "r"(a[1]), "r"(a[2]), "r"(a[3]), "l"(DESC), "n"(SCALE_D));
}

__device__ __forceinline__ void ldsm4(uint32_t (&r)[4], uint32_t addr) {
  asm volatile("ldmatrix.sync.aligned.m8n8.x4.shared.b16 {%0,%1,%2,%3}, [%4];"
               : "=r"(r[0]), "=r"(r[1]), "=r"(r[2]), "=r"(r[3]) : "r"(addr) : "memory");
}
__device__ __forceinline__ uint32_t badd(uint32_t a, uint32_t b) {
  uint32_t d; asm volatile("add.rn.bf16x2 %0, %1, %2;" : "=r"(d) : "r"(a), "r"(b)); return d;
}
__device__ __forceinline__ uint32_t bsub(uint32_t a, uint32_t b) {
  uint32_t d; asm volatile("sub.rn.bf16x2 %0, %1, %2;" : "=r"(d) : "r"(a), "r"(b)); return d;
}
__device__ __forceinline__ uint32_t pack2(float lo, float hi) {
  uint32_t d; asm volatile("cvt.rn.bf16x2.f32 %0, %1, %2;" : "=r"(d) : "f"(hi), "f"(lo)); return d;
}

__device__ __forceinline__ void mbar_wait(uint32_t bar, uint32_t parity) {
  asm volatile(
      "{\n.reg .pred p;\n.reg .u32 it;\n"
      "mbarrier.try_wait.parity.shared::cta.b64 p, [%0], %1;\n"
      "@p bra WAIT_DONE;\n"
      "mov.u32 it, 0;\n"
      "WAIT_LOOP:\n"
      ".pragma \"nounroll\";\n"
      "mbarrier.try_wait.parity.shared::cta.b64 p, [%0], %1;\n"
      "@p bra WAIT_DONE;\n"
      "add.u32 it, it, 1;\n"
      "setp.lt.u32 p, it, 4194304;\n"
      "@p bra WAIT_LOOP;\n"
      "trap;\n"
      "WAIT_DONE:\n}\n" ::"r"(bar), "r"(parity) : "memory");
}
__device__ __forceinline__ bool mbar_try(uint32_t bar, uint32_t parity) {
  uint32_t ok;
  asm volatile("{\n.reg .pred p;\nmbarrier.test_wait.parity.shared::cta.b64 p, [%1], %2;\nselp.u32 %0, 1, 0, p;\n}\n"
               : "=r"(ok) : "r"(bar), "r"(parity) : "memory");
  return ok;
}
__device__ __forceinline__ void mbar_init(uint32_t bar, uint32_t count) {
  asm volatile("mbarrier.init.shared::cta.b64 [%0], %1;" ::"r"(bar), "r"(count) : "memory");
}
__device__ __forceinline__ void mbar_arrive(uint32_t bar) {
  asm volatile("mbarrier.arrive.shared::cta.b64 _, [%0];" ::"r"(bar) : "memory");
}
__device__ __forceinline__ void mbar_expect_tx(uint32_t bar, uint32_t bytes) {
  asm volatile("mbarrier.arrive.expect_tx.shared::cta.b64 _, [%0], %1;" ::"r"(bar), "r"(bytes) : "memory");
}
__device__ __forceinline__ void tma_load5(uint32_t dst, const CUtensorMap* map, uint32_t bar, int c0, int c1, int c2, int c3, int c4) {
  asm volatile("cp.async.bulk.tensor.5d.shared::cluster.global.mbarrier::complete_tx::bytes [%0], [%1, {%3,%4,%5,%6,%7}], [%2];"
               ::"r"(dst), "l"(map), "r"(bar), "r"(c0), "r"(c1), "r"(c2), "r"(c3), "r"(c4) : "memory");
}
__device__ __forceinline__ void bulk_load(uint32_t dst, const void* src, uint32_t bytes, uint32_t bar) {
  asm volatile("cp.async.bulk.shared::cluster.global.mbarrier::complete_tx::bytes [%0], [%1], %2, [%3];"
               ::"r"(dst), "l"(src), "r"(bytes), "r"(bar) : "memory");
}
template <int OFF>
__device__ __forceinline__ void st_async4(uint32_t cluster_addr, uint32_t cluster_bar, uint32_t a, uint32_t b, uint32_t c, uint32_t d) {
  asm volatile("st.async.shared::cluster.mbarrier::complete_tx::bytes.v4.b32 [%0+%6], {%2,%3,%4,%5}, [%1];"
               ::"r"(cluster_addr), "r"(cluster_bar), "r"(a), "r"(b), "r"(c), "r"(d), "n"(OFF) : "memory");
}
__device__ __forceinline__ void stsm4(uint32_t addr, uint32_t a, uint32_t b, uint32_t c, uint32_t d) {
  asm volatile("stmatrix.sync.aligned.m8n8.x4.shared.b16 [%0], {%1,%2,%3,%4};" ::"r"(addr), "r"(a), "r"(b), "r"(c), "r"(d) : "memory");
}
__device__ __forceinline__ uint32_t bfma(uint32_t a, uint32_t b, uint32_t c) {
  uint32_t d; asm volatile("fma.rn.bf16x2 %0, %1, %2, %3;" : "=r"(d) : "r"(a), "r"(b), "r"(c)); return d;
}
__device__ __forceinline__ void lds4(uint32_t (&r)[4], uint32_t addr) {
  asm volatile("ld.shared.v4.b32 {%0,%1,%2,%3}, [%4];" : "=r"(r[0]), "=r"(r[1]), "=r"(r[2]), "=r"(r[3]) : "r"(addr) : "memory");
}
__device__ __forceinline__ void sts4(uint32_t addr, const uint32_t (&r)[4]) {
  asm volatile("st.shared.v4.b32 [%0], {%1,%2,%3,%4};" ::"r"(addr), "r"(r[0]), "r"(r[1]), "r"(r[2]), "r"(r[3]) : "memory");
}
__device__ __forceinline__ void tma_store5(const CUtensorMap* map, uint32_t src, int c0, int c1, int c2, int c3, int c4) {
  asm volatile("cp.async.bulk.tensor.5d.global.shared::cta.bulk_group [%0, {%2,%3,%4,%5,%6}], [%1];"
               ::"l"(map), "r"(src), "r"(c0), "r"(c1), "r"(c2), "r"(c3), "r"(c4) : "memory");
  asm volatile("cp.async.bulk.commit_group;" ::: "memory");
}
__device__ __forceinline__ bool elect_one() {
  uint32_t p;
  asm volatile("{\n.reg .pred P;\nelect.sync _|P, 0xffffffff;\nselp.u32 %0, 1, 0, P;\n}\n" : "=r"(p));
  return p;
}
__device__ __forceinline__ uint32_t mapa(uint32_t addr, uint32_t rank) {
  uint32_t r; asm("mapa.shared::cluster.u32 %0, %1, %2;" : "=r"(r) : "r"(addr), "r"(rank)); return r;
}

__device__ __forceinline__ void tr_sum(uint32_t (&t)[3][4], const uint32_t (&U)[3][4], const uint32_t (&V)[3][4]) {
#pragma unroll
  for (int k = 0; k < 3; k++)
#pragma unroll
    for (int i = 0; i < 4; i++) t[k][i] = badd(U[k][i], V[k][i]);
}
__device__ __forceinline__ void tr_dif(uint32_t (&t)[3][4], const uint32_t (&U)[3][4], const uint32_t (&V)[3][4]) {
#pragma unroll
  for (int k = 0; k < 3; k++)
#pragma unroll
    for (int i = 0; i < 4; i++) t[k][i] = bsub(V[k][i], U[k][i]);
}
__device__ __forceinline__ void tr_t0(uint32_t (&t)[3][4], const uint32_t (&V)[3][4], const uint32_t (&E)[3][4]) {
#pragma unroll
  for (int k = 0; k < 3; k++) {
    t[k][0] = bsub(E[k][0], V[k][0]); t[k][1] = bsub(V[k][0], V[k][1]);
    t[k][2] = bsub(E[k][2], V[k][2]); t[k][3] = bsub(V[k][2], V[k][3]);
  }
}
__device__ __forceinline__ void tr_t3(uint32_t (&t)[3][4], const uint32_t (&U)[3][4], const uint32_t (&E)[3][4]) {
#pragma unroll
  for (int k = 0; k < 3; k++) {
    t[k][0] = bsub(U[k][1], U[k][0]); t[k][1] = bsub(E[k][1], U[k][1]);
    t[k][2] = bsub(U[k][3], U[k][2]); t[k][3] = bsub(E[k][3], U[k][3]);
  }
}
__device__ __forceinline__ void ld3(uint32_t (&R)[3][4], uint32_t aU, int off) {
#pragma unroll
  for (int k = 0; k < 3; k++) ldsm4(R[k], (aU ^ (32 * k)) + off);
}
template <int COMP, int AGE, int FIRST>
__device__ __forceinline__ void batch(float (&acc)[48], const uint32_t (&t)[3][4]) {
  constexpr int base = ((COMP * 3 + AGE) * 3) * BT_BYTES;
  wgmma96<FIRST ? 0 : 1, BDESC + ((base) >> 4)>(acc, t[0]);
  wgmma96<1, BDESC + ((base + BT_BYTES) >> 4)>(acc, t[1]);
  wgmma96<1, BDESC + ((base + 2 * BT_BYTES) >> 4)>(acc, t[2]);
  wg_commit();
}

#define DBG_T(c, idx)
#define DBG_TA(idx)
#define TL(c, k)
#define DBG_U(c, idx)
#define DBG_FLUSH(c)
#define DBG_G(c, idx)

struct Ctx {
  uint32_t aU, aE;
  uint32_t in_base;
  uint32_t bar_full;
  uint32_t xaddr, xfull;
  uint32_t xbase;
  const CUtensorMap* omap;
  const CUtensorMap* map;
  const char* xseg;
  int wg, warp;
  int c0, u0, h0, hstep;
  int nrows;
  bool producer;
};

__device__ __forceinline__ void prefetch_row(const Ctx& c, int h) {
  if ((unsigned)h < (unsigned)IMG_H)
    asm volatile("cp.async.bulk.prefetch.L2.global [%0], %1;" ::"l"(c.xseg + (size_t)h * (IMG_W * CH * 2)), "r"(64 * CH * 2) : "memory");
}

template <int BUF, int C0, int C1>
__device__ __forceinline__ void load_partner(const Ctx& c, uint32_t (&P)[6][4]) {
#pragma unroll
  for (int ch = C0; ch < C1; ch++) lds4(P[ch], c.xaddr + BUF * XBUF_BYTES + (ch & 1) * 6144 + (ch >> 1) * 64);
}
template <int BUF, int C0, int C1>
__device__ __forceinline__ void finish_chunks(const Ctx& c, const float (&Y)[48], uint32_t (&P)[6][4]) {
#pragma unroll
  for (int ch = C0; ch < C1; ch++) {
    const int m = ch >> 1, s = ch & 1;
#pragma unroll
    for (int ss = 0; ss < 4; ss++) P[ch][ss] = badd(pack2(Y[16 * m + 4 * ss + 2 * s], Y[16 * m + 4 * ss + 2 * s + 1]), P[ch][ss]);
    sts4(c.xaddr + BUF * XBUF_BYTES + s * 6144 + m * 64, P[ch]);
  }
}
template <int RANK, int BUF, int CH0>
__device__ __forceinline__ void send_chunk(const Ctx& c, const float (&X)[48]) {
  constexpr uint32_t RDELTA = RANK ? 0xFF000000u : 0x01000000u;
  constexpr int m = CH0 >> 1, s = CH0 & 1;
  uint32_t o[4];
#pragma unroll
  for (int ss = 0; ss < 4; ss++) o[ss] = pack2(X[16 * m + 4 * ss + 2 * s], X[16 * m + 4 * ss + 2 * s + 1]);
  st_async4<BUF * XBUF_BYTES + s * 6144 + m * 64>(c.xaddr + RDELTA, c.xfull + BUF * 64 + RDELTA, o[0], o[1], o[2], o[3]);
}

#define PF_DIST 1
#define ORD1 0
#define TAIL 0
#define NCL 66
#define RORD 0x654210
#define RORDS 0x625140
#define REL 0
#define ORD3 2
#define SLOT 0
#define ORD2 1

struct Regs {
  float X[48], Y[48];
  uint32_t T[4][2][3][4];
  uint32_t U[3][4], V[3][4], E[3][4];
};

template <int RANK, int OLD>
__device__ __forceinline__ void tma_slot(const Ctx& c, int n) {
  constexpr int MID = 1 - OLD;
  asm volatile("fence.proxy.async.shared::cta;" ::: "memory");
  asm volatile("bar.sync %0, 128;" ::"r"(2 + c.wg) : "memory");
  if (elect_one()) {
    const int h = c.h0 + n * c.hstep;
    if (c.warp < 2) {
      if (n + 2 < c.nrows) {
        mbar_expect_tx(c.bar_full + 8 * OLD, BOX_BYTES);
        tma_load5(c.in_base + OLD * STAGE_BYTES + c.warp * OFF_BOXB, c.map, c.bar_full + 8 * OLD, c.c0, 2 * c.warp, c.u0 - c.warp, 0,
                  h + 4 * c.hstep);
      } else {
        mbar_arrive(c.bar_full + 8 * OLD);
      }
    } else if (c.warp == 2) {
      if (OLD == 1 || n > 0) tma_store5(c.omap, c.xbase + MID * XBUF_BYTES, 0, c.u0, 0, RANK, h);
    } else {
      if (PF_DIST > 0 && n + 2 + PF_DIST < c.nrows) prefetch_row(c, h + (4 + PF_DIST) * c.hstep);
    }
  }
  __syncwarp();
}
template <int RANK, int OLD>
__device__ __forceinline__ void release_xbuf(const Ctx& c) {
  constexpr uint32_t RDELTA = RANK ? 0xFF000000u : 0x01000000u;
  asm volatile("cp.async.bulk.wait_group.read 0;" ::: "memory");
  asm volatile("{\n.reg .pred p;\nsetp.eq.u32 p, %1, 64;\n@p mbarrier.arrive.shared::cluster.b64 _, [%0];\n}\n"
               ::"r"(c.bar_full + 8 * (1 - OLD) + RDELTA), "r"(threadIdx.x & 127) : "memory");
}
__device__ __forceinline__ void pack_acc(uint32_t (&Z)[6][4], const float (&Y)[48]) {
#pragma unroll
  for (int ch = 0; ch < 6; ch++)
#pragma unroll
    for (int ss = 0; ss < 4; ss++) {
      const int i = 16 * (ch >> 1) + 4 * ss + 2 * (ch & 1);
      Z[ch][ss] = pack2(Y[i], Y[i + 1]);
    }
}
template <int BUF, int C0, int C1>
__device__ __forceinline__ void add_stage(const Ctx& c, uint32_t (&Z)[6][4], const uint32_t (&P)[6][4]) {
#pragma unroll
  for (int ch = C0; ch < C1; ch++)
#pragma unroll
    for (int ss = 0; ss < 4; ss++) Z[ch][ss] = badd(Z[ch][ss], P[ch][ss]);
#pragma unroll
  for (int ch = C0; ch < C1; ch++) sts4(c.xaddr + BUF * XBUF_BYTES + (ch & 1) * 6144 + (ch >> 1) * 64, Z[ch]);
}

template <int RANK, int OLD, bool FIRST>
__device__ __forceinline__ void phase1(const Ctx& c, int n, Regs& r) {
  constexpr int MID = 1 - OLD;
  uint32_t Z[6][4], P[6][4];
  wg_fence();
  if (FIRST) {
    batch<0, 1, 1>(r.X, r.T[0][MID]);
    batch<1, 1, 1>(r.Y, r.T[1][MID]);
    if ((unsigned)c.h0 < (unsigned)IMG_H) {
      wg_fence();
      batch<0, 0, 0>(r.X, r.T[0][OLD]);
      batch<1, 0, 0>(r.Y, r.T[1][OLD]);
    }
  } else {
    batch<0, 0, 1>(r.X, r.T[0][OLD]);
    if (ORD1 == 0) batch<0, 1, 0>(r.X, r.T[0][MID]);
    wg_wait<ORD1 == 0 ? 2 : 1>();
    pack_acc(Z, r.Y);
    wg_fence();
    batch<1, 0, 1>(r.Y, r.T[1][OLD]);
    if (ORD1 == 1) batch<0, 1, 0>(r.X, r.T[0][MID]);
    if (ORD3 == 0) batch<1, 1, 0>(r.Y, r.T[1][MID]);
  }
  if (FIRST) {
    mbar_wait(c.bar_full + 8 * OLD, 0);
    ld3(r.U, c.aU, OLD * STAGE_BYTES);
    ld3(r.V, c.aU, OLD * STAGE_BYTES + OFF_V);
  } else {
    mbar_wait(c.xfull + MID * 64, ((n - 1) >> 1) & 1);
    load_partner<MID, 0, 3>(c, P);
    if (elect_one()) mbar_expect_tx(c.xfull + MID * 64, X_BYTES);
    if (REL == 0) release_xbuf<RANK, OLD>(c);
    if (ORD3 == 1) { wg_fence(); batch<1, 1, 0>(r.Y, r.T[1][MID]); }
    add_stage<MID, 0, 3>(c, Z, P);
    if (RANK == 0) ld3(r.V, c.aU, OLD * STAGE_BYTES + OFF_V); else ld3(r.U, c.aU, OLD * STAGE_BYTES);
    load_partner<MID, 3, 6>(c, P);
    if (ORD3 == 2) { wg_fence(); batch<1, 1, 0>(r.Y, r.T[1][MID]); }
    if (REL == 1) release_xbuf<RANK, OLD>(c);
  }
  wg_wait<FIRST ? 1 : 3>();
  tr_sum(r.T[0][OLD], r.U, r.V);
  wg_fence();
  batch<0, 2, 0>(r.X, r.T[0][OLD]);
  if (REL == 2 && !FIRST) release_xbuf<RANK, OLD>(c);
  wg_wait<FIRST ? 1 : 2>();
  tr_dif(r.T[1][OLD], r.U, r.V);
  wg_fence();
  batch<1, 2, 0>(r.Y, r.T[1][OLD]);
  if (!FIRST) add_stage<MID, 3, 6>(c, Z, P);
  ld3(r.E, c.aE, OLD * STAGE_BYTES);
  if (SLOT == 0) tma_slot<RANK, OLD>(c, n);
  wg_wait<0>();
}

template <int RANK, int OLD, bool LAST>
__device__ __forceinline__ void phase2(const Ctx& c, int n, Regs& r) {
  constexpr int MID = 1 - OLD;
#pragma unroll
  for (int i = 0; i < 48; i++) {
    if (RANK == 0) asm volatile("sub.rn.f32 %0, %0, %1;\nfma.rn.f32 %1, %1, 0f40000000, %0;" : "+f"(r.X[i]), "+f"(r.Y[i]));
    else           asm volatile("add.rn.f32 %0, %0, %1;\nfma.rn.f32 %1, %1, 0fC0000000, %0;" : "+f"(r.X[i]), "+f"(r.Y[i]));
  }
  wg_fence();
  batch<2, 0, 0>(r.X, r.T[2][OLD]);
  batch<2, 1, 0>(r.X, r.T[2][MID]);
  if (SLOT == 1) tma_slot<RANK, OLD>(c, n);
  mbar_wait(c.bar_full + 8 * MID, ((n + 2 + MID) >> 1) & 1);
  wg_wait<1>();
  if (RANK == 0) tr_t3(r.T[2][OLD], r.U, r.E); else tr_t0(r.T[2][OLD], r.V, r.E);
  if (!LAST) { if (RANK == 0) ld3(r.U, c.aU, MID * STAGE_BYTES); else ld3(r.V, c.aU, MID * STAGE_BYTES + OFF_V); }
  wg_fence();
  batch<2, 2, 0>(r.X, r.T[2][OLD]);
  batch<3, 0, 0>(r.Y, r.T[3][OLD]);
  if (ORD2 == 1) batch<3, 1, 0>(r.Y, r.T[3][MID]);
  wg_wait<ORD2 == 1 ? 2 : 1>();
  send_chunk<RANK, OLD, 0>(c, r.X); send_chunk<RANK, OLD, 1>(c, r.X); send_chunk<RANK, OLD, 2>(c, r.X);
  if (ORD2 == 2) { wg_fence(); batch<3, 1, 0>(r.Y, r.T[3][MID]); }
  send_chunk<RANK, OLD, 3>(c, r.X); send_chunk<RANK, OLD, 4>(c, r.X); send_chunk<RANK, OLD, 5>(c, r.X);
  if (ORD2 == 0) { wg_fence(); batch<3, 1, 0>(r.Y, r.T[3][MID]); }
  wg_wait<1>();
  if (RANK == 0) tr_t0(r.T[3][OLD], r.V, r.E); else tr_t3(r.T[3][OLD], r.U, r.E);
  wg_fence();
  batch<3, 2, 0>(r.Y, r.T[3][OLD]);
}

template <int RANK, int BUF>
__device__ __forceinline__ void finish_strip(const Ctx& c, Regs& r) {
  DBG_T(c, 35);
  uint32_t P[6][4];
  mbar_wait(c.xfull + BUF * 64, ((c.nrows - 1) >> 1) & 1);
  load_partner<BUF, 0, 6>(c, P);
  wg_wait<0>();
  finish_chunks<BUF, 0, 6>(c, r.Y, P);
  asm volatile("fence.proxy.async.shared::cta;" ::: "memory");
  asm volatile("bar.sync %0, 128;" ::"r"(2 + c.wg) : "memory");
  if (c.warp == 2 && elect_one()) {
    tma_store5(c.omap, c.xbase + BUF * XBUF_BYTES, 0, c.u0, 0, RANK, c.h0 + c.nrows * c.hstep);
    asm volatile("cp.async.bulk.wait_group.read 0;" ::: "memory");
  }
  DBG_T(c, 40); DBG_G(c, 1); DBG_FLUSH(c);
}

template <int RANK>
__device__ __forceinline__ void run_strip(const Ctx& c, uint32_t row0_off, uint32_t bar_row0) {
  Regs r;
#pragma unroll
  for (int m = 0; m < 2; m++) {
    const uint32_t off = m ? STAGE_BYTES : row0_off;
    mbar_wait(m ? c.bar_full + 8 : bar_row0, 0);
    DBG_T(c, 50 + m);
    ld3(r.U, c.aU, off);
    ld3(r.V, c.aU, off + OFF_V);
    ld3(r.E, c.aE, off);
    tr_sum(r.T[0][m], r.U, r.V);
    tr_dif(r.T[1][m], r.U, r.V);
    tr_t3(r.T[RANK == 0 ? 2 : 3][m], r.U, r.E);
    tr_t0(r.T[RANK == 0 ? 3 : 2][m], r.V, r.E);
  }
  asm volatile("bar.sync %0, 128;" ::"r"(2 + c.wg) : "memory");
  asm volatile("barrier.cluster.wait.aligned;" ::: "memory");
  if (elect_one()) {
    if (c.warp < 2) {
      mbar_expect_tx(c.bar_full + 8, BOX_BYTES);
      tma_load5(c.in_base + STAGE_BYTES + c.warp * OFF_BOXB, c.map, c.bar_full + 8, c.c0, 2 * c.warp, c.u0 - c.warp, 0, c.h0 + 3 * c.hstep);
    } else if (c.warp == 2) {
      asm volatile("mbarrier.arrive.shared::cluster.b64 _, [%0];" ::"r"((bar_row0 + (BAR_READY - BAR_ROW0) * 8) ^ 0x01000000u) : "memory");
    } else {
      mbar_arrive(c.bar_full + 8);
    }
  }
  __syncwarp();
  DBG_T(c, 46);
  mbar_wait(SMEM_BASE + (RANK << 24) + OFF_BAR + 8 * BAR_W + 24, 0);
  DBG_T(c, 3);
#pragma unroll
  for (int i = 0; i < 48; i++) { r.X[i] = 0.f; r.Y[i] = 0.f; }
  phase1<RANK, 0, true>(c, 0, r);
  mbar_wait(bar_row0 + (BAR_READY - BAR_ROW0) * 8, 0);
#pragma unroll 1
  for (int n = 0;; n += 2) {
    phase2<RANK, 0, false>(c, n, r);
    if (n + 1 == c.nrows) { finish_strip<RANK, 0>(c, r); break; }
    phase1<RANK, 1, false>(c, n + 1, r);
    phase2<RANK, 1, false>(c, n + 1, r);
    if (n + 2 == c.nrows) { finish_strip<RANK, 1>(c, r); break; }
    phase1<RANK, 0, false>(c, n + 2, r);
  }
}

struct Strip { int seg, h0, hstep, nrows; };
__device__ __forceinline__ Strip get_strip(int cl, int wg) {
  int seg, par, r0, nrows; bool down;
  if (NCL == 64) {
    const int sid = cl * 2 + wg;
    seg = sid & 3; par = (sid >> 2) & 1; r0 = (sid >> 3) * 16; nrows = 16; down = !((sid >> 3) & 1);
  } else if (cl >= 64) {
    seg = (cl - 64) * 2 + wg; par = 1; r0 = 0; nrows = 16; down = true;
  } else {
    const int i = cl >> 2;
    seg = cl & 3; par = wg; down = !(i & 1);
    r0 = wg ? 16 + 15 * (down ? i + 1 : i - 1) : 16 * i;
    nrows = 16 - wg;
  }
  return Strip{seg, 2 * (down ? r0 - 1 : r0 + nrows) + par, down ? 2 : -2, nrows};
}

__global__ void __cluster_dims__(2, 1, 1) __launch_bounds__(256, 1)
dilated_conv_wino_kernel(const __grid_constant__ CUtensorMap xmap, const __grid_constant__ CUtensorMap omap,
                         const __nv_bfloat16* __restrict__ x, const __nv_bfloat16* __restrict__ w) {
  extern __shared__ uint8_t smem_raw[];
  const int tid = threadIdx.x;
  const int wg = __shfl_sync(0xffffffff, tid >> 7, 0);
  const int warp = __shfl_sync(0xffffffff, (tid >> 5) & 3, 0);
  const int lane = tid & 31;
  const int rank = blockIdx.x & 1;
  const uint32_t sbase = SMEM_BASE + (rank << 24);
  if ((uint32_t)__cvta_generic_to_shared(smem_raw) != sbase || mapa(sbase, rank ^ 1) != (sbase ^ 0x01000000u)) __trap();
  const int cl = blockIdx.x >> 1;
  const Strip sp = get_strip(cl, wg);
  const bool down = sp.hstep > 0;

  Ctx c;
  c.map = &xmap;
  c.wg = wg;
  c.warp = warp;
  c.in_base = sbase + OFF_IN + wg * WG_IN_BYTES;
  c.bar_full = sbase + OFF_BAR + 8 * (BAR_FULL + wg * NSTAGE);
  c.c0 = rank * 48;
  c.u0 = sp.seg * 16;
  c.h0 = sp.h0;
  c.hstep = sp.hstep;
  c.nrows = sp.nrows;
  c.producer = (tid & 127) == 0;
  c.xfull = sbase + OFF_BAR + 8 * (BAR_XFULL + wg * 4 + warp);
  c.xseg = reinterpret_cast<const char*>(x) + (sp.seg * 128 + rank * 64) * (CH * 2);

  DBG_G(c, 0); DBG_T(c, 0);
  const uint32_t bar_w = sbase + OFF_BAR + 8 * BAR_W;
  const uint32_t o_w0 = (rank ? 2 : 3) * 9 * BT_BYTES, o_w2 = (rank ? 3 : 2) * 9 * BT_BYTES;
  if (elect_one()) {
    const uint32_t b0 = sbase + OFF_BAR;
    const int w8 = wg * 4 + warp;
    if (w8 >= 5) {
      const int a = w8 - 5, i = down ? a : 2 - a;
      const __nv_bfloat16* src = w + ((size_t)(i * 3) * CH + rank * 48) * CH;
      const uint32_t dst = sbase + OFF_W + a * 3 * BT_BYTES;
      mbar_init(bar_w + 8 * a, 1);
      asm volatile("fence.proxy.async.shared::cta;" ::: "memory");
      mbar_expect_tx(bar_w + 8 * a, 9 * BT_BYTES);
      bulk_load(dst + o_w0, src, 3 * BT_BYTES, bar_w + 8 * a);
      bulk_load(dst, src + CH * CH, 3 * BT_BYTES, bar_w + 8 * a);
      bulk_load(dst + o_w2, src + 2 * CH * CH, 3 * BT_BYTES, bar_w + 8 * a);
      DBG_TA(53 + a);
    } else {
      if (w8 < 4) {
        mbar_init(b0 + 8 * w8, 3);
#pragma unroll
        for (int q = 0; q < 4; q++) mbar_init(b0 + 8 * (BAR_XFULL + 4 * w8 + q), 1);
        mbar_expect_tx(b0 + 8 * w8, 2 * BOX_BYTES);
        asm volatile("mbarrier.arrive.shared::cta.b64 _, [%0], 2;" ::"r"(b0 + 8 * w8) : "memory");
      } else {
        asm volatile("prefetch.tensormap [%0];" ::"l"(&xmap) : "memory");
#pragma unroll
        for (int q = 0; q < 2; q++) {
          mbar_init(b0 + 8 * (BAR_ROW0 + q), 1);
          mbar_init(b0 + 8 * (BAR_READY + q), 1);
          mbar_expect_tx(b0 + 8 * (BAR_ROW0 + q), 2 * BOX_BYTES);
        }
        mbar_init(bar_w + 24, 6);
      }
      asm volatile("fence.mbarrier_init.release.cluster;" ::: "memory");
      asm volatile("fence.proxy.async.shared::cta;" ::: "memory");
    }
  }
  DBG_T(c, 45);
  __syncthreads();
  asm volatile("barrier.cluster.arrive.relaxed.aligned;" ::: "memory");
  DBG_T(c, 41);
  const uint32_t row0 = sbase + (wg ? OFF_ROW0_1 : OFF_ROW0_0);
  const uint32_t bar_row0 = sbase + OFF_BAR + 8 * (BAR_ROW0 + wg);
  if (warp == 3) {
    if (elect_one()) {
      const Strip so = get_strip(cl, wg ^ 1);
#pragma unroll 1
      for (int k = 0; k < 6; k++) {
        const int code = ((cl < 64 ? RORD : RORDS) >> (4 * k)) & 15, g = code >> 2, m = code & 3;
        const uint32_t dst = m == 0 ? sbase + (g ? OFF_ROW0_1 : OFF_ROW0_0) : sbase + OFF_IN + g * WG_IN_BYTES + (m & 1) * STAGE_BYTES;
        const uint32_t bar = sbase + OFF_BAR + 8 * (m == 0 ? BAR_ROW0 + g : BAR_FULL + 2 * g + (m & 1));
        tma_load5(dst + wg * OFF_BOXB, &xmap, bar, c.c0, 2 * wg, (g == wg ? sp.seg : so.seg) * 16 - wg, 0, (g == wg ? sp.h0 : so.h0) + m * c.hstep);
      }
      asm volatile("prefetch.tensormap [%0];" ::"l"(&omap) : "memory");
      DBG_TA(49);
    }
    __syncwarp();
  } else {
#pragma unroll 1
    for (int age = 0; age < 3; age++) {
      const uint32_t base = sbase + OFF_W + (age * 6 + wg * 3 + warp) * 1536;
      mbar_wait(bar_w + 8 * age, 0);
      DBG_T(c, 42 + age);
      uint32_t wa[3][4], wb[3][4], wd[3][4];
      const uint32_t src = base + (lane >> 2) * 192 + (lane & 3) * 16;
#pragma unroll
      for (int m = 0; m < 3; m++) {
        lds4(wa[m], src + o_w0 + m * 64);
        lds4(wb[m], src + m * 64);
        lds4(wd[m], src + o_w2 + m * 64);
      }
      __syncwarp();
      const uint32_t dst = base + lane * 16;
#pragma unroll
      for (int m = 0; m < 3; m++) {
        uint32_t g1[4], g2[4];
        stsm4(dst + m * 512 + o_w0, wa[m][0], wa[m][1], wa[m][2], wa[m][3]);
        stsm4(dst + m * 512 + o_w2, wd[m][0], wd[m][1], wd[m][2], wd[m][3]);
#pragma unroll
        for (int ss = 0; ss < 4; ss++) {
          const uint32_t a = wa[m][ss], b = wb[m][ss], d = wd[m][ss];
          const float slo = __uint_as_float(a << 16) + __uint_as_float(d << 16);
          const float shi = __uint_as_float(a & 0xffff0000u) + __uint_as_float(d & 0xffff0000u);
          const float blo = 0.5f * __uint_as_float(b << 16), bhi = 0.5f * __uint_as_float(b & 0xffff0000u);
          g1[ss] = pack2(fmaf(slo, 0.5f, blo), fmaf(shi, 0.5f, bhi));
          g2[ss] = pack2(fmaf(slo, 0.5f, -blo), fmaf(shi, 0.5f, -bhi));
        }
        stsm4(dst + m * 512, g1[0], g1[1], g1[2], g1[3]);
        stsm4(dst + m * 512 + 9 * BT_BYTES, g2[0], g2[1], g2[2], g2[3]);
      }
    }
    asm volatile("fence.proxy.async.shared::cta;" ::: "memory");
    __syncwarp();
    if (elect_one()) mbar_arrive(bar_w + 24);
  }
  if (elect_one()) { mbar_expect_tx(c.xfull, X_BYTES); mbar_expect_tx(c.xfull + 64, X_BYTES); }
  DBG_T(c, 1);

  {
    const int g = lane & 7, mi = lane >> 3;
    const int rU = 8 * warp + g + ((mi & 1) ? 34 : 0);
    const int rE = 8 * warp + g + ((mi & 1) ? 2 : 70 + 34);
    const uint32_t pU = c.in_base + rU * 128, pE = c.in_base + rE * 128;
    c.aU = pU + (((mi >> 1) ^ ((pU >> 7) & 7)) << 4);
    c.aE = pE + (((mi >> 1) ^ ((pE >> 7) & 7)) << 4);
  }
  c.xbase = sbase + OFF_X + wg * 2 * XBUF_BYTES;
  c.xaddr = c.xbase + (warp * 8 + (lane >> 2)) * 192 + (lane & 3) * 16;
  c.omap = &omap;
  if (rank == 0) run_strip<0>(c, row0 - c.in_base, bar_row0); else run_strip<1>(c, row0 - c.in_base, bar_row0);
}

typedef CUresult (*EncodeTiledFn)(CUtensorMap*, CUtensorMapDataType, cuuint32_t, void*, const cuuint64_t*, const cuuint64_t*,
                                  const cuuint32_t*, const cuuint32_t*, CUtensorMapInterleave, CUtensorMapSwizzle,
                                  CUtensorMapL2promotion, CUtensorMapFloatOOBfill);

}

extern "C" void kernel_launch(void* const* d_in, const int* in_sizes, int n_in, void* d_out, int out_size) {
  (void)in_sizes; (void)n_in; (void)out_size;
  static EncodeTiledFn encode = nullptr;
  if (!encode) {
    void* fn = nullptr;
    cudaDriverEntryPointQueryResult qr;
    cudaGetDriverEntryPoint("cuTensorMapEncodeTiled", &fn, cudaEnableDefault, &qr);
    encode = (EncodeTiledFn)fn;
    cudaFuncSetAttribute(dilated_conv_wino_kernel, cudaFuncAttributeMaxDynamicSharedMemorySize, SMEM_BYTES);
  }
  CUtensorMap xmap;
  const cuuint64_t dims[5] = {CH, 4, IMG_W / 8, 2, IMG_H};
  const cuuint64_t strides[4] = {CH * 2, 8 * CH * 2, 4 * CH * 2, IMG_W * CH * 2};
  const cuuint32_t box[5] = {48, 2, 17, 2, 1};
  const cuuint32_t estr[5] = {1, 1, 1, 1, 1};
#define PROMO CU_TENSOR_MAP_L2_PROMOTION_L2_128B
  encode(&xmap, CU_TENSOR_MAP_DATA_TYPE_BFLOAT16, 5, d_in[0], dims, strides, box, estr, CU_TENSOR_MAP_INTERLEAVE_NONE,
         CU_TENSOR_MAP_SWIZZLE_128B, PROMO, CU_TENSOR_MAP_FLOAT_OOB_FILL_NONE);
  CUtensorMap omap;
  const cuuint64_t odims[5] = {2 * CH, IMG_W / 8, 2, 2, IMG_H};
  const cuuint64_t ostrides[4] = {8 * CH * 2, 4 * CH * 2, 2 * CH * 2, IMG_W * CH * 2};
  const cuuint32_t obox[5] = {2 * CH, 16, 2, 1, 1};
  encode(&omap, CU_TENSOR_MAP_DATA_TYPE_BFLOAT16, 5, d_out, odims, ostrides, obox, estr, CU_TENSOR_MAP_INTERLEAVE_NONE,
         CU_TENSOR_MAP_SWIZZLE_NONE, CU_TENSOR_MAP_L2_PROMOTION_NONE, CU_TENSOR_MAP_FLOAT_OOB_FILL_NONE);
  dilated_conv_wino_kernel<<<2 * NCL, 256, SMEM_BYTES>>>(xmap, omap, (const __nv_bfloat16*)d_in[0], (const __nv_bfloat16*)d_in[1]);
}
```

```cpp
#include <cuda_runtime.h>
#include <cuda_bf16.h>
#include <cuda.h>
#include <stdint.h>

namespace {

constexpr int IMG_H = 512, IMG_W = 512, CH = 96;
constexpr int NSTAGE = 2;

constexpr int BT_BYTES   = 3072;
constexpr int W_BYTES    = 36 * BT_BYTES;
constexpr int BOX_BYTES  = 68 * 96;
constexpr int OFF_BOXB   = 70 * 128;
constexpr int STAGE_BYTES = 144 * 128;
constexpr int OFF_V      = 72 * 128;
constexpr int WG_IN_BYTES = STAGE_BYTES + 138 * 128;
constexpr int OFF_W      = 0;
constexpr int OFF_IN     = OFF_W + W_BYTES;
constexpr int OFF_X      = OFF_IN + 2 * WG_IN_BYTES;
constexpr int X_BYTES    = 3072;
constexpr int XBUF_BYTES = 4 * X_BYTES;
constexpr int SMEM_BYTES = OFF_X + 4 * XBUF_BYTES;
constexpr int OFF_ROW0_0 = OFF_X + ((OFF_IN - OFF_X) & 1023);
constexpr int OFF_ROW0_1 = OFF_X + 2 * XBUF_BYTES + ((OFF_IN + WG_IN_BYTES - OFF_X) & 1023);
constexpr int OFF_BAR    = OFF_IN + 68 * 128;
constexpr int BAR_FULL = 0, BAR_XFULL = 8, BAR_W = 24, BAR_ROW0 = 28, BAR_READY = 30;
constexpr int OFF_DBG    = OFF_IN + 138 * 128;
static_assert(SMEM_BYTES <= 232448, "shared memory");
constexpr uint32_t SMEM_BASE = 1024;
constexpr uint64_t BDESC = (uint64_t)((SMEM_BASE + OFF_W) >> 4) | ((uint64_t)(1536 >> 4) << 16) | ((uint64_t)(128 >> 4) << 32);

__device__ __forceinline__ void wg_fence()  { asm volatile("wgmma.fence.sync.aligned;" ::: "memory"); }
__device__ __forceinline__ void wg_commit() { asm volatile("wgmma.commit_group.sync.aligned;" ::: "memory"); }
template <int N> __device__ __forceinline__ void wg_wait() { asm volatile("wgmma.wait_group.sync.aligned %0;" ::"n"(N) : "memory"); }

template <int SCALE_D>
__device__ __forceinline__ void wgmma96(float (&d)[48], const uint32_t (&a)[4], uint64_t DESC) {
  asm volatile(
      "{\n.reg .pred p;\nsetp.ne.b32 p, %53, 0;\n"
      "wgmma.mma_async.sync.aligned.m64n96k16.f32.bf16.bf16 "
      "{%0,%1,%2,%3,%4,%5,%6,%7,%8,%9,%10,%11,%12,%13,%14,%15,%16,%17,%18,%19,%20,%21,%22,%23,"
      "%24,%25,%26,%27,%28,%29,%30,%31,%32,%33,%34,%35,%36,%37,%38,%39,%40,%41,%42,%43,%44,%45,%46,%47}, "
      "{%48,%49,%50,%51}, %52, p, 1, 1, 1;\n}\n"
      : "+f"(d[0]), "+f"(d[1]), "+f"(d[2]), "+f"(d[3]), "+f"(d[4]), "+f"(d[5]), "+f"(d[6]), "+f"(d[7]),
        "+f"(d[8]), "+f"(d[9]), "+f"(d[10]), "+f"(d[11]), "+f"(d[12]), "+f"(d[13]), "+f"(d[14]), "+f"(d[15]),
        "+f"(d[16]), "+f"(d[17]), "+f"(d[18]), "+f"(d[19]), "+f"(d[20]), "+f"(d[21]), "+f"(d[22]), "+f"(d[23]),
        "+f"(d[24]), "+f"(d[25]), "+f"(d[26]), "+f"(d[27]), "+f"(d[28]), "+f"(d[29]), "+f"(d[30]), "+f"(d[31]),
        "+f"(d[32]), "+f"(d[33]), "+f"(d[34]), "+f"(d[35]), "+f"(d[36]), "+f"(d[37]), "+f"(d[38]), "+f"(d[39]),
        "+f"(d[40]), "+f"(d[41]), "+f"(d[42]), "+f"(d[43]), "+f"(d[44]), "+f"(d[45]), "+f"(d[46]), "+f"(d[47])
      : "r"(a[0]), "r"(a[1]), "r"(a[2]), "r"(a[3]), "l"(DESC), "n"(SCALE_D));
}

__device__ __forceinline__ void ldsm4(uint32_t (&r)[4], uint32_t addr) {
  asm volatile("ldmatrix.sync.aligned.m8n8.x4.shared.b16 {%0,%1,%2,%3}, [%4];"
               : "=r"(r[0]), "=r"(r[1]), "=r"(r[2]), "=r"(r[3]) : "r"(addr) : "memory");
}
__device__ __forceinline__ uint32_t badd(uint32_t a, uint32_t b) {
  uint32_t d; asm volatile("add.rn.bf16x2 %0, %1, %2;" : "=r"(d) : "r"(a), "r"(b)); return d;
}
__device__ __forceinline__ uint32_t bsub(uint32_t a, uint32_t b) {
  uint32_t d; asm volatile("sub.rn.bf16x2 %0, %1, %2;" : "=r"(d) : "r"(a), "r"(b)); return d;
}
__device__ __forceinline__ uint32_t pack2(float lo, float hi) {
  uint32_t d; asm volatile("cvt.rn.bf16x2.f32 %0, %1, %2;" : "=r"(d) : "f"(hi), "f"(lo)); return d;
}

__device__ __forceinline__ void mbar_wait(uint32_t bar, uint32_t parity) {
  asm volatile(
      "{\n.reg .pred p;\n.reg .u32 it;\n"
      "mbarrier.try_wait.parity.shared::cta.b64 p, [%0], %1;\n"
      "@p bra WAIT_DONE;\n"
      "mov.u32 it, 0;\n"
      "WAIT_LOOP:\n"
      ".pragma \"nounroll\";\n"
      "mbarrier.try_wait.parity.shared::cta.b64 p, [%0], %1;\n"
      "@p bra WAIT_DONE;\n"
      "add.u32 it, it, 1;\n"
      "setp.lt.u32 p, it, 4194304;\n"
      "@p bra WAIT_LOOP;\n"
      "trap;\n"
      "WAIT_DONE:\n}\n" ::"r"(bar), "r"(parity) : "memory");
}
__device__ __forceinline__ bool mbar_try(uint32_t bar, uint32_t parity) {
  uint32_t ok;
  asm volatile("{\n.reg .pred p;\nmbarrier.test_wait.parity.shared::cta.b64 p, [%1], %2;\nselp.u32 %0, 1, 0, p;\n}\n"
               : "=r"(ok) : "r"(bar), "r"(parity) : "memory");
  return ok;
}
__device__ __forceinline__ void mbar_init(uint32_t bar, uint32_t count) {
  asm volatile("mbarrier.init.shared::cta.b64 [%0], %1;" ::"r"(bar), "r"(count) : "memory");
}
__device__ __forceinline__ void mbar_arrive(uint32_t bar) {
  asm volatile("mbarrier.arrive.shared::cta.b64 _, [%0];" ::"r"(bar) : "memory");
}
__device__ __forceinline__ void mbar_expect_tx(uint32_t bar, uint32_t bytes) {
  asm volatile("mbarrier.arrive.expect_tx.shared::cta.b64 _, [%0], %1;" ::"r"(bar), "r"(bytes) : "memory");
}
__device__ __forceinline__ void tma_load5(uint32_t dst, const CUtensorMap* map, uint32_t bar, int c0, int c1, int c2, int c3, int c4) {
  asm volatile("cp.async.bulk.tensor.5d.shared::cluster.global.mbarrier::complete_tx::bytes [%0], [%1, {%3,%4,%5,%6,%7}], [%2];"
               ::"r"(dst), "l"(map), "r"(bar), "r"(c0), "r"(c1), "r"(c2), "r"(c3), "r"(c4) : "memory");
}
__device__ __forceinline__ void bulk_load(uint32_t dst, const void* src, uint32_t bytes, uint32_t bar) {
  asm volatile("cp.async.bulk.shared::cluster.global.mbarrier::complete_tx::bytes [%0], [%1], %2, [%3];"
               ::"r"(dst), "l"(src), "r"(bytes), "r"(bar) : "memory");
}
template <int OFF>
__device__ __forceinline__ void st_async4(uint32_t cluster_addr, uint32_t cluster_bar, uint32_t a, uint32_t b, uint32_t c, uint32_t d) {
  asm volatile("st.async.shared::cluster.mbarrier::complete_tx::bytes.v4.b32 [%0+%6], {%2,%3,%4,%5}, [%1];"
               ::"r"(cluster_addr), "r"(cluster_bar), "r"(a), "r"(b), "r"(c), "r"(d), "n"(OFF) : "memory");
}
__device__ __forceinline__ void stsm4(uint32_t addr, uint32_t a, uint32_t b, uint32_t c, uint32_t d) {
  asm volatile("stmatrix.sync.aligned.m8n8.x4.shared.b16 [%0], {%1,%2,%3,%4};" ::"r"(addr), "r"(a), "r"(b), "r"(c), "r"(d) : "memory");
}
__device__ __forceinline__ uint32_t bfma(uint32_t a, uint32_t b, uint32_t c) {
  uint32_t d; asm volatile("fma.rn.bf16x2 %0, %1, %2, %3;" : "=r"(d) : "r"(a), "r"(b), "r"(c)); return d;
}
__device__ __forceinline__ void lds4(uint32_t (&r)[4], uint32_t addr) {
  asm volatile("ld.shared.v4.b32 {%0,%1,%2,%3}, [%4];" : "=r"(r[0]), "=r"(r[1]), "=r"(r[2]), "=r"(r[3]) : "r"(addr) : "memory");
}
__device__ __forceinline__ void sts4(uint32_t addr, const uint32_t (&r)[4]) {
  asm volatile("st.shared.v4.b32 [%0], {%1,%2,%3,%4};" ::"r"(addr), "r"(r[0]), "r"(r[1]), "r"(r[2]), "r"(r[3]) : "memory");
}
__device__ __forceinline__ void tma_store5(const CUtensorMap* map, uint32_t src, int c0, int c1, int c2, int c3, int c4) {
  asm volatile("cp.async.bulk.tensor.5d.global.shared::cta.bulk_group [%0, {%2,%3,%4,%5,%6}], [%1];"
               ::"l"(map), "r"(src), "r"(c0), "r"(c1), "r"(c2), "r"(c3), "r"(c4) : "memory");
  asm volatile("cp.async.bulk.commit_group;" ::: "memory");
}
__device__ __forceinline__ bool elect_one() {
  uint32_t p;
  asm volatile("{\n.reg .pred P;\nelect.sync _|P, 0xffffffff;\nselp.u32 %0, 1, 0, P;\n}\n" : "=r"(p));
  return p;
}
__device__ __forceinline__ uint32_t mapa(uint32_t addr, uint32_t rank) {
  uint32_t r; asm("mapa.shared::cluster.u32 %0, %1, %2;" : "=r"(r) : "r"(addr), "r"(rank)); return r;
}

__device__ __forceinline__ void tr_sum(uint32_t (&t)[3][4], const uint32_t (&U)[3][4], const uint32_t (&V)[3][4]) {
#pragma unroll
  for (int k = 0; k < 3; k++)
#pragma unroll
    for (int i = 0; i < 4; i++) t[k][i] = badd(U[k][i], V[k][i]);
}
__device__ __forceinline__ void tr_dif(uint32_t (&t)[3][4], const uint32_t (&U)[3][4], const uint32_t (&V)[3][4]) {
#pragma unroll
  for (int k = 0; k < 3; k++)
#pragma unroll
    for (int i = 0; i < 4; i++) t[k][i] = bsub(V[k][i], U[k][i]);
}
__device__ __forceinline__ void tr_t0(uint32_t (&t)[3][4], const uint32_t (&V)[3][4], const uint32_t (&E)[3][4]) {
#pragma unroll
  for (int k = 0; k < 3; k++) {
    t[k][0] = bsub(E[k][0], V[k][0]); t[k][1] = bsub(V[k][0], V[k][1]);
    t[k][2] = bsub(E[k][2], V[k][2]); t[k][3] = bsub(V[k][2], V[k][3]);
  }
}
__device__ __forceinline__ void tr_t3(uint32_t (&t)[3][4], const uint32_t (&U)[3][4], const uint32_t (&E)[3][4]) {
#pragma unroll
  for (int k = 0; k < 3; k++) {
    t[k][0] = bsub(U[k][1], U[k][0]); t[k][1] = bsub(E[k][1], U[k][1]);
    t[k][2] = bsub(U[k][3], U[k][2]); t[k][3] = bsub(E[k][3], U[k][3]);
  }
}
__device__ __forceinline__ void ld3(uint32_t (&R)[3][4], uint32_t aU, int off) {
#pragma unroll
  for (int k = 0; k < 3; k++) ldsm4(R[k], (aU ^ (32 * k)) + off);
}
template <int COMP, int AGE, int FIRST>
__device__ __forceinline__ void batch_(float (&acc)[48], const uint32_t (&t)[3][4], uint64_t bd) {
  constexpr int base = ((COMP * 3 + AGE) * 3) * BT_BYTES;
  wgmma96<FIRST ? 0 : 1>(acc, t[0], bd + ((base) >> 4));
  wgmma96<1>(acc, t[1], bd + ((base + BT_BYTES) >> 4));
  wgmma96<1>(acc, t[2], bd + ((base + 2 * BT_BYTES) >> 4));
  wg_commit();
}

#define DBG_T(c, idx)
#define DBG_TA(idx)
#define TL(c, k)
#define DBG_U(c, idx)
#define DBG_FLUSH(c)
#define DBG_G(c, idx)

struct Ctx {
  uint32_t aU, aE;
  uint32_t in_base;
  uint32_t bar_full;
  uint32_t xaddr, xfull;
  uint32_t xbase;
  const CUtensorMap* omap;
  const CUtensorMap* map;
  const char* xseg;
  int wg, warp;
  int c0, u0, h0, hstep;
  int nrows;
  bool producer;
};

__device__ __forceinline__ void prefetch_row(const Ctx& c, int h) {
  if ((unsigned)h < (unsigned)IMG_H)
    asm volatile("cp.async.bulk.prefetch.L2.global [%0], %1;" ::"l"(c.xseg + (size_t)h * (IMG_W * CH * 2)), "r"(64 * CH * 2) : "memory");
}

template <int BUF, int C0, int C1>
__device__ __forceinline__ void load_partner(const Ctx& c, uint32_t (&P)[6][4]) {
#pragma unroll
  for (int ch = C0; ch < C1; ch++) lds4(P[ch], c.xaddr + BUF * XBUF_BYTES + (ch & 1) * 6144 + (ch >> 1) * 64);
}
template <int BUF, int C0, int C1>
__device__ __forceinline__ void finish_chunks(const Ctx& c, const float (&Y)[48], uint32_t (&P)[6][4]) {
#pragma unroll
  for (int ch = C0; ch < C1; ch++) {
    const int m = ch >> 1, s = ch & 1;
#pragma unroll
    for (int ss = 0; ss < 4; ss++) P[ch][ss] = badd(pack2(Y[16 * m + 4 * ss + 2 * s], Y[16 * m + 4 * ss + 2 * s + 1]), P[ch][ss]);
    sts4(c.xaddr + BUF * XBUF_BYTES + s * 6144 + m * 64, P[ch]);
  }
}
template <int RANK, int BUF, int CH0>
__device__ __forceinline__ void send_chunk(const Ctx& c, const float (&X)[48]) {
  constexpr uint32_t RDELTA = RANK ? 0xFF000000u : 0x01000000u;
  constexpr int m = CH0 >> 1, s = CH0 & 1;
  uint32_t o[4];
#pragma unroll
  for (int ss = 0; ss < 4; ss++) o[ss] = pack2(X[16 * m + 4 * ss + 2 * s], X[16 * m + 4 * ss + 2 * s + 1]);
  st_async4<BUF * XBUF_BYTES + s * 6144 + m * 64>(c.xaddr + RDELTA, c.xfull + BUF * 64 + RDELTA, o[0], o[1], o[2], o[3]);
}

#define SLOTV 0
#define PF_DIST 1
#define NCL 66
#define RORD 0x654210
#define RORDS 0x625140

struct Regs {
  float X[48], Y[48];
  uint32_t T[4][2][3][4];
  uint32_t U[3][4], V[3][4], E[3][4];
  uint32_t Z[6][4], P[6][4];
};

template <int RANK, int OLD>
__device__ __forceinline__ void tma_slot(const Ctx& c, int n) {
  constexpr int MID = 1 - OLD;
  const int h = c.h0 + n * c.hstep;
  asm volatile("fence.proxy.async.shared::cta;" ::: "memory");
  asm volatile("bar.sync %0, 128;" ::"r"(2 + c.wg) : "memory");
  if (elect_one()) {
    if (c.warp < 2) {
      if (n + 2 < c.nrows) {
        mbar_expect_tx(c.bar_full + 8 * OLD, BOX_BYTES);
        tma_load5(c.in_base + OLD * STAGE_BYTES + c.warp * OFF_BOXB, c.map, c.bar_full + 8 * OLD, c.c0, 2 * c.warp, c.u0 - c.warp, 0,
                  h + 4 * c.hstep);
      } else {
        mbar_arrive(c.bar_full + 8 * OLD);
      }
    } else if (c.warp == 2) {
      if (OLD == 1 || n > 0) tma_store5(c.omap, c.xbase + MID * XBUF_BYTES, 0, c.u0, 0, RANK, h);
    } else {
      if (PF_DIST > 0 && n + 2 + PF_DIST < c.nrows) prefetch_row(c, h + (4 + PF_DIST) * c.hstep);
    }
  }
  __syncwarp();
}
template <int RANK, int OLD>
__device__ __forceinline__ void release_xbuf(const Ctx& c) {
  constexpr uint32_t RDELTA = RANK ? 0xFF000000u : 0x01000000u;
  asm volatile("cp.async.bulk.wait_group.read 0;" ::: "memory");
  asm volatile("{\n.reg .pred p, q;\nelect.sync _|q, 0xffffffff;\nsetp.eq.and.u32 p, %1, 2, q;\n@p mbarrier.arrive.shared::cluster.b64 _, [%0];\n}\n"
               ::"r"(c.bar_full + 8 * (1 - OLD) + RDELTA), "r"(c.warp) : "memory");
}
__device__ __forceinline__ void pack_acc(uint32_t (&Z)[6][4], const float (&Y)[48]) {
#pragma unroll
  for (int ch = 0; ch < 6; ch++)
#pragma unroll
    for (int ss = 0; ss < 4; ss++) {
      const int i = 16 * (ch >> 1) + 4 * ss + 2 * (ch & 1);
      Z[ch][ss] = pack2(Y[i], Y[i + 1]);
    }
}
template <int BUF, int C0, int C1>
__device__ __forceinline__ void add_stage(const Ctx& c, uint32_t (&Z)[6][4], const uint32_t (&P)[6][4]) {
#pragma unroll
  for (int ch = C0; ch < C1; ch++)
#pragma unroll
    for (int ss = 0; ss < 4; ss++) Z[ch][ss] = badd(Z[ch][ss], P[ch][ss]);
#pragma unroll
  for (int ch = C0; ch < C1; ch++) sts4(c.xaddr + BUF * XBUF_BYTES + (ch & 1) * 6144 + (ch >> 1) * 64, Z[ch]);
}

__device__ __forceinline__ uint64_t get_bd(const Ctx& c, int n) {
  return BDESC;
}
#define G1  batch_<0, 0, 1>(r.X, r.T[0][OLD], bd);
#define G2  batch_<0, 1, 0>(r.X, r.T[0][MID], bd);
#define G3  batch_<0, 2, 0>(r.X, r.T[0][OLD], bd);
#define G4  batch_<1, 0, 1>(r.Y, r.T[1][OLD], bd);
#define G5  batch_<1, 1, 0>(r.Y, r.T[1][MID], bd);
#define G6  batch_<1, 2, 0>(r.Y, r.T[1][OLD], bd);
#define G7  batch_<2, 0, 0>(r.X, r.T[2][OLD], bd);
#define G8  batch_<2, 1, 0>(r.X, r.T[2][MID], bd);
#define G9  batch_<2, 2, 0>(r.X, r.T[2][OLD], bd);
#define G10 batch_<3, 0, 0>(r.Y, r.T[3][OLD], bd);
#define G11 batch_<3, 1, 0>(r.Y, r.T[3][MID], bd);
#define G12 batch_<3, 2, 0>(r.Y, r.T[3][OLD], bd);
#define F   wg_fence();
#define W(k) wg_wait<k>();
#define PACK pack_acc(r.Z, r.Y);
#define XW  mbar_wait(c.xfull + MID * 64, ((n - 1) >> 1) & 1);
#define ARM if (elect_one()) mbar_expect_tx(c.xfull + MID * 64, X_BYTES);
#define REL release_xbuf<RANK, OLD>(c);
#define LP(a, b) load_partner<MID, a, b>(c, r.P);
#define AS(a, b) add_stage<MID, a, b>(c, r.Z, r.P);
#define LV1 if (RANK == 0) ld3(r.V, c.aU, OLD * STAGE_BYTES + OFF_V); else ld3(r.U, c.aU, OLD * STAGE_BYTES);
#define LU1 if (RANK == 0) ld3(r.U, c.aU, OLD * STAGE_BYTES); else ld3(r.V, c.aU, OLD * STAGE_BYTES + OFF_V);
#define LU2 if (RANK == 0) ld3(r.U, c.aU, MID * STAGE_BYTES); else ld3(r.V, c.aU, MID * STAGE_BYTES + OFF_V);
#define LE  ld3(r.E, c.aE, OLD * STAGE_BYTES);
#define TRS tr_sum(r.T[0][OLD], r.U, r.V);
#define TRF tr_dif(r.T[1][OLD], r.U, r.V);
#define TRC if (RANK == 0) tr_t3(r.T[2][OLD], r.U, r.E); else tr_t0(r.T[2][OLD], r.V, r.E);
#define TRD if (RANK == 0) tr_t0(r.T[3][OLD], r.V, r.E); else tr_t3(r.T[3][OLD], r.U, r.E);
#define SLOT tma_slot<RANK, OLD>(c, n);
#define FW  mbar_wait(c.bar_full + 8 * MID, ((n + 2 + MID) >> 1) & 1);
#define SND(k) send_chunk<RANK, OLD, k>(c, r.X);
#define SCHED1 F G1 G2 XW W(2) PACK ARM LP(0,3) REL AS(0,3) LP(3,6) LV1 F G4 G5 W(3) TRS F G3 AS(3,6) W(2) TRF LE F G6 SLOT
#define SCHED1_FIRST LE SLOT
#define SCHED2 F G7 G8 FW W(1) TRC LU2 F G9 G10 W(1) SND(0) SND(1) F G11 SND(2) SND(3) W(1) TRD SND(4) SND(5) F G12

template <int RANK, int OLD, bool FIRST>
__device__ __forceinline__ void phase1(const Ctx& c, int n, Regs& r) {
  constexpr int MID = 1 - OLD;
  const uint64_t bd = get_bd(c, n);
  if (FIRST) {
    wg_fence();
    batch_<0, 1, 1>(r.X, r.T[0][MID], bd);
    batch_<1, 1, 1>(r.Y, r.T[1][MID], bd);
    if ((unsigned)c.h0 < (unsigned)IMG_H) {
      wg_fence();
      batch_<0, 0, 0>(r.X, r.T[0][OLD], bd);
      batch_<1, 0, 0>(r.Y, r.T[1][OLD], bd);
    }
    mbar_wait(c.bar_full + 8 * OLD, 0);
    LU1 LV1 W(1) TRS F G3 W(1) TRF F G6
    SCHED1_FIRST
  } else {
    SCHED1
  }
  wg_wait<0>();
  DBG_U(c, 4 + n);
}

template <int RANK, int OLD>
__device__ __forceinline__ void phase2(const Ctx& c, int n, Regs& r) {
  constexpr int MID = 1 - OLD;
  const uint64_t bd = get_bd(c, n);
#pragma unroll
  for (int i = 0; i < 48; i++) {
    if (RANK == 0) asm volatile("sub.rn.f32 %0, %0, %1;\nfma.rn.f32 %1, %1, 0f40000000, %0;" : "+f"(r.X[i]), "+f"(r.Y[i]));
    else           asm volatile("add.rn.f32 %0, %0, %1;\nfma.rn.f32 %1, %1, 0fC0000000, %0;" : "+f"(r.X[i]), "+f"(r.Y[i]));
  }
  SCHED2
}

template <int RANK, int BUF>
__device__ __forceinline__ void finish_strip(const Ctx& c, Regs& r) {
  DBG_T(c, 35);
  uint32_t P[6][4];
  mbar_wait(c.xfull + BUF * 64, ((c.nrows - 1) >> 1) & 1);
  load_partner<BUF, 0, 6>(c, P);
  wg_wait<0>();
  finish_chunks<BUF, 0, 6>(c, r.Y, P);
  asm volatile("fence.proxy.async.shared::cta;" ::: "memory");
  asm volatile("bar.sync %0, 128;" ::"r"(2 + c.wg) : "memory");
  if (c.warp == 2 && elect_one()) {
    tma_store5(c.omap, c.xbase + BUF * XBUF_BYTES, 0, c.u0, 0, RANK, c.h0 + c.nrows * c.hstep);
    asm volatile("cp.async.bulk.wait_group.read 0;" ::: "memory");
  }
  DBG_T(c, 40); DBG_G(c, 1); DBG_FLUSH(c);
}

template <int RANK>
__device__ __forceinline__ void run_strip(const Ctx& c, uint32_t row0_off, uint32_t bar_row0) {
  Regs r;
#pragma unroll
  for (int m = 0; m < 2; m++) {
    const uint32_t off = m ? STAGE_BYTES : row0_off;
    mbar_wait(m ? c.bar_full + 8 : bar_row0, 0);
    DBG_T(c, 50 + m);
    ld3(r.U, c.aU, off);
    ld3(r.V, c.aU, off + OFF_V);
    ld3(r.E, c.aE, off);
    tr_sum(r.T[0][m], r.U, r.V);
    tr_dif(r.T[1][m], r.U, r.V);
    tr_t3(r.T[RANK == 0 ? 2 : 3][m], r.U, r.E);
    tr_t0(r.T[RANK == 0 ? 3 : 2][m], r.V, r.E);
  }
  asm volatile("bar.sync %0, 128;" ::"r"(2 + c.wg) : "memory");
  asm volatile("barrier.cluster.wait.aligned;" ::: "memory");
  if (elect_one()) {
    if (c.warp < 2) {
      mbar_expect_tx(c.bar_full + 8, BOX_BYTES);
      tma_load5(c.in_base + STAGE_BYTES + c.warp * OFF_BOXB, c.map, c.bar_full + 8, c.c0, 2 * c.warp, c.u0 - c.warp, 0, c.h0 + 3 * c.hstep);
    } else if (c.warp == 2) {
      asm volatile("mbarrier.arrive.shared::cluster.b64 _, [%0];" ::"r"((bar_row0 + (BAR_READY - BAR_ROW0) * 8) ^ 0x01000000u) : "memory");
    } else {
      mbar_arrive(c.bar_full + 8);
    }
  }
  __syncwarp();
  DBG_T(c, 46);
  mbar_wait(SMEM_BASE + (RANK << 24) + OFF_BAR + 8 * BAR_W + 24, 0);
  DBG_T(c, 3);
#pragma unroll
  for (int i = 0; i < 48; i++) { r.X[i] = 0.f; r.Y[i] = 0.f; r.Z[i % 6][i / 12] = 0; r.P[i % 6][i / 12] = 0; }
  phase1<RANK, 0, true>(c, 0, r);
  mbar_wait(bar_row0 + (BAR_READY - BAR_ROW0) * 8, 0);
#pragma unroll 1
  for (int n = 0;; n += 2) {
    phase2<RANK, 0>(c, n, r);
    if (n + 1 == c.nrows) { finish_strip<RANK, 0>(c, r); break; }
    phase1<RANK, 1, false>(c, n + 1, r);
    phase2<RANK, 1>(c, n + 1, r);
    if (n + 2 == c.nrows) { finish_strip<RANK, 1>(c, r); break; }
    phase1<RANK, 0, false>(c, n + 2, r);
  }
}

struct Strip { int seg, h0, hstep, nrows; };
__device__ __forceinline__ Strip get_strip(int cl, int wg) {
  int seg, par, r0, nrows; bool down;
  if (NCL == 64) {
    const int sid = cl * 2 + wg;
    seg = sid & 3; par = (sid >> 2) & 1; r0 = (sid >> 3) * 16; nrows = 16; down = !((sid >> 3) & 1);
  } else if (cl >= 64) {
    seg = (cl - 64) * 2 + wg; par = 1; r0 = 0; nrows = 16; down = true;
  } else {
    const int i = cl >> 2;
    seg = cl & 3; par = wg; down = !(i & 1);
    r0 = wg ? 16 + 15 * (down ? i + 1 : i - 1) : 16 * i;
    nrows = 16 - wg;
  }
  return Strip{seg, 2 * (down ? r0 - 1 : r0 + nrows) + par, down ? 2 : -2, nrows};
}

__global__ void __cluster_dims__(2, 1, 1) __launch_bounds__(256, 1)
dilated_conv_wino_kernel(const __grid_constant__ CUtensorMap xmap, const __grid_constant__ CUtensorMap omap,
                         const __nv_bfloat16* __restrict__ x, const __nv_bfloat16* __restrict__ w) {
  extern __shared__ uint8_t smem_raw[];
  const int tid = threadIdx.x;
  const int wg = __shfl_sync(0xffffffff, tid >> 7, 0);
  const int warp = __shfl_sync(0xffffffff, (tid >> 5) & 3, 0);
  const int lane = tid & 31;
  const int rank = blockIdx.x & 1;
  const uint32_t sbase = SMEM_BASE + (rank << 24);
  if ((uint32_t)__cvta_generic_to_shared(smem_raw) != sbase || mapa(sbase, rank ^ 1) != (sbase ^ 0x01000000u)) __trap();
  const int cl = blockIdx.x >> 1;
  const Strip sp = get_strip(cl, wg);
  const bool down = sp.hstep > 0;

  Ctx c;
  c.map = &xmap;
  c.wg = wg;
  c.warp = warp;
  c.in_base = sbase + OFF_IN + wg * WG_IN_BYTES;
  c.bar_full = sbase + OFF_BAR + 8 * (BAR_FULL + wg * NSTAGE);
  c.c0 = rank * 48;
  c.u0 = sp.seg * 16;
  c.h0 = sp.h0;
  c.hstep = sp.hstep;
  c.nrows = sp.nrows;
  c.producer = (tid & 127) == 0;
  c.xfull = sbase + OFF_BAR + 8 * (BAR_XFULL + wg * 4 + warp);
  c.xseg = reinterpret_cast<const char*>(x) + (sp.seg * 128 + rank * 64) * (CH * 2);

  DBG_G(c, 0); DBG_T(c, 0);
  const uint32_t bar_w = sbase + OFF_BAR + 8 * BAR_W;
  const uint32_t o_w0 = (rank ? 2 : 3) * 9 * BT_BYTES, o_w2 = (rank ? 3 : 2) * 9 * BT_BYTES;
  if (elect_one()) {
    const uint32_t b0 = sbase + OFF_BAR;
    const int w8 = wg * 4 + warp;
    if (w8 >= 5) {
      const int a = w8 - 5, i = down ? a : 2 - a;
      const __nv_bfloat16* src = w + ((size_t)(i * 3) * CH + rank * 48) * CH;
      const uint32_t dst = sbase + OFF_W + a * 3 * BT_BYTES;
      mbar_init(bar_w + 8 * a, 1);
      asm volatile("fence.proxy.async.shared::cta;" ::: "memory");
      mbar_expect_tx(bar_w + 8 * a, 9 * BT_BYTES);
      bulk_load(dst + o_w0, src, 3 * BT_BYTES, bar_w + 8 * a);
      bulk_load(dst, src + CH * CH, 3 * BT_BYTES, bar_w + 8 * a);
      bulk_load(dst + o_w2, src + 2 * CH * CH, 3 * BT_BYTES, bar_w + 8 * a);
      DBG_TA(53 + a);
    } else {
      if (w8 < 4) {
        mbar_init(b0 + 8 * w8, 3);
#pragma unroll
        for (int q = 0; q < 4; q++) mbar_init(b0 + 8 * (BAR_XFULL + 4 * w8 + q), 1);
        mbar_expect_tx(b0 + 8 * w8, 2 * BOX_BYTES);
        asm volatile("mbarrier.arrive.shared::cta.b64 _, [%0], 2;" ::"r"(b0 + 8 * w8) : "memory");
      } else {
        asm volatile("prefetch.tensormap [%0];" ::"l"(&xmap) : "memory");
#pragma unroll
        for (int q = 0; q < 2; q++) {
          mbar_init(b0 + 8 * (BAR_ROW0 + q), 1);
          mbar_init(b0 + 8 * (BAR_READY + q), 1);
          mbar_expect_tx(b0 + 8 * (BAR_ROW0 + q), 2 * BOX_BYTES);
        }
        mbar_init(bar_w + 24, 6);
      }
      asm volatile("fence.mbarrier_init.release.cluster;" ::: "memory");
      asm volatile("fence.proxy.async.shared::cta;" ::: "memory");
    }
  }
  DBG_T(c, 45);
  __syncthreads();
  asm volatile("barrier.cluster.arrive.relaxed.aligned;" ::: "memory");
  DBG_T(c, 41);
  const uint32_t row0 = sbase + (wg ? OFF_ROW0_1 : OFF_ROW0_0);
  const uint32_t bar_row0 = sbase + OFF_BAR + 8 * (BAR_ROW0 + wg);
  if (warp == 3) {
    if (elect_one()) {
      const Strip so = get_strip(cl, wg ^ 1);
#pragma unroll 1
      for (int k = 0; k < 6; k++) {
        const int code = ((cl < 64 ? RORD : RORDS) >> (4 * k)) & 15, g = code >> 2, m = code & 3;
        const uint32_t dst = m == 0 ? sbase + (g ? OFF_ROW0_1 : OFF_ROW0_0) : sbase + OFF_IN + g * WG_IN_BYTES + (m & 1) * STAGE_BYTES;
        const uint32_t bar = sbase + OFF_BAR + 8 * (m == 0 ? BAR_ROW0 + g : BAR_FULL + 2 * g + (m & 1));
        tma_load5(dst + wg * OFF_BOXB, &xmap, bar, c.c0, 2 * wg, (g == wg ? sp.seg : so.seg) * 16 - wg, 0, (g == wg ? sp.h0 : so.h0) + m * c.hstep);
      }
      asm volatile("prefetch.tensormap [%0];" ::"l"(&omap) : "memory");
      DBG_TA(49);
    }
    __syncwarp();
  } else {
#pragma unroll 1
    for (int age = 0; age < 3; age++) {
      const uint32_t base = sbase + OFF_W + (age * 6 + wg * 3 + warp) * 1536;
      mbar_wait(bar_w + 8 * age, 0);
      DBG_T(c, 42 + age);
      uint32_t wa[3][4], wb[3][4], wd[3][4];
      const uint32_t src = base + (lane >> 2) * 192 + (lane & 3) * 16;
#pragma unroll
      for (int m = 0; m < 3; m++) {
        lds4(wa[m], src + o_w0 + m * 64);
        lds4(wb[m], src + m * 64);
        lds4(wd[m], src + o_w2 + m * 64);
      }
      __syncwarp();
      const uint32_t dst = base + lane * 16;
#pragma unroll
      for (int m = 0; m < 3; m++) {
        uint32_t g1[4], g2[4];
        stsm4(dst + m * 512 + o_w0, wa[m][0], wa[m][1], wa[m][2], wa[m][3]);
        stsm4(dst + m * 512 + o_w2, wd[m][0], wd[m][1], wd[m][2], wd[m][3]);
#pragma unroll
        for (int ss = 0; ss < 4; ss++) {
          const uint32_t a = wa[m][ss], b = wb[m][ss], d = wd[m][ss];
          const float slo = __uint_as_float(a << 16) + __uint_as_float(d << 16);
          const float shi = __uint_as_float(a & 0xffff0000u) + __uint_as_float(d & 0xffff0000u);
          const float blo = 0.5f * __uint_as_float(b << 16), bhi = 0.5f * __uint_as_float(b & 0xffff0000u);
          g1[ss] = pack2(fmaf(slo, 0.5f, blo), fmaf(shi, 0.5f, bhi));
          g2[ss] = pack2(fmaf(slo, 0.5f, -blo), fmaf(shi, 0.5f, -bhi));
        }
        stsm4(dst + m * 512, g1[0], g1[1], g1[2], g1[3]);
        stsm4(dst + m * 512 + 9 * BT_BYTES, g2[0], g2[1], g2[2], g2[3]);
      }
    }
    asm volatile("fence.proxy.async.shared::cta;" ::: "memory");
    __syncwarp();
    if (elect_one()) mbar_arrive(bar_w + 24);
  }
  if (elect_one()) { mbar_expect_tx(c.xfull, X_BYTES); mbar_expect_tx(c.xfull + 64, X_BYTES); }
  DBG_T(c, 1);

  {
    const int g = lane & 7, mi = lane >> 3;
    const int rU = 8 * warp + g + ((mi & 1) ? 34 : 0);
    const int rE = 8 * warp + g + ((mi & 1) ? 2 : 70 + 34);
    const uint32_t pU = c.in_base + rU * 128, pE = c.in_base + rE * 128;
    c.aU = pU + (((mi >> 1) ^ ((pU >> 7) & 7)) << 4);
    c.aE = pE + (((mi >> 1) ^ ((pE >> 7) & 7)) << 4);
  }
  c.xbase = sbase + OFF_X + wg * 2 * XBUF_BYTES;
  c.xaddr = c.xbase + (warp * 8 + (lane >> 2)) * 192 + (lane & 3) * 16;
  c.omap = &omap;
  if (rank == 0) run_strip<0>(c, row0 - c.in_base, bar_row0); else run_strip<1>(c, row0 - c.in_base, bar_row0);
}

typedef CUresult (*EncodeTiledFn)(CUtensorMap*, CUtensorMapDataType, cuuint32_t, void*, const cuuint64_t*, const cuuint64_t*,
                                  const cuuint32_t*, const cuuint32_t*, CUtensorMapInterleave, CUtensorMapSwizzle,
                                  CUtensorMapL2promotion, CUtensorMapFloatOOBfill);

}

extern "C" void kernel_launch(void* const* d_in, const int* in_sizes, int n_in, void* d_out, int out_size) {
  (void)in_sizes; (void)n_in; (void)out_size;
  static EncodeTiledFn encode = nullptr;
  if (!encode) {
    void* fn = nullptr;
    cudaDriverEntryPointQueryResult qr;
    cudaGetDriverEntryPoint("cuTensorMapEncodeTiled", &fn, cudaEnableDefault, &qr);
    encode = (EncodeTiledFn)fn;
    cudaFuncSetAttribute(dilated_conv_wino_kernel, cudaFuncAttributeMaxDynamicSharedMemorySize, SMEM_BYTES);
  }
  CUtensorMap xmap;
  const cuuint64_t dims[5] = {CH, 4, IMG_W / 8, 2, IMG_H};
  const cuuint64_t strides[4] = {CH * 2, 8 * CH * 2, 4 * CH * 2, IMG_W * CH * 2};
  const cuuint32_t box[5] = {48, 2, 17, 2, 1};
  const cuuint32_t estr[5] = {1, 1, 1, 1, 1};
#define PROMO CU_TENSOR_MAP_L2_PROMOTION_L2_128B
  encode(&xmap, CU_TENSOR_MAP_DATA_TYPE_BFLOAT16, 5, d_in[0], dims, strides, box, estr, CU_TENSOR_MAP_INTERLEAVE_NONE,
         CU_TENSOR_MAP_SWIZZLE_128B, PROMO, CU_TENSOR_MAP_FLOAT_OOB_FILL_NONE);
  CUtensorMap omap;
  const cuuint64_t odims[5] = {2 * CH, IMG_W / 8, 2, 2, IMG_H};
  const cuuint64_t ostrides[4] = {8 * CH * 2, 4 * CH * 2, 2 * CH * 2, IMG_W * CH * 2};
  const cuuint32_t obox[5] = {2 * CH, 16, 2, 1, 1};
  encode(&omap, CU_TENSOR_MAP_DATA_TYPE_BFLOAT16, 5, d_out, odims, ostrides, obox, estr, CU_TENSOR_MAP_INTERLEAVE_NONE,
         CU_TENSOR_MAP_SWIZZLE_NONE, CU_TENSOR_MAP_L2_PROMOTION_NONE, CU_TENSOR_MAP_FLOAT_OOB_FILL_NONE);
  dilated_conv_wino_kernel<<<2 * NCL, 256, SMEM_BYTES>>>(xmap, omap, (const __nv_bfloat16*)d_in[0], (const __nv_bfloat16*)d_in[1]);
}
```

```cpp
#include <cuda_runtime.h>
#include <cuda_bf16.h>
#include <cuda.h>
#include <stdint.h>

namespace {

constexpr int IMG_H = 512, IMG_W = 512, CH = 96;
constexpr int NSTAGE = 2;

constexpr int BT_BYTES   = 3072;
constexpr int W_BYTES    = 36 * BT_BYTES;
constexpr int BOX_BYTES  = 68 * 96;
constexpr int OFF_BOXB   = 70 * 128;
constexpr int STAGE_BYTES = 144 * 128;
constexpr int OFF_V      = 72 * 128;
constexpr int WG_IN_BYTES = STAGE_BYTES + 138 * 128;
constexpr int OFF_W      = 0;
constexpr int OFF_IN     = OFF_W + W_BYTES;
constexpr int OFF_X      = OFF_IN + 2 * WG_IN_BYTES;
constexpr int X_BYTES    = 3072;
constexpr int XBUF_BYTES = 4 * X_BYTES;
constexpr int X_TX = X_BYTES;
constexpr int SMEM_BYTES = OFF_X + 4 * XBUF_BYTES;
constexpr int OFF_ROW0_0 = OFF_X + ((OFF_IN - OFF_X) & 1023);
constexpr int OFF_ROW0_1 = OFF_X + 2 * XBUF_BYTES + ((OFF_IN + WG_IN_BYTES - OFF_X) & 1023);
constexpr int OFF_BAR    = OFF_IN + 68 * 128;
constexpr int BAR_FULL = 0, BAR_XFULL = 8, BAR_W = 24, BAR_ROW0 = 28, BAR_READY = 30;
constexpr int OFF_DBG    = OFF_IN + 138 * 128;
static_assert(SMEM_BYTES <= 232448, "shared memory");
constexpr uint32_t SMEM_BASE = 1024;
constexpr uint64_t BDESC = (uint64_t)((SMEM_BASE + OFF_W) >> 4) | ((uint64_t)(1536 >> 4) << 16) | ((uint64_t)(128 >> 4) << 32);

__device__ __forceinline__ void wg_fence()  { asm volatile("wgmma.fence.sync.aligned;" ::: "memory"); }
__device__ __forceinline__ void wg_commit() { asm volatile("wgmma.commit_group.sync.aligned;" ::: "memory"); }
template <int N> __device__ __forceinline__ void wg_wait() { asm volatile("wgmma.wait_group.sync.aligned %0;" ::"n"(N) : "memory"); }

template <int SCALE_D>
__device__ __forceinline__ void wgmma96(float (&d)[48], const uint32_t (&a)[4], uint64_t DESC) {
  asm volatile(
      "{\n.reg .pred p;\nsetp.ne.b32 p, %53, 0;\n"
      "wgmma.mma_async.sync.aligned.m64n96k16.f32.bf16.bf16 "
      "{%0,%1,%2,%3,%4,%5,%6,%7,%8,%9,%10,%11,%12,%13,%14,%15,%16,%17,%18,%19,%20,%21,%22,%23,"
      "%24,%25,%26,%27,%28,%29,%30,%31,%32,%33,%34,%35,%36,%37,%38,%39,%40,%41,%42,%43,%44,%45,%46,%47}, "
      "{%48,%49,%50,%51}, %52, p, 1, 1, 1;\n}\n"
      : "+f"(d[0]), "+f"(d[1]), "+f"(d[2]), "+f"(d[3]), "+f"(d[4]), "+f"(d[5]), "+f"(d[6]), "+f"(d[7]),
        "+f"(d[8]), "+f"(d[9]), "+f"(d[10]), "+f"(d[11]), "+f"(d[12]), "+f"(d[13]), "+f"(d[14]), "+f"(d[15]),
        "+f"(d[16]), "+f"(d[17]), "+f"(d[18]), "+f"(d[19]), "+f"(d[20]), "+f"(d[21]), "+f"(d[22]), "+f"(d[23]),
        "+f"(d[24]), "+f"(d[25]), "+f"(d[26]), "+f"(d[27]), "+f"(d[28]), "+f"(d[29]), "+f"(d[30]), "+f"(d[31]),
        "+f"(d[32]), "+f"(d[33]), "+f"(d[34]), "+f"(d[35]), "+f"(d[36]), "+f"(d[37]), "+f"(d[38]), "+f"(d[39]),
        "+f"(d[40]), "+f"(d[41]), "+f"(d[42]), "+f"(d[43]), "+f"(d[44]), "+f"(d[45]), "+f"(d[46]), "+f"(d[47])
      : "r"(a[0]), "r"(a[1]), "r"(a[2]), "r"(a[3]), "l"(DESC), "n"(SCALE_D));
}

__device__ __forceinline__ void ldsm4(uint32_t (&r)[4], uint32_t addr) {
  asm volatile("ldmatrix.sync.aligned.m8n8.x4.shared.b16 {%0,%1,%2,%3}, [%4];"
               : "=r"(r[0]), "=r"(r[1]), "=r"(r[2]), "=r"(r[3]) : "r"(addr) : "memory");
}
__device__ __forceinline__ uint32_t badd(uint32_t a, uint32_t b) {
  uint32_t d; asm volatile("add.rn.bf16x2 %0, %1, %2;" : "=r"(d) : "r"(a), "r"(b)); return d;
}
__device__ __forceinline__ uint32_t bsub(uint32_t a, uint32_t b) {
  uint32_t d; asm volatile("sub.rn.bf16x2 %0, %1, %2;" : "=r"(d) : "r"(a), "r"(b)); return d;
}
__device__ __forceinline__ uint32_t pack2(float lo, float hi) {
  uint32_t d; asm volatile("cvt.rn.bf16x2.f32 %0, %1, %2;" : "=r"(d) : "f"(hi), "f"(lo)); return d;
}

__device__ __forceinline__ void mbar_wait(uint32_t bar, uint32_t parity) {
  asm volatile(
      "{\n.reg .pred p;\n.reg .u32 it;\n"
      "mbarrier.try_wait.parity.shared::cta.b64 p, [%0], %1;\n"
      "@p bra WAIT_DONE;\n"
      "mov.u32 it, 0;\n"
      "WAIT_LOOP:\n"
      ".pragma \"nounroll\";\n"
      "mbarrier.try_wait.parity.shared::cta.b64 p, [%0], %1;\n"
      "@p bra WAIT_DONE;\n"
      "add.u32 it, it, 1;\n"
      "setp.lt.u32 p, it, 4194304;\n"
      "@p bra WAIT_LOOP;\n"
      "trap;\n"
      "WAIT_DONE:\n}\n" ::"r"(bar), "r"(parity) : "memory");
}
__device__ __forceinline__ bool mbar_try(uint32_t bar, uint32_t parity) {
  uint32_t ok;
  asm volatile("{\n.reg .pred p;\nmbarrier.test_wait.parity.shared::cta.b64 p, [%1], %2;\nselp.u32 %0, 1, 0, p;\n}\n"
               : "=r"(ok) : "r"(bar), "r"(parity) : "memory");
  return ok;
}
__device__ __forceinline__ void mbar_init(uint32_t bar, uint32_t count) {
  asm volatile("mbarrier.init.shared::cta.b64 [%0], %1;" ::"r"(bar), "r"(count) : "memory");
}
__device__ __forceinline__ void mbar_arrive(uint32_t bar) {
  asm volatile("mbarrier.arrive.shared::cta.b64 _, [%0];" ::"r"(bar) : "memory");
}
__device__ __forceinline__ void mbar_expect_tx(uint32_t bar, uint32_t bytes) {
  asm volatile("mbarrier.arrive.expect_tx.shared::cta.b64 _, [%0], %1;" ::"r"(bar), "r"(bytes) : "memory");
}
__device__ __forceinline__ void tma_load5(uint32_t dst, const CUtensorMap* map, uint32_t bar, int c0, int c1, int c2, int c3, int c4) {
  asm volatile("cp.async.bulk.tensor.5d.shared::cluster.global.mbarrier::complete_tx::bytes [%0], [%1, {%3,%4,%5,%6,%7}], [%2];"
               ::"r"(dst), "l"(map), "r"(bar), "r"(c0), "r"(c1), "r"(c2), "r"(c3), "r"(c4) : "memory");
}
__device__ __forceinline__ void bulk_load(uint32_t dst, const void* src, uint32_t bytes, uint32_t bar) {
  asm volatile("cp.async.bulk.shared::cluster.global.mbarrier::complete_tx::bytes [%0], [%1], %2, [%3];"
               ::"r"(dst), "l"(src), "r"(bytes), "r"(bar) : "memory");
}
template <int OFF>
__device__ __forceinline__ void st_async4(uint32_t cluster_addr, uint32_t cluster_bar, uint32_t a, uint32_t b, uint32_t c, uint32_t d) {
  asm volatile("st.async.shared::cluster.mbarrier::complete_tx::bytes.v4.b32 [%0+%6], {%2,%3,%4,%5}, [%1];"
               ::"r"(cluster_addr), "r"(cluster_bar), "r"(a), "r"(b), "r"(c), "r"(d), "n"(OFF) : "memory");
}
__device__ __forceinline__ void stsm4(uint32_t addr, uint32_t a, uint32_t b, uint32_t c, uint32_t d) {
  asm volatile("stmatrix.sync.aligned.m8n8.x4.shared.b16 [%0], {%1,%2,%3,%4};" ::"r"(addr), "r"(a), "r"(b), "r"(c), "r"(d) : "memory");
}
__device__ __forceinline__ uint32_t bfma(uint32_t a, uint32_t b, uint32_t c) {
  uint32_t d; asm volatile("fma.rn.bf16x2 %0, %1, %2, %3;" : "=r"(d) : "r"(a), "r"(b), "r"(c)); return d;
}
__device__ __forceinline__ void lds4(uint32_t (&r)[4], uint32_t addr) {
  asm volatile("ld.shared.v4.b32 {%0,%1,%2,%3}, [%4];" : "=r"(r[0]), "=r"(r[1]), "=r"(r[2]), "=r"(r[3]) : "r"(addr) : "memory");
}
__device__ __forceinline__ void sts4(uint32_t addr, const uint32_t (&r)[4]) {
  asm volatile("st.shared.v4.b32 [%0], {%1,%2,%3,%4};" ::"r"(addr), "r"(r[0]), "r"(r[1]), "r"(r[2]), "r"(r[3]) : "memory");
}
__device__ __forceinline__ void tma_store5(const CUtensorMap* map, uint32_t src, int c0, int c1, int c2, int c3, int c4) {
  asm volatile("cp.async.bulk.tensor.5d.global.shared::cta.bulk_group [%0, {%2,%3,%4,%5,%6}], [%1];"
               ::"l"(map), "r"(src), "r"(c0), "r"(c1), "r"(c2), "r"(c3), "r"(c4) : "memory");
  asm volatile("cp.async.bulk.commit_group;" ::: "memory");
}
__device__ __forceinline__ bool elect_one() {
  uint32_t p;
  asm volatile("{\n.reg .pred P;\nelect.sync _|P, 0xffffffff;\nselp.u32 %0, 1, 0, P;\n}\n" : "=r"(p));
  return p;
}
__device__ __forceinline__ uint32_t mapa(uint32_t addr, uint32_t rank) {
  uint32_t r; asm("mapa.shared::cluster.u32 %0, %1, %2;" : "=r"(r) : "r"(addr), "r"(rank)); return r;
}

__device__ __forceinline__ void tr_sum(uint32_t (&t)[3][4], const uint32_t (&U)[3][4], const uint32_t (&V)[3][4]) {
#pragma unroll
  for (int k = 0; k < 3; k++)
#pragma unroll
    for (int i = 0; i < 4; i++) t[k][i] = badd(U[k][i], V[k][i]);
}
__device__ __forceinline__ void tr_dif(uint32_t (&t)[3][4], const uint32_t (&U)[3][4], const uint32_t (&V)[3][4]) {
#pragma unroll
  for (int k = 0; k < 3; k++)
#pragma unroll
    for (int i = 0; i < 4; i++) t[k][i] = bsub(V[k][i], U[k][i]);
}
__device__ __forceinline__ void tr_t0(uint32_t (&t)[3][4], const uint32_t (&V)[3][4], const uint32_t (&E)[3][4]) {
#pragma unroll
  for (int k = 0; k < 3; k++) {
    t[k][0] = bsub(E[k][0], V[k][0]); t[k][1] = bsub(V[k][0], V[k][1]);
    t[k][2] = bsub(E[k][2], V[k][2]); t[k][3] = bsub(V[k][2], V[k][3]);
  }
}
__device__ __forceinline__ void tr_t3(uint32_t (&t)[3][4], const uint32_t (&U)[3][4], const uint32_t (&E)[3][4]) {
#pragma unroll
  for (int k = 0; k < 3; k++) {
    t[k][0] = bsub(U[k][1], U[k][0]); t[k][1] = bsub(E[k][1], U[k][1]);
    t[k][2] = bsub(U[k][3], U[k][2]); t[k][3] = bsub(E[k][3], U[k][3]);
  }
}
__device__ __forceinline__ void ld3(uint32_t (&R)[3][4], uint32_t aU, int off) {
#pragma unroll
  for (int k = 0; k < 3; k++) ldsm4(R[k], (aU ^ (32 * k)) + off);
}
template <int COMP, int AGE, int FIRST>
__device__ __forceinline__ void batch_(float (&acc)[48], const uint32_t (&t)[3][4], uint64_t bd) {
  constexpr int base = ((COMP * 3 + AGE) * 3) * BT_BYTES;
  wgmma96<FIRST ? 0 : 1>(acc, t[0], bd + ((base) >> 4));
  wgmma96<1>(acc, t[1], bd + ((base + BT_BYTES) >> 4));
  wgmma96<1>(acc, t[2], bd + ((base + 2 * BT_BYTES) >> 4));
  wg_commit();
}

#define DBG_T(c, idx)
#define DBG_TA(idx)
#define TL(c, k)
#define DBG_U(c, idx)
#define DBG_FLUSH(c)
#define DBG_G(c, idx)

struct Ctx {
  uint32_t aU, aE;
  uint32_t in_base;
  uint32_t bar_full;
  uint32_t bar_ready;
  uint32_t xaddr, xfull;
  uint32_t xbase;
  const CUtensorMap* omap;
  const CUtensorMap* map;
  const char* xseg;
  int wg, warp;
  int c0, u0, h0, hstep;
  int nrows;
  bool producer;
};

__device__ __forceinline__ void prefetch_row(const Ctx& c, int h) {
  if ((unsigned)h < (unsigned)IMG_H)
    asm volatile("cp.async.bulk.prefetch.L2.global [%0], %1;" ::"l"(c.xseg + (size_t)h * (IMG_W * CH * 2)), "r"(64 * CH * 2) : "memory");
}

template <int BUF, int C0, int C1>
__device__ __forceinline__ void load_partner(const Ctx& c, uint32_t (&P)[6][4]) {
#pragma unroll
  for (int ch = C0; ch < C1; ch++) lds4(P[ch], c.xaddr + BUF * XBUF_BYTES + (ch & 1) * 6144 + (ch >> 1) * 64);
}
template <int BUF, int C0, int C1>
__device__ __forceinline__ void finish_chunks(const Ctx& c, const float (&Y)[48], uint32_t (&P)[6][4]) {
#pragma unroll
  for (int ch = C0; ch < C1; ch++) {
    const int m = ch >> 1, s = ch & 1;
#pragma unroll
    for (int ss = 0; ss < 4; ss++) P[ch][ss] = badd(pack2(Y[16 * m + 4 * ss + 2 * s], Y[16 * m + 4 * ss + 2 * s + 1]), P[ch][ss]);
    sts4(c.xaddr + BUF * XBUF_BYTES + s * 6144 + m * 64, P[ch]);
  }
}
template <int RANK, int BUF, int CH0>
__device__ __forceinline__ void send_chunk(const Ctx& c, const float (&X)[48]) {
  constexpr uint32_t RDELTA = RANK ? 0xFF000000u : 0x01000000u;
  constexpr int m = CH0 >> 1, s = CH0 & 1;
  uint32_t o[4];
#pragma unroll
  for (int ss = 0; ss < 4; ss++) o[ss] = pack2(X[16 * m + 4 * ss + 2 * s], X[16 * m + 4 * ss + 2 * s + 1]);
  st_async4<BUF * XBUF_BYTES + s * 6144 + m * 64>(c.xaddr + RDELTA, c.xfull + BUF * 64 + RDELTA, o[0], o[1], o[2], o[3]);
}

#define SLOTV 0
#define FULLSKIP 3
#define CLROT 2
#define SPN 16
#define LATE3 1
#define PF_DIST 1
#define NCL 66
#define RORD 0x652410
#define RORDS 0x625140

struct Regs {
  float X[48], Y[48];
  uint32_t T[4][2][3][4];
  uint32_t U[3][4], V[3][4], E[3][4];
  uint32_t Z[6][4], P[6][4];
};

template <int RANK, int OLD>
__device__ __forceinline__ void tma_slot(const Ctx& c, int n) {
  constexpr int MID = 1 - OLD;
  const int h = c.h0 + n * c.hstep;
  asm volatile("fence.proxy.async.shared::cta;" ::: "memory");
  asm volatile("bar.sync %0, 128;" ::"r"(2 + c.wg) : "memory");
  if (elect_one()) {
    if (c.warp < 2) {
      if (n + 2 < c.nrows) {
        mbar_expect_tx(c.bar_full + 8 * OLD, BOX_BYTES);
        tma_load5(c.in_base + OLD * STAGE_BYTES + c.warp * OFF_BOXB, c.map, c.bar_full + 8 * OLD, c.c0, 2 * c.warp, c.u0 - c.warp, 0,
                  h + 4 * c.hstep);
      } else {
        mbar_arrive(c.bar_full + 8 * OLD);
      }
    } else if (c.warp == 2) {
      if (OLD == 1 || n > 0) tma_store5(c.omap, c.xbase + MID * XBUF_BYTES, 0, c.u0, 0, RANK, h);
    } else {
      if (PF_DIST > 0 && n + 2 + PF_DIST < c.nrows) prefetch_row(c, h + (4 + PF_DIST) * c.hstep);
    }
  }
  __syncwarp();
}
template <int RANK, int OLD>
__device__ __forceinline__ void release_xbuf(const Ctx& c) {
  constexpr uint32_t RDELTA = RANK ? 0xFF000000u : 0x01000000u;
  asm volatile("cp.async.bulk.wait_group.read 0;" ::: "memory");
  asm volatile("{\n.reg .pred p, q;\nelect.sync _|q, 0xffffffff;\nsetp.eq.and.u32 p, %1, 2, q;\n@p mbarrier.arrive.shared::cluster.b64 _, [%0];\n}\n"
               ::"r"(c.bar_full + 8 * (1 - OLD) + RDELTA), "r"(c.warp) : "memory");
}
template <int C0, int C1>
__device__ __forceinline__ void pack_acc(uint32_t (&Z)[6][4], const float (&Y)[48]) {
#pragma unroll
  for (int ch = C0; ch < C1; ch++)
#pragma unroll
    for (int ss = 0; ss < 4; ss++) {
      const int i = 16 * (ch >> 1) + 4 * ss + 2 * (ch & 1);
      Z[ch][ss] = pack2(Y[i], Y[i + 1]);
    }
}
template <int BUF, int C0, int C1>
__device__ __forceinline__ void add_stage(const Ctx& c, uint32_t (&Z)[6][4], const uint32_t (&P)[6][4]) {
#pragma unroll
  for (int ch = C0; ch < C1; ch++)
#pragma unroll
    for (int ss = 0; ss < 4; ss++) Z[ch][ss] = badd(Z[ch][ss], P[ch][ss]);
#pragma unroll
  for (int ch = C0; ch < C1; ch++) sts4(c.xaddr + BUF * XBUF_BYTES + (ch & 1) * 6144 + (ch >> 1) * 64, Z[ch]);
}

__device__ __forceinline__ uint64_t get_bd(const Ctx& c, int n) {
  return BDESC;
}
#define G1  batch_<0, 0, 1>(r.X, r.T[0][OLD], bd);
#define G2  batch_<0, 1, 0>(r.X, r.T[0][MID], bd);
#define G3  batch_<0, 2, 0>(r.X, r.T[0][OLD], bd);
#define G4  batch_<1, 0, 1>(r.Y, r.T[1][OLD], bd);
#define G5  batch_<1, 1, 0>(r.Y, r.T[1][MID], bd);
#define G6  batch_<1, 2, 0>(r.Y, r.T[1][OLD], bd);
#define G7  if (OLD == 1 || !(FULLSKIP & 1)) batch_<2, 0, 0>(r.X, r.T[2][OLD], bd); else { if (!skip) { F batch_<2, 0, 0>(r.X, r.T[2][OLD], bd); } else { F wg_commit(); } F }
#define G8  batch_<2, 1, 0>(r.X, r.T[2][MID], bd);
#define G9  batch_<2, 2, 0>(r.X, r.T[2][OLD], bd);
#define G10 if (OLD == 1 || !(FULLSKIP & 2)) batch_<3, 0, 0>(r.Y, r.T[3][OLD], bd); else { if (!skip) { F batch_<3, 0, 0>(r.Y, r.T[3][OLD], bd); } else { F wg_commit(); } F }
#define G11 batch_<3, 1, 0>(r.Y, r.T[3][MID], bd);
#define G12 batch_<3, 2, 0>(r.Y, r.T[3][OLD], bd);
#define F   wg_fence();
#define W(k) wg_wait<k>();
#define PACK pack_acc<0, 6>(r.Z, r.Y);
#define PK(a, b) pack_acc<a, b>(r.Z, r.Y);
#define XW  mbar_wait(c.xfull + MID * 64, ((n - 1) >> 1) & 1); FIX3
#define ARM if (elect_one()) mbar_expect_tx(c.xfull + MID * 64, X_TX);
#define REL release_xbuf<RANK, OLD>(c);
#define LP(a, b) load_partner<MID, a, b>(c, r.P);
#define AS(a, b) add_stage<MID, a, b>(c, r.Z, r.P);
#define LV1 if (RANK == 0) ld3(r.V, c.aU, OLD * STAGE_BYTES + OFF_V); else ld3(r.U, c.aU, OLD * STAGE_BYTES);
#define LU1 if (RANK == 0) ld3(r.U, c.aU, OLD * STAGE_BYTES); else ld3(r.V, c.aU, OLD * STAGE_BYTES + OFF_V);
#define LU2 if (RANK == 0) ld3(r.U, c.aU, MID * STAGE_BYTES); else ld3(r.V, c.aU, MID * STAGE_BYTES + OFF_V);
#define LE  ld3(r.E, c.aE, OLD * STAGE_BYTES);
#define LEk(k)  ldsm4(r.E[k], (c.aE ^ (32 * k)) + OLD * STAGE_BYTES);
#define LV1k(k) if (RANK == 0) ldsm4(r.V[k], (c.aU ^ (32 * k)) + OLD * STAGE_BYTES + OFF_V); else ldsm4(r.U[k], (c.aU ^ (32 * k)) + OLD * STAGE_BYTES);
#define LV2k(k) if (RANK == 0) ldsm4(r.V[k], (c.aU ^ (32 * k)) + MID * STAGE_BYTES + OFF_V); else ldsm4(r.U[k], (c.aU ^ (32 * k)) + MID * STAGE_BYTES);
#define LU1k(k) if (RANK == 0) ldsm4(r.U[k], (c.aU ^ (32 * k)) + OLD * STAGE_BYTES); else ldsm4(r.V[k], (c.aU ^ (32 * k)) + OLD * STAGE_BYTES + OFF_V);
#define LU2k(k) if (RANK == 0) ldsm4(r.U[k], (c.aU ^ (32 * k)) + MID * STAGE_BYTES); else ldsm4(r.V[k], (c.aU ^ (32 * k)) + MID * STAGE_BYTES + OFF_V);
#define TRS tr_sum(r.T[0][OLD], r.U, r.V);
#define TRF tr_dif(r.T[1][OLD], r.U, r.V);
#define TRC if (RANK == 0) tr_t3(r.T[2][OLD], r.U, r.E); else tr_t0(r.T[2][OLD], r.V, r.E);
#define TRD if (RANK == 0) tr_t0(r.T[3][OLD], r.V, r.E); else tr_t3(r.T[3][OLD], r.U, r.E);
#define SLOT tma_slot<RANK, OLD>(c, n);
#define FW  if (OLD == 1) mbar_wait(c.bar_full, ((n + 2) >> 1) & 1); \
            else mbar_wait(n ? c.bar_full + 8 : c.bar_ready, n ? ((n + 3) >> 1) & 1 : 0);
#define FIX3 if (OLD == 1 && n == 1) { mbar_wait(c.bar_full + 8, 1); SCHED_FIX3 }
#define SND(k) send_chunk<RANK, OLD, k>(c, r.X);
#define SCHED1 F G1 G2 XW W(2) PK(0,1) ARM LP(0,1) PK(1,2) LP(1,2) LP(2,3) REL AS(0,1) PK(2,3) PK(3,4) PK(4,5) AS(1,2) LP(3,4) PK(5,6) LP(4,5) AS(2,3) LP(5,6) LV1k(0) LV1k(1) LV1k(2) F G4 G5 W(3) TRS F G3 AS(3,4) AS(4,5) W(2) TRF LEk(0) LEk(1) LEk(2) AS(5,6) F G6 SLOT
#define SCHED1_FIRST LEk(0) LEk(1) LEk(2) SLOT
#define SCHED_FIX3 LU1k(0) LU1k(1) LU1k(2)
#define SCHED2 F G7 G8 FW W(1) TRC LU2k(0) F G9 LU2k(1) LU2k(2) F G10 W(1) SND(0) SND(1) SND(2) F G11 SND(3) W(1) TRD SND(4) SND(5) F G12

template <int RANK, int OLD, bool FIRST>
__device__ __forceinline__ void phase1(const Ctx& c, int n, Regs& r) {
  constexpr int MID = 1 - OLD;
  const uint64_t bd = get_bd(c, n);
  if (FIRST) {
    wg_fence();
    batch_<0, 1, 1>(r.X, r.T[0][MID], bd);
    batch_<1, 1, 1>(r.Y, r.T[1][MID], bd);
    if ((unsigned)c.h0 < (unsigned)IMG_H) {
      wg_fence();
      batch_<0, 0, 0>(r.X, r.T[0][OLD], bd);
      batch_<1, 0, 0>(r.Y, r.T[1][OLD], bd);
    }
    mbar_wait(c.bar_full + 8 * OLD, 0);
    LU1 LV1 W(1) TRS F G3 W(1) TRF F G6
    SCHED1_FIRST
  } else {
    SCHED1
  }
  wg_wait<0>();
  DBG_U(c, 4 + n);
}

template <int RANK, int OLD>
__device__ __forceinline__ void phase2(const Ctx& c, int n, Regs& r) {
  constexpr int MID = 1 - OLD;
  const uint64_t bd = get_bd(c, n);
#pragma unroll
  for (int i = 0; i < 48; i++) {
    if (RANK == 0) asm volatile("sub.rn.f32 %0, %0, %1;\nfma.rn.f32 %1, %1, 0f40000000, %0;" : "+f"(r.X[i]), "+f"(r.Y[i]));
    else           asm volatile("add.rn.f32 %0, %0, %1;\nfma.rn.f32 %1, %1, 0fC0000000, %0;" : "+f"(r.X[i]), "+f"(r.Y[i]));
  }
  const bool skip = (unsigned)(c.h0 + n * c.hstep) >= (unsigned)IMG_H;
  SCHED2
}

template <int RANK, int BUF>
__device__ __forceinline__ void finish_strip(const Ctx& c, Regs& r) {
  DBG_T(c, 35);
  uint32_t P[6][4];
  mbar_wait(c.xfull + BUF * 64, ((c.nrows - 1) >> 1) & 1);
  load_partner<BUF, 0, 6>(c, P);
  wg_wait<0>();
  finish_chunks<BUF, 0, 6>(c, r.Y, P);
  asm volatile("fence.proxy.async.shared::cta;" ::: "memory");
  asm volatile("bar.sync %0, 128;" ::"r"(2 + c.wg) : "memory");
  if (c.warp == 2 && elect_one()) {
    tma_store5(c.omap, c.xbase + BUF * XBUF_BYTES, 0, c.u0, 0, RANK, c.h0 + c.nrows * c.hstep);
    asm volatile("cp.async.bulk.wait_group.read 0;" ::: "memory");
  }
  DBG_T(c, 40); DBG_G(c, 1);
  DBG_FLUSH(c);
}

template <int RANK>
__device__ __forceinline__ void run_strip(const Ctx& c, uint32_t row0_off, uint32_t bar_row0) {
  Regs r;
#pragma unroll
  for (int m = 0; m < 2; m++) {
    const uint32_t off = m ? STAGE_BYTES : row0_off;
    mbar_wait(m ? c.bar_full + 8 : bar_row0, 0);
    DBG_T(c, 50 + m);
    ld3(r.U, c.aU, off);
    ld3(r.V, c.aU, off + OFF_V);
    ld3(r.E, c.aE, off);
    tr_sum(r.T[0][m], r.U, r.V);
    tr_dif(r.T[1][m], r.U, r.V);
    tr_t3(r.T[RANK == 0 ? 2 : 3][m], r.U, r.E);
    tr_t0(r.T[RANK == 0 ? 3 : 2][m], r.V, r.E);
  }
  asm volatile("bar.sync %0, 128;" ::"r"(2 + c.wg) : "memory");
  asm volatile("barrier.cluster.wait.aligned;" ::: "memory");
  if (elect_one()) {
    if (c.warp < 2) {
      mbar_expect_tx(c.bar_full + 8, BOX_BYTES);
      tma_load5(c.in_base + STAGE_BYTES + c.warp * OFF_BOXB, c.map, c.bar_full + 8, c.c0, 2 * c.warp, c.u0 - c.warp, 0, c.h0 + 3 * c.hstep);
    } else if (c.warp == 2) {
      asm volatile("mbarrier.arrive.shared::cluster.b64 _, [%0];" ::"r"((bar_row0 + (BAR_READY - BAR_ROW0) * 8) ^ 0x01000000u) : "memory");
    } else {
      mbar_arrive(c.bar_full + 8);
    }
  }
  __syncwarp();
  DBG_T(c, 46);
  mbar_wait(SMEM_BASE + (RANK << 24) + OFF_BAR + 8 * BAR_W + 24, 0);
  DBG_T(c, 3);
#pragma unroll
  for (int i = 0; i < 48; i++) { r.X[i] = 0.f; r.Y[i] = 0.f; r.Z[i % 6][i / 12] = 0; r.P[i % 6][i / 12] = 0; }
  phase1<RANK, 0, true>(c, 0, r);
  if (!LATE3) mbar_wait(c.bar_ready, 0);
#pragma unroll 1
  for (int n = 0;; n += 2) {
    phase2<RANK, 0>(c, n, r);
    if (n + 1 == c.nrows) { finish_strip<RANK, 0>(c, r); break; }
    phase1<RANK, 1, false>(c, n + 1, r);
    phase2<RANK, 1>(c, n + 1, r);
    if (n + 2 == c.nrows) { finish_strip<RANK, 1>(c, r); break; }
    phase1<RANK, 0, false>(c, n + 2, r);
  }
}

struct Strip { int seg, h0, hstep, nrows; };
__device__ __forceinline__ Strip get_strip(int cl, int wg) {
  int seg, par, r0, nrows; bool down;
  if (NCL == 64) {
    const int sid = cl * 2 + wg;
    seg = sid & 3; par = (sid >> 2) & 1; r0 = (sid >> 3) * 16; nrows = 16; down = !((sid >> 3) & 1);
  } else if (cl >= 64) {
    seg = (cl - 64) * 2 + wg; par = 1; r0 = 0; nrows = SPN; down = true;
  } else {
    const int i = cl >> 2;
    seg = cl & 3; par = wg; down = !(i & 1);
    r0 = wg ? 16 + 15 * (down ? i + 1 : i - 1) : 16 * i;
    nrows = 16 - wg;
  }
  return Strip{seg, 2 * (down ? r0 - 1 : r0 + nrows) + par, down ? 2 : -2, nrows};
}

__global__ void __cluster_dims__(2, 1, 1) __launch_bounds__(256, 1)
dilated_conv_wino_kernel(const __grid_constant__ CUtensorMap xmap, const __grid_constant__ CUtensorMap omap,
                         const __nv_bfloat16* __restrict__ x, const __nv_bfloat16* __restrict__ w) {
  extern __shared__ uint8_t smem_raw[];
  const int tid = threadIdx.x;
  const int wg = __shfl_sync(0xffffffff, tid >> 7, 0);
  const int warp = __shfl_sync(0xffffffff, (tid >> 5) & 3, 0);
  const int lane = tid & 31;
  const int rank = blockIdx.x & 1;
  const uint32_t sbase = SMEM_BASE + (rank << 24);
  if ((uint32_t)__cvta_generic_to_shared(smem_raw) != sbase || mapa(sbase, rank ^ 1) != (sbase ^ 0x01000000u)) __trap();
  const int cl = CLROT ? ((blockIdx.x >> 1) + NCL - CLROT) % NCL : blockIdx.x >> 1;
  const Strip sp = get_strip(cl, wg);
  const bool down = sp.hstep > 0;

  Ctx c;
  c.map = &xmap;
  c.wg = wg;
  c.warp = warp;
  c.in_base = sbase + OFF_IN + wg * WG_IN_BYTES;
  c.bar_full = sbase + OFF_BAR + 8 * (BAR_FULL + wg * NSTAGE);
  c.bar_ready = sbase + OFF_BAR + 8 * (BAR_READY + wg);
  c.c0 = rank * 48;
  c.u0 = sp.seg * 16;
  c.h0 = sp.h0;
  c.hstep = sp.hstep;
  c.nrows = sp.nrows;
  c.producer = (tid & 127) == 0;
  c.xfull = sbase + OFF_BAR + 8 * (BAR_XFULL + wg * 4 + warp);
  c.xseg = reinterpret_cast<const char*>(x) + (sp.seg * 128 + rank * 64) * (CH * 2);

  DBG_G(c, 0); DBG_T(c, 0);
  const uint32_t bar_w = sbase + OFF_BAR + 8 * BAR_W;
  const uint32_t o_w0 = (rank ? 2 : 3) * 9 * BT_BYTES, o_w2 = (rank ? 3 : 2) * 9 * BT_BYTES;
  if (elect_one()) {
    const uint32_t b0 = sbase + OFF_BAR;
    const int w8 = wg * 4 + warp;
    if (w8 >= 5) {
      const int a = w8 - 5, i = down ? a : 2 - a;
      const __nv_bfloat16* src = w + ((size_t)(i * 3) * CH + rank * 48) * CH;
      const uint32_t dst = sbase + OFF_W + a * 3 * BT_BYTES;
      mbar_init(bar_w + 8 * a, 1);
      asm volatile("fence.proxy.async.shared::cta;" ::: "memory");
      mbar_expect_tx(bar_w + 8 * a, 9 * BT_BYTES);
      bulk_load(dst + o_w0, src, 3 * BT_BYTES, bar_w + 8 * a);
      bulk_load(dst, src + CH * CH, 3 * BT_BYTES, bar_w + 8 * a);
      bulk_load(dst + o_w2, src + 2 * CH * CH, 3 * BT_BYTES, bar_w + 8 * a);
      DBG_TA(53 + a);
    } else {
      if (w8 < 4) {
        mbar_init(b0 + 8 * w8, 3);
#pragma unroll
        for (int q = 0; q < 4; q++) mbar_init(b0 + 8 * (BAR_XFULL + 4 * w8 + q), 1);
        mbar_expect_tx(b0 + 8 * w8, 2 * BOX_BYTES);
        asm volatile("mbarrier.arrive.shared::cta.b64 _, [%0], 2;" ::"r"(b0 + 8 * w8) : "memory");
      } else {
        asm volatile("prefetch.tensormap [%0];" ::"l"(&xmap) : "memory");
#pragma unroll
        for (int q = 0; q < 2; q++) {
          mbar_init(b0 + 8 * (BAR_ROW0 + q), 1);
          mbar_init(b0 + 8 * (BAR_READY + q), 1);
          mbar_expect_tx(b0 + 8 * (BAR_ROW0 + q), 2 * BOX_BYTES);
        }
        mbar_init(bar_w + 24, 6);
      }
      asm volatile("fence.mbarrier_init.release.cluster;" ::: "memory");
      asm volatile("fence.proxy.async.shared::cta;" ::: "memory");
    }
  }
  DBG_T(c, 45);
  __syncthreads();
  asm volatile("barrier.cluster.arrive.relaxed.aligned;" ::: "memory");
  DBG_T(c, 41);
  const uint32_t row0 = sbase + (wg ? OFF_ROW0_1 : OFF_ROW0_0);
  const uint32_t bar_row0 = sbase + OFF_BAR + 8 * (BAR_ROW0 + wg);
  if (warp == 3) {
    if (elect_one()) {
      const Strip so = get_strip(cl, wg ^ 1);
#pragma unroll 1
      for (int k = 0; k < 6; k++) {
        const int code = ((cl < 64 ? RORD : RORDS) >> (4 * k)) & 15, g = code >> 2, m = code & 3;
        const uint32_t dst = m == 0 ? sbase + (g ? OFF_ROW0_1 : OFF_ROW0_0) : sbase + OFF_IN + g * WG_IN_BYTES + (m & 1) * STAGE_BYTES;
        const uint32_t bar = sbase + OFF_BAR + 8 * (m == 0 ? BAR_ROW0 + g : BAR_FULL + 2 * g + (m & 1));
        tma_load5(dst + wg * OFF_BOXB, &xmap, bar, c.c0, 2 * wg, (g == wg ? sp.seg : so.seg) * 16 - wg, 0, (g == wg ? sp.h0 : so.h0) + m * c.hstep);
      }
      asm volatile("prefetch.tensormap [%0];" ::"l"(&omap) : "memory");
      DBG_TA(49);
    }
    __syncwarp();
  } else {
#pragma unroll 1
    for (int age = 0; age < 3; age++) {
      const uint32_t base = sbase + OFF_W + (age * 6 + wg * 3 + warp) * 1536;
      mbar_wait(bar_w + 8 * age, 0);
      DBG_T(c, 42 + age);
      uint32_t wa[3][4], wb[3][4], wd[3][4];
      const uint32_t src = base + (lane >> 2) * 192 + (lane & 3) * 16;
#pragma unroll
      for (int m = 0; m < 3; m++) {
        lds4(wa[m], src + o_w0 + m * 64);
        lds4(wb[m], src + m * 64);
        lds4(wd[m], src + o_w2 + m * 64);
      }
      __syncwarp();
      const uint32_t dst = base + lane * 16;
#pragma unroll
      for (int m = 0; m < 3; m++) {
        uint32_t g1[4], g2[4];
        stsm4(dst + m * 512 + o_w0, wa[m][0], wa[m][1], wa[m][2], wa[m][3]);
        stsm4(dst + m * 512 + o_w2, wd[m][0], wd[m][1], wd[m][2], wd[m][3]);
#pragma unroll
        for (int ss = 0; ss < 4; ss++) {
          const uint32_t a = wa[m][ss], b = wb[m][ss], d = wd[m][ss];
          const uint32_t hs = bfma(badd(a, d), 0x3f003f00u, 0x80008000u);
          g1[ss] = bfma(b, 0x3f003f00u, hs);
          g2[ss] = bfma(b, 0xbf00bf00u, hs);
        }
        stsm4(dst + m * 512, g1[0], g1[1], g1[2], g1[3]);
        stsm4(dst + m * 512 + 9 * BT_BYTES, g2[0], g2[1], g2[2], g2[3]);
      }
    }
    asm volatile("fence.proxy.async.shared::cta;" ::: "memory");
    __syncwarp();
    if (elect_one()) mbar_arrive(bar_w + 24);
  }
  if (elect_one()) { mbar_expect_tx(c.xfull, X_TX); mbar_expect_tx(c.xfull + 64, X_TX); }
  DBG_T(c, 1);

  {
    const int g = lane & 7, mi = lane >> 3;
    const int rU = 8 * warp + g + ((mi & 1) ? 34 : 0);
    const int rE = 8 * warp + g + ((mi & 1) ? 2 : 70 + 34);
    const uint32_t pU = c.in_base + rU * 128, pE = c.in_base + rE * 128;
    c.aU = pU + (((mi >> 1) ^ ((pU >> 7) & 7)) << 4);
    c.aE = pE + (((mi >> 1) ^ ((pE >> 7) & 7)) << 4);
  }
  c.xbase = sbase + OFF_X + wg * 2 * XBUF_BYTES;
  c.xaddr = c.xbase + (warp * 8 + (lane >> 2)) * 192 + (lane & 3) * 16;
  c.omap = &omap;
  if (rank == 0) run_strip<0>(c, row0 - c.in_base, bar_row0); else run_strip<1>(c, row0 - c.in_base, bar_row0);
}

typedef CUresult (*EncodeTiledFn)(CUtensorMap*, CUtensorMapDataType, cuuint32_t, void*, const cuuint64_t*, const cuuint64_t*,
                                  const cuuint32_t*, const cuuint32_t*, CUtensorMapInterleave, CUtensorMapSwizzle,
                                  CUtensorMapL2promotion, CUtensorMapFloatOOBfill);

}

extern "C" void kernel_launch(void* const* d_in, const int* in_sizes, int n_in, void* d_out, int out_size) {
  (void)in_sizes; (void)n_in; (void)out_size;
  static EncodeTiledFn encode = nullptr;
  if (!encode) {
    void* fn = nullptr;
    cudaDriverEntryPointQueryResult qr;
    cudaGetDriverEntryPoint("cuTensorMapEncodeTiled", &fn, cudaEnableDefault, &qr);
    encode = (EncodeTiledFn)fn;
    cudaFuncSetAttribute(dilated_conv_wino_kernel, cudaFuncAttributeMaxDynamicSharedMemorySize, SMEM_BYTES);
  }
  CUtensorMap xmap;
  const cuuint64_t dims[5] = {CH, 4, IMG_W / 8, 2, IMG_H};
  const cuuint64_t strides[4] = {CH * 2, 8 * CH * 2, 4 * CH * 2, IMG_W * CH * 2};
  const cuuint32_t box[5] = {48, 2, 17, 2, 1};
  const cuuint32_t estr[5] = {1, 1, 1, 1, 1};
#define PROMO CU_TENSOR_MAP_L2_PROMOTION_L2_128B
  encode(&xmap, CU_TENSOR_MAP_DATA_TYPE_BFLOAT16, 5, d_in[0], dims, strides, box, estr, CU_TENSOR_MAP_INTERLEAVE_NONE,
         CU_TENSOR_MAP_SWIZZLE_128B, PROMO, CU_TENSOR_MAP_FLOAT_OOB_FILL_NONE);
  CUtensorMap omap;
  const cuuint64_t odims[5] = {2 * CH, IMG_W / 8, 2, 2, IMG_H};
  const cuuint64_t ostrides[4] = {8 * CH * 2, 4 * CH * 2, 2 * CH * 2, IMG_W * CH * 2};
  const cuuint32_t obox[5] = {2 * CH, 16, 2, 1, 1};
  encode(&omap, CU_TENSOR_MAP_DATA_TYPE_BFLOAT16, 5, d_out, odims, ostrides, obox, estr, CU_TENSOR_MAP_INTERLEAVE_NONE,
         CU_TENSOR_MAP_SWIZZLE_NONE, CU_TENSOR_MAP_L2_PROMOTION_NONE, CU_TENSOR_MAP_FLOAT_OOB_FILL_NONE);
  dilated_conv_wino_kernel<<<2 * NCL, 256, SMEM_BYTES>>>(xmap, omap, (const __nv_bfloat16*)d_in[0], (const __nv_bfloat16*)d_in[1]);
}
```

```cpp
#include <cuda_runtime.h>
#include <cuda_bf16.h>
#include <cuda.h>
#include <stdint.h>

namespace {

constexpr int IMG_H = 512, IMG_W = 512, CH = 96;
constexpr int NSTAGE = 2;

constexpr int BT_BYTES   = 3072;
constexpr int W_BYTES    = 36 * BT_BYTES;
constexpr int BOX_BYTES  = 68 * 96;
constexpr int OFF_BOXB   = 70 * 128;
constexpr int STAGE_BYTES = 144 * 128;
constexpr int OFF_V      = 72 * 128;
constexpr int WG_IN_BYTES = STAGE_BYTES + 138 * 128;
constexpr int OFF_W      = 0;
constexpr int OFF_IN     = OFF_W + W_BYTES;
constexpr int OFF_X      = OFF_IN + 2 * WG_IN_BYTES;
constexpr int X_BYTES    = 3072;
constexpr int XBUF_BYTES = 4 * X_BYTES;
constexpr int X_TX = X_BYTES;
constexpr int SMEM_BYTES = OFF_X + 4 * XBUF_BYTES;
constexpr int OFF_ROW0_0 = OFF_X + ((OFF_IN - OFF_X) & 1023);
constexpr int OFF_ROW0_1 = OFF_X + 2 * XBUF_BYTES + ((OFF_IN + WG_IN_BYTES - OFF_X) & 1023);
constexpr int OFF_BAR    = OFF_IN + 68 * 128;
constexpr int BAR_FULL = 0, BAR_XFULL = 8, BAR_W = 24, BAR_ROW0 = 28, BAR_READY = 30;
constexpr int OFF_DBG    = OFF_IN + 138 * 128;
static_assert(SMEM_BYTES <= 232448, "shared memory");
constexpr uint32_t SMEM_BASE = 1024;
constexpr uint64_t BDESC = (uint64_t)((SMEM_BASE + OFF_W) >> 4) | ((uint64_t)(1536 >> 4) << 16) | ((uint64_t)(128 >> 4) << 32);

__device__ __forceinline__ void wg_fence()  { asm volatile("wgmma.fence.sync.aligned;" ::: "memory"); }
__device__ __forceinline__ void wg_commit() { asm volatile("wgmma.commit_group.sync.aligned;" ::: "memory"); }
template <int N> __device__ __forceinline__ void wg_wait() { asm volatile("wgmma.wait_group.sync.aligned %0;" ::"n"(N) : "memory"); }

template <int SCALE_D>
__device__ __forceinline__ void wgmma96(float (&d)[48], const uint32_t (&a)[4], uint64_t DESC) {
  asm volatile(
      "{\n.reg .pred p;\nsetp.ne.b32 p, %53, 0;\n"
      "wgmma.mma_async.sync.aligned.m64n96k16.f32.bf16.bf16 "
      "{%0,%1,%2,%3,%4,%5,%6,%7,%8,%9,%10,%11,%12,%13,%14,%15,%16,%17,%18,%19,%20,%21,%22,%23,"
      "%24,%25,%26,%27,%28,%29,%30,%31,%32,%33,%34,%35,%36,%37,%38,%39,%40,%41,%42,%43,%44,%45,%46,%47}, "
      "{%48,%49,%50,%51}, %52, p, 1, 1, 1;\n}\n"
      : "+f"(d[0]), "+f"(d[1]), "+f"(d[2]), "+f"(d[3]), "+f"(d[4]), "+f"(d[5]), "+f"(d[6]), "+f"(d[7]),
        "+f"(d[8]), "+f"(d[9]), "+f"(d[10]), "+f"(d[11]), "+f"(d[12]), "+f"(d[13]), "+f"(d[14]), "+f"(d[15]),
        "+f"(d[16]), "+f"(d[17]), "+f"(d[18]), "+f"(d[19]), "+f"(d[20]), "+f"(d[21]), "+f"(d[22]), "+f"(d[23]),
        "+f"(d[24]), "+f"(d[25]), "+f"(d[26]), "+f"(d[27]), "+f"(d[28]), "+f"(d[29]), "+f"(d[30]), "+f"(d[31]),
        "+f"(d[32]), "+f"(d[33]), "+f"(d[34]), "+f"(d[35]), "+f"(d[36]), "+f"(d[37]), "+f"(d[38]), "+f"(d[39]),
        "+f"(d[40]), "+f"(d[41]), "+f"(d[42]), "+f"(d[43]), "+f"(d[44]), "+f"(d[45]), "+f"(d[46]), "+f"(d[47])
      : "r"(a[0]), "r"(a[1]), "r"(a[2]), "r"(a[3]), "l"(DESC), "n"(SCALE_D));
}

__device__ __forceinline__ void ldsm4(uint32_t (&r)[4], uint32_t addr) {
  asm volatile("ldmatrix.sync.aligned.m8n8.x4.shared.b16 {%0,%1,%2,%3}, [%4];"
               : "=r"(r[0]), "=r"(r[1]), "=r"(r[2]), "=r"(r[3]) : "r"(addr) : "memory");
}
__device__ __forceinline__ uint32_t badd(uint32_t a, uint32_t b) {
  uint32_t d; asm volatile("add.rn.bf16x2 %0, %1, %2;" : "=r"(d) : "r"(a), "r"(b)); return d;
}
__device__ __forceinline__ uint32_t bsub(uint32_t a, uint32_t b) {
  uint32_t d; asm volatile("sub.rn.bf16x2 %0, %1, %2;" : "=r"(d) : "r"(a), "r"(b)); return d;
}
__device__ __forceinline__ uint32_t pack2(float lo, float hi) {
  uint32_t d; asm volatile("cvt.rn.bf16x2.f32 %0, %1, %2;" : "=r"(d) : "f"(hi), "f"(lo)); return d;
}

__device__ __forceinline__ void mbar_wait(uint32_t bar, uint32_t parity) {
  asm volatile(
      "{\n.reg .pred p;\n.reg .u32 it;\n"
      "mbarrier.try_wait.parity.shared::cta.b64 p, [%0], %1;\n"
      "@p bra WAIT_DONE;\n"
      "mov.u32 it, 0;\n"
      "WAIT_LOOP:\n"
      ".pragma \"nounroll\";\n"
      "mbarrier.try_wait.parity.shared::cta.b64 p, [%0], %1;\n"
      "@p bra WAIT_DONE;\n"
      "add.u32 it, it, 1;\n"
      "setp.lt.u32 p, it, 4194304;\n"
      "@p bra WAIT_LOOP;\n"
      "trap;\n"
      "WAIT_DONE:\n}\n" ::"r"(bar), "r"(parity) : "memory");
}
__device__ __forceinline__ bool mbar_try(uint32_t bar, uint32_t parity) {
  uint32_t ok;
  asm volatile("{\n.reg .pred p;\nmbarrier.test_wait.parity.shared::cta.b64 p, [%1], %2;\nselp.u32 %0, 1, 0, p;\n}\n"
               : "=r"(ok) : "r"(bar), "r"(parity) : "memory");
  return ok;
}
__device__ __forceinline__ void mbar_init(uint32_t bar, uint32_t count) {
  asm volatile("mbarrier.init.shared::cta.b64 [%0], %1;" ::"r"(bar), "r"(count) : "memory");
}
__device__ __forceinline__ void mbar_arrive(uint32_t bar) {
  asm volatile("mbarrier.arrive.shared::cta.b64 _, [%0];" ::"r"(bar) : "memory");
}
__device__ __forceinline__ void mbar_expect_tx(uint32_t bar, uint32_t bytes) {
  asm volatile("mbarrier.arrive.expect_tx.shared::cta.b64 _, [%0], %1;" ::"r"(bar), "r"(bytes) : "memory");
}
__device__ __forceinline__ void tma_load5(uint32_t dst, const CUtensorMap* map, uint32_t bar, int c0, int c1, int c2, int c3, int c4) {
  asm volatile("cp.async.bulk.tensor.5d.shared::cluster.global.mbarrier::complete_tx::bytes [%0], [%1, {%3,%4,%5,%6,%7}], [%2];"
               ::"r"(dst), "l"(map), "r"(bar), "r"(c0), "r"(c1), "r"(c2), "r"(c3), "r"(c4) : "memory");
}
__device__ __forceinline__ void bulk_load(uint32_t dst, const void* src, uint32_t bytes, uint32_t bar) {
  asm volatile("cp.async.bulk.shared::cluster.global.mbarrier::complete_tx::bytes [%0], [%1], %2, [%3];"
               ::"r"(dst), "l"(src), "r"(bytes), "r"(bar) : "memory");
}
template <int OFF>
__device__ __forceinline__ void st_async4(uint32_t cluster_addr, uint32_t cluster_bar, uint32_t a, uint32_t b, uint32_t c, uint32_t d) {
  asm volatile("st.async.shared::cluster.mbarrier::complete_tx::bytes.v4.b32 [%0+%6], {%2,%3,%4,%5}, [%1];"
               ::"r"(cluster_addr), "r"(cluster_bar), "r"(a), "r"(b), "r"(c), "r"(d), "n"(OFF) : "memory");
}
__device__ __forceinline__ void stsm4(uint32_t addr, uint32_t a, uint32_t b, uint32_t c, uint32_t d) {
  asm volatile("stmatrix.sync.aligned.m8n8.x4.shared.b16 [%0], {%1,%2,%3,%4};" ::"r"(addr), "r"(a), "r"(b), "r"(c), "r"(d) : "memory");
}
__device__ __forceinline__ uint32_t bfma(uint32_t a, uint32_t b, uint32_t c) {
  uint32_t d; asm volatile("fma.rn.bf16x2 %0, %1, %2, %3;" : "=r"(d) : "r"(a), "r"(b), "r"(c)); return d;
}
__device__ __forceinline__ void lds4(uint32_t (&r)[4], uint32_t addr) {
  asm volatile("ld.shared.v4.b32 {%0,%1,%2,%3}, [%4];" : "=r"(r[0]), "=r"(r[1]), "=r"(r[2]), "=r"(r[3]) : "r"(addr) : "memory");
}
__device__ __forceinline__ void sts4(uint32_t addr, const uint32_t (&r)[4]) {
  asm volatile("st.shared.v4.b32 [%0], {%1,%2,%3,%4};" ::"r"(addr), "r"(r[0]), "r"(r[1]), "r"(r[2]), "r"(r[3]) : "memory");
}
__device__ __forceinline__ void tma_store5(const CUtensorMap* map, uint32_t src, int c0, int c1, int c2, int c3, int c4) {
  asm volatile("cp.async.bulk.tensor.5d.global.shared::cta.bulk_group [%0, {%2,%3,%4,%5,%6}], [%1];"
               ::"l"(map), "r"(src), "r"(c0), "r"(c1), "r"(c2), "r"(c3), "r"(c4) : "memory");
  asm volatile("cp.async.bulk.commit_group;" ::: "memory");
}
__device__ __forceinline__ bool elect_one() {
  uint32_t p;
  asm volatile("{\n.reg .pred P;\nelect.sync _|P, 0xffffffff;\nselp.u32 %0, 1, 0, P;\n}\n" : "=r"(p));
  return p;
}
__device__ __forceinline__ uint32_t mapa(uint32_t addr, uint32_t rank) {
  uint32_t r; asm("mapa.shared::cluster.u32 %0, %1, %2;" : "=r"(r) : "r"(addr), "r"(rank)); return r;
}

__device__ __forceinline__ void tr_sum(uint32_t (&t)[3][4], const uint32_t (&U)[3][4], const uint32_t (&V)[3][4]) {
#pragma unroll
  for (int k = 0; k < 3; k++)
#pragma unroll
    for (int i = 0; i < 4; i++) t[k][i] = badd(U[k][i], V[k][i]);
}
__device__ __forceinline__ void tr_dif(uint32_t (&t)[3][4], const uint32_t (&U)[3][4], const uint32_t (&V)[3][4]) {
#pragma unroll
  for (int k = 0; k < 3; k++)
#pragma unroll
    for (int i = 0; i < 4; i++) t[k][i] = bsub(V[k][i], U[k][i]);
}
__device__ __forceinline__ void tr_t0(uint32_t (&t)[3][4], const uint32_t (&V)[3][4], const uint32_t (&E)[3][4]) {
#pragma unroll
  for (int k = 0; k < 3; k++) {
    t[k][0] = bsub(E[k][0], V[k][0]); t[k][1] = bsub(V[k][0], V[k][1]);
    t[k][2] = bsub(E[k][2], V[k][2]); t[k][3] = bsub(V[k][2], V[k][3]);
  }
}
__device__ __forceinline__ void tr_t3(uint32_t (&t)[3][4], const uint32_t (&U)[3][4], const uint32_t (&E)[3][4]) {
#pragma unroll
  for (int k = 0; k < 3; k++) {
    t[k][0] = bsub(U[k][1], U[k][0]); t[k][1] = bsub(E[k][1], U[k][1]);
    t[k][2] = bsub(U[k][3], U[k][2]); t[k][3] = bsub(E[k][3], U[k][3]);
  }
}
__device__ __forceinline__ void ld3(uint32_t (&R)[3][4], uint32_t aU, int off) {
#pragma unroll
  for (int k = 0; k < 3; k++) ldsm4(R[k], (aU ^ (32 * k)) + off);
}
template <int COMP, int AGE, int FIRST>
__device__ __forceinline__ void batch_(float (&acc)[48], const uint32_t (&t)[3][4], uint64_t bd) {
  constexpr int base = ((COMP * 3 + AGE) * 3) * BT_BYTES;
  wgmma96<FIRST ? 0 : 1>(acc, t[0], bd + ((base) >> 4));
  wgmma96<1>(acc, t[1], bd + ((base + BT_BYTES) >> 4));
  wgmma96<1>(acc, t[2], bd + ((base + 2 * BT_BYTES) >> 4));
  wg_commit();
}

template <int RANK, int I0, int I1>
__device__ __forceinline__ void butterfly(float (&X)[48], float (&Y)[48]) {
#pragma unroll
  for (int i = I0; i < I1; i++) {
    if (RANK == 0) asm volatile("sub.rn.f32 %0, %0, %1;\nfma.rn.f32 %1, %1, 0f40000000, %0;" : "+f"(X[i]), "+f"(Y[i]));
    else           asm volatile("add.rn.f32 %0, %0, %1;\nfma.rn.f32 %1, %1, 0fC0000000, %0;" : "+f"(X[i]), "+f"(Y[i]));
  }
}

#define DBG_T(c, idx)
#define DBG_TA(idx)
#define TL(c, k)
#define DBG_U(c, idx)
#define DBG_FLUSH(c)
#define DBG_G(c, idx)

struct Ctx {
  uint32_t aU, aE;
  uint32_t in_base;
  uint32_t bar_full;
  uint32_t bar_ready;
  uint32_t xaddr, xfull;
  uint32_t xbase;
  const CUtensorMap* omap;
  const CUtensorMap* map;
  const char* xseg;
  int wg, warp;
  int c0, u0, h0, hstep;
  int nrows;
  bool producer;
};

__device__ __forceinline__ void prefetch_row(const Ctx& c, int h) {
  if ((unsigned)h < (unsigned)IMG_H)
    asm volatile("cp.async.bulk.prefetch.L2.global [%0], %1;" ::"l"(c.xseg + (size_t)h * (IMG_W * CH * 2)), "r"(64 * CH * 2) : "memory");
}

template <int BUF, int C0, int C1>
__device__ __forceinline__ void load_partner(const Ctx& c, uint32_t (&P)[6][4]) {
#pragma unroll
  for (int ch = C0; ch < C1; ch++) lds4(P[ch], c.xaddr + BUF * XBUF_BYTES + (ch & 1) * 6144 + (ch >> 1) * 64);
}
template <int BUF, int C0, int C1>
__device__ __forceinline__ void finish_chunks(const Ctx& c, const float (&Y)[48], uint32_t (&P)[6][4]) {
#pragma unroll
  for (int ch = C0; ch < C1; ch++) {
    const int m = ch >> 1, s = ch & 1;
#pragma unroll
    for (int ss = 0; ss < 4; ss++) P[ch][ss] = badd(pack2(Y[16 * m + 4 * ss + 2 * s], Y[16 * m + 4 * ss + 2 * s + 1]), P[ch][ss]);
    sts4(c.xaddr + BUF * XBUF_BYTES + s * 6144 + m * 64, P[ch]);
  }
}
template <int RANK, int BUF, int CH0>
__device__ __forceinline__ void send_chunk(const Ctx& c, const float (&X)[48]) {
  constexpr uint32_t RDELTA = RANK ? 0xFF000000u : 0x01000000u;
  constexpr int m = CH0 >> 1, s = CH0 & 1;
  uint32_t o[4];
#pragma unroll
  for (int ss = 0; ss < 4; ss++) o[ss] = pack2(X[16 * m + 4 * ss + 2 * s], X[16 * m + 4 * ss + 2 * s + 1]);
  st_async4<BUF * XBUF_BYTES + s * 6144 + m * 64>(c.xaddr + RDELTA, c.xfull + BUF * 64 + RDELTA, o[0], o[1], o[2], o[3]);
}

#define SLOTV 0
#define FULLSKIP 3
#define CLROT 2
#define SPN 16
#define LATE3 1
#define PF_START 2
#define R3POS 1
#define WASG 1
#define WWARPS (WASG ? 8 : 6)
#define PF_DIST 1
#define NCL 66
#define RORD 0x652410
#define RORDS 0x625140

struct Regs {
  float X[48], Y[48];
  uint32_t T[4][2][3][4];
  uint32_t U[3][4], V[3][4], E[3][4];
  uint32_t Z[6][4], P[6][4];
};

template <int RANK, int OLD>
__device__ __forceinline__ void tma_slot(const Ctx& c, int n) {
  constexpr int MID = 1 - OLD;
  const int h = c.h0 + n * c.hstep;
  asm volatile("fence.proxy.async.shared::cta;" ::: "memory");
  asm volatile("bar.sync %0, 128;" ::"r"(2 + c.wg) : "memory");
  if (elect_one()) {
    if (c.warp < 2) {
      if (n + 2 < c.nrows) {
        mbar_expect_tx(c.bar_full + 8 * OLD, BOX_BYTES);
        tma_load5(c.in_base + OLD * STAGE_BYTES + c.warp * OFF_BOXB, c.map, c.bar_full + 8 * OLD, c.c0, 2 * c.warp, c.u0 - c.warp, 0,
                  h + 4 * c.hstep);
      } else {
        mbar_arrive(c.bar_full + 8 * OLD);
      }
    } else if (c.warp == 2) {
      if (OLD == 1 || n > 0) tma_store5(c.omap, c.xbase + MID * XBUF_BYTES, 0, c.u0, 0, RANK, h);
    } else {
      if (PF_DIST > 0 && n >= PF_START && n + 2 + PF_DIST < c.nrows) prefetch_row(c, h + (4 + PF_DIST) * c.hstep);
    }
  }
  __syncwarp();
}
template <int RANK, int OLD>
__device__ __forceinline__ void release_xbuf(const Ctx& c) {
  constexpr uint32_t RDELTA = RANK ? 0xFF000000u : 0x01000000u;
  asm volatile("cp.async.bulk.wait_group.read 0;" ::: "memory");
  asm volatile("{\n.reg .pred p, q;\nelect.sync _|q, 0xffffffff;\nsetp.eq.and.u32 p, %1, 2, q;\n@p mbarrier.arrive.shared::cluster.b64 _, [%0];\n}\n"
               ::"r"(c.bar_full + 8 * (1 - OLD) + RDELTA), "r"(c.warp) : "memory");
}
template <int C0, int C1>
__device__ __forceinline__ void pack_acc(uint32_t (&Z)[6][4], const float (&Y)[48]) {
#pragma unroll
  for (int ch = C0; ch < C1; ch++)
#pragma unroll
    for (int ss = 0; ss < 4; ss++) {
      const int i = 16 * (ch >> 1) + 4 * ss + 2 * (ch & 1);
      Z[ch][ss] = pack2(Y[i], Y[i + 1]);
    }
}
template <int BUF, int C0, int C1>
__device__ __forceinline__ void add_stage(const Ctx& c, uint32_t (&Z)[6][4], const uint32_t (&P)[6][4]) {
#pragma unroll
  for (int ch = C0; ch < C1; ch++)
#pragma unroll
    for (int ss = 0; ss < 4; ss++) Z[ch][ss] = badd(Z[ch][ss], P[ch][ss]);
#pragma unroll
  for (int ch = C0; ch < C1; ch++) sts4(c.xaddr + BUF * XBUF_BYTES + (ch & 1) * 6144 + (ch >> 1) * 64, Z[ch]);
}

__device__ __forceinline__ uint64_t get_bd(const Ctx& c, int n) {
  return BDESC;
}
#define G1  batch_<0, 0, 1>(r.X, r.T[0][OLD], bd);
#define G2  batch_<0, 1, 0>(r.X, r.T[0][MID], bd);
#define G3  batch_<0, 2, 0>(r.X, r.T[0][OLD], bd);
#define G4  batch_<1, 0, 1>(r.Y, r.T[1][OLD], bd);
#define G5  batch_<1, 1, 0>(r.Y, r.T[1][MID], bd);
#define G6  batch_<1, 2, 0>(r.Y, r.T[1][OLD], bd);
#define G7  if (OLD == 1 || !(FULLSKIP & 1)) batch_<2, 0, 0>(r.X, r.T[2][OLD], bd); else { if (!skip) { F batch_<2, 0, 0>(r.X, r.T[2][OLD], bd); } else { F wg_commit(); } F }
#define G8  batch_<2, 1, 0>(r.X, r.T[2][MID], bd);
#define G9  batch_<2, 2, 0>(r.X, r.T[2][OLD], bd);
#define G10 if (OLD == 1 || !(FULLSKIP & 2)) batch_<3, 0, 0>(r.Y, r.T[3][OLD], bd); else { if (!skip) { F batch_<3, 0, 0>(r.Y, r.T[3][OLD], bd); } else { F wg_commit(); } F }
#define G11 batch_<3, 1, 0>(r.Y, r.T[3][MID], bd);
#define G12 batch_<3, 2, 0>(r.Y, r.T[3][OLD], bd);
#define F   wg_fence();
#define W(k) wg_wait<k>();
#define PACK pack_acc<0, 6>(r.Z, r.Y);
#define PK(a, b) pack_acc<a, b>(r.Z, r.Y);
#define XW  mbar_wait(c.xfull + MID * 64, ((n - 1) >> 1) & 1); FIX3
#define ARM if (elect_one()) mbar_expect_tx(c.xfull + MID * 64, X_TX);
#define REL release_xbuf<RANK, OLD>(c);
#define LP(a, b) load_partner<MID, a, b>(c, r.P);
#define AS(a, b) add_stage<MID, a, b>(c, r.Z, r.P);
#define LV1 if (RANK == 0) ld3(r.V, c.aU, OLD * STAGE_BYTES + OFF_V); else ld3(r.U, c.aU, OLD * STAGE_BYTES);
#define LU1 if (RANK == 0) ld3(r.U, c.aU, OLD * STAGE_BYTES); else ld3(r.V, c.aU, OLD * STAGE_BYTES + OFF_V);
#define LU2 if (RANK == 0) ld3(r.U, c.aU, MID * STAGE_BYTES); else ld3(r.V, c.aU, MID * STAGE_BYTES + OFF_V);
#define LE  ld3(r.E, c.aE, OLD * STAGE_BYTES);
#define LEk(k)  ldsm4(r.E[k], (c.aE ^ (32 * k)) + OLD * STAGE_BYTES);
#define LV1k(k) if (RANK == 0) ldsm4(r.V[k], (c.aU ^ (32 * k)) + OLD * STAGE_BYTES + OFF_V); else ldsm4(r.U[k], (c.aU ^ (32 * k)) + OLD * STAGE_BYTES);
#define LV2k(k) if (RANK == 0) ldsm4(r.V[k], (c.aU ^ (32 * k)) + MID * STAGE_BYTES + OFF_V); else ldsm4(r.U[k], (c.aU ^ (32 * k)) + MID * STAGE_BYTES);
#define LU1k(k) if (RANK == 0) ldsm4(r.U[k], (c.aU ^ (32 * k)) + OLD * STAGE_BYTES); else ldsm4(r.V[k], (c.aU ^ (32 * k)) + OLD * STAGE_BYTES + OFF_V);
#define LU2k(k) if (RANK == 0) ldsm4(r.U[k], (c.aU ^ (32 * k)) + MID * STAGE_BYTES); else ldsm4(r.V[k], (c.aU ^ (32 * k)) + MID * STAGE_BYTES + OFF_V);
#define TRS tr_sum(r.T[0][OLD], r.U, r.V);
#define TRF tr_dif(r.T[1][OLD], r.U, r.V);
#define TRC if (RANK == 0) tr_t3(r.T[2][OLD], r.U, r.E); else tr_t0(r.T[2][OLD], r.V, r.E);
#define TRD if (RANK == 0) tr_t0(r.T[3][OLD], r.V, r.E); else tr_t3(r.T[3][OLD], r.U, r.E);
#define SLOT tma_slot<RANK, OLD>(c, n);
#define FW  if (OLD == 1) mbar_wait(c.bar_full, ((n + 2) >> 1) & 1); \
            else mbar_wait(n ? c.bar_full + 8 : c.bar_ready, n ? ((n + 3) >> 1) & 1 : 0);
#define FIX3 if (OLD == 1 && n == 1) { mbar_wait(c.bar_full + 8, 1); SCHED_FIX3 }
#define SND(k) send_chunk<RANK, OLD, k>(c, r.X);
#define SCHED1 F G1 G2 XW W(2) PK(0,1) ARM LP(0,1) PK(1,2) LP(1,2) LP(2,3) REL AS(0,1) PK(2,3) PK(3,4) PK(4,5) AS(1,2) LP(3,4) PK(5,6) LP(4,5) AS(2,3) LP(5,6) LV1k(0) LV1k(1) LV1k(2) F G4 G5 W(3) TRS F G3 AS(3,4) AS(4,5) W(2) TRF LEk(0) LEk(1) LEk(2) AS(5,6) F G6 SLOT
#define SCHED1_FIRST LEk(0) LEk(1) LEk(2) SLOT
#define SCHED_FIX3 LU1k(0) LU1k(1) LU1k(2)
#define SCHED2 F G7 G8 FW W(1) TRC LU2k(0) F G9 LU2k(1) LU2k(2) F G10 W(1) SND(0) SND(1) SND(2) F G11 SND(3) W(1) TRD SND(4) SND(5) F G12

__device__ __forceinline__ void load_row3(const Ctx& c) {
  mbar_expect_tx(c.bar_full + 8, BOX_BYTES);
  tma_load5(c.in_base + STAGE_BYTES + c.warp * OFF_BOXB, c.map, c.bar_full + 8, c.c0, 2 * c.warp, c.u0 - c.warp, 0, c.h0 + 3 * c.hstep);
}
template <int RANK, int OLD, bool FIRST>
__device__ __forceinline__ void phase1(const Ctx& c, int n, Regs& r) {
  constexpr int MID = 1 - OLD;
  const uint64_t bd = get_bd(c, n);
  if (FIRST) {
    wg_fence();
    batch_<0, 1, 1>(r.X, r.T[0][MID], bd);
    batch_<1, 1, 1>(r.Y, r.T[1][MID], bd);
    if ((unsigned)c.h0 < (unsigned)IMG_H) {
      wg_fence();
      batch_<0, 0, 0>(r.X, r.T[0][OLD], bd);
      batch_<1, 0, 0>(r.Y, r.T[1][OLD], bd);
    }
    mbar_wait(c.bar_full + 8 * OLD, 0);
    if (R3POS == 1) { if (c.warp < 2 && elect_one()) load_row3(c); __syncwarp(); }
    LU1 LV1 W(1) TRS F G3 W(1) TRF F G6
    if (R3POS == 2) { if (c.warp < 2 && elect_one()) load_row3(c); __syncwarp(); }
    SCHED1_FIRST
  } else {
    SCHED1
  }
  wg_wait<0>();
  DBG_U(c, 4 + n);
}

template <int RANK, int OLD>
__device__ __forceinline__ void phase2(const Ctx& c, int n, Regs& r) {
  constexpr int MID = 1 - OLD;
  const uint64_t bd = get_bd(c, n);
  butterfly<RANK, 0, 48>(r.X, r.Y);
  const bool skip = (unsigned)(c.h0 + n * c.hstep) >= (unsigned)IMG_H;
  SCHED2
}

template <int RANK, int BUF>
__device__ __forceinline__ void finish_strip(const Ctx& c, Regs& r) {
  DBG_T(c, 35);
  uint32_t P[6][4];
  mbar_wait(c.xfull + BUF * 64, ((c.nrows - 1) >> 1) & 1);
  load_partner<BUF, 0, 6>(c, P);
  wg_wait<0>();
  finish_chunks<BUF, 0, 6>(c, r.Y, P);
  asm volatile("fence.proxy.async.shared::cta;" ::: "memory");
  asm volatile("bar.sync %0, 128;" ::"r"(2 + c.wg) : "memory");
  if (c.warp == 2 && elect_one()) {
    tma_store5(c.omap, c.xbase + BUF * XBUF_BYTES, 0, c.u0, 0, RANK, c.h0 + c.nrows * c.hstep);
    asm volatile("cp.async.bulk.wait_group.read 0;" ::: "memory");
  }
  DBG_T(c, 40); DBG_G(c, 1);
  DBG_FLUSH(c);
}

template <int RANK>
__device__ __forceinline__ void run_strip(const Ctx& c, uint32_t row0_off, uint32_t bar_row0) {
  Regs r;
#pragma unroll
  for (int m = 0; m < 2; m++) {
    const uint32_t off = m ? STAGE_BYTES : row0_off;
    mbar_wait(m ? c.bar_full + 8 : bar_row0, 0);
    DBG_T(c, 50 + m);
    ld3(r.U, c.aU, off);
    ld3(r.V, c.aU, off + OFF_V);
    ld3(r.E, c.aE, off);
    tr_sum(r.T[0][m], r.U, r.V);
    tr_dif(r.T[1][m], r.U, r.V);
    tr_t3(r.T[RANK == 0 ? 2 : 3][m], r.U, r.E);
    tr_t0(r.T[RANK == 0 ? 3 : 2][m], r.V, r.E);
  }
  asm volatile("bar.sync %0, 128;" ::"r"(2 + c.wg) : "memory");
  asm volatile("barrier.cluster.wait.aligned;" ::: "memory");
  if (elect_one()) {
    if (c.warp < 2) {
      if (R3POS == 0) load_row3(c);
    } else if (c.warp == 2) {
      asm volatile("mbarrier.arrive.shared::cluster.b64 _, [%0];" ::"r"((bar_row0 + (BAR_READY - BAR_ROW0) * 8) ^ 0x01000000u) : "memory");
    } else {
      mbar_arrive(c.bar_full + 8);
    }
  }
  __syncwarp();
  DBG_T(c, 46);
  mbar_wait(SMEM_BASE + (RANK << 24) + OFF_BAR + 8 * BAR_W + 24, 0);
  DBG_T(c, 3);
#pragma unroll
  for (int i = 0; i < 48; i++) { r.X[i] = 0.f; r.Y[i] = 0.f; r.Z[i % 6][i / 12] = 0; r.P[i % 6][i / 12] = 0; }
  phase1<RANK, 0, true>(c, 0, r);
  if (!LATE3) mbar_wait(c.bar_ready, 0);
#pragma unroll 1
  for (int n = 0;; n += 2) {
    phase2<RANK, 0>(c, n, r);
    if (n + 1 == c.nrows) { finish_strip<RANK, 0>(c, r); break; }
    phase1<RANK, 1, false>(c, n + 1, r);
    phase2<RANK, 1>(c, n + 1, r);
    if (n + 2 == c.nrows) { finish_strip<RANK, 1>(c, r); break; }
    phase1<RANK, 0, false>(c, n + 2, r);
  }
}

struct Strip { int seg, h0, hstep, nrows; };
__device__ __forceinline__ Strip get_strip(int cl, int wg) {
  int seg, par, r0, nrows; bool down;
  if (NCL == 64) {
    const int sid = cl * 2 + wg;
    seg = sid & 3; par = (sid >> 2) & 1; r0 = (sid >> 3) * 16; nrows = 16; down = !((sid >> 3) & 1);
  } else if (cl >= 64) {
    seg = (cl - 64) * 2 + wg; par = 1; r0 = 0; nrows = SPN; down = true;
  } else {
    const int i = cl >> 2;
    seg = cl & 3; par = wg; down = !(i & 1);
    r0 = wg ? 16 + 15 * (down ? i + 1 : i - 1) : 16 * i;
    nrows = 16 - wg;
  }
  return Strip{seg, 2 * (down ? r0 - 1 : r0 + nrows) + par, down ? 2 : -2, nrows};
}

__global__ void __cluster_dims__(2, 1, 1) __launch_bounds__(256, 1)
dilated_conv_wino_kernel(const __grid_constant__ CUtensorMap xmap, const __grid_constant__ CUtensorMap omap,
                         const __nv_bfloat16* __restrict__ x, const __nv_bfloat16* __restrict__ w) {
  extern __shared__ uint8_t smem_raw[];
  const int tid = threadIdx.x;
  const int wg = __shfl_sync(0xffffffff, tid >> 7, 0);
  const int warp = __shfl_sync(0xffffffff, (tid >> 5) & 3, 0);
  const int lane = tid & 31;
  const int rank = blockIdx.x & 1;
  const uint32_t sbase = SMEM_BASE + (rank << 24);
  if ((uint32_t)__cvta_generic_to_shared(smem_raw) != sbase || mapa(sbase, rank ^ 1) != (sbase ^ 0x01000000u)) __trap();
  const int cl = CLROT ? ((blockIdx.x >> 1) + NCL - CLROT) % NCL : blockIdx.x >> 1;
  const Strip sp = get_strip(cl, wg);
  const bool down = sp.hstep > 0;

  Ctx c;
  c.map = &xmap;
  c.wg = wg;
  c.warp = warp;
  c.in_base = sbase + OFF_IN + wg * WG_IN_BYTES;
  c.bar_full = sbase + OFF_BAR + 8 * (BAR_FULL + wg * NSTAGE);
  c.bar_ready = sbase + OFF_BAR + 8 * (BAR_READY + wg);
  c.c0 = rank * 48;
  c.u0 = sp.seg * 16;
  c.h0 = sp.h0;
  c.hstep = sp.hstep;
  c.nrows = sp.nrows;
  c.producer = (tid & 127) == 0;
  c.xfull = sbase + OFF_BAR + 8 * (BAR_XFULL + wg * 4 + warp);
  c.xseg = reinterpret_cast<const char*>(x) + (sp.seg * 128 + rank * 64) * (CH * 2);

  DBG_G(c, 0); DBG_T(c, 0);
  const uint32_t bar_w = sbase + OFF_BAR + 8 * BAR_W;
  const uint32_t o_w0 = (rank ? 2 : 3) * 9 * BT_BYTES, o_w2 = (rank ? 3 : 2) * 9 * BT_BYTES;
  if (elect_one()) {
    const uint32_t b0 = sbase + OFF_BAR;
    const int w8 = wg * 4 + warp;
    if (w8 >= 5) {
      const int a = w8 - 5, i = down ? a : 2 - a;
      const __nv_bfloat16* src = w + ((size_t)(i * 3) * CH + rank * 48) * CH;
      const uint32_t dst = sbase + OFF_W + a * 3 * BT_BYTES;
      mbar_init(bar_w + 8 * a, 1);
      asm volatile("fence.proxy.async.shared::cta;" ::: "memory");
      mbar_expect_tx(bar_w + 8 * a, 9 * BT_BYTES);
      bulk_load(dst + o_w0, src, 3 * BT_BYTES, bar_w + 8 * a);
      bulk_load(dst, src + CH * CH, 3 * BT_BYTES, bar_w + 8 * a);
      bulk_load(dst + o_w2, src + 2 * CH * CH, 3 * BT_BYTES, bar_w + 8 * a);
      DBG_TA(53 + a);
    } else {
      if (w8 < 4) {
        mbar_init(b0 + 8 * w8, 3);
#pragma unroll
        for (int q = 0; q < 4; q++) mbar_init(b0 + 8 * (BAR_XFULL + 4 * w8 + q), 1);
        mbar_expect_tx(b0 + 8 * w8, 2 * BOX_BYTES);
        asm volatile("mbarrier.arrive.shared::cta.b64 _, [%0], 2;" ::"r"(b0 + 8 * w8) : "memory");
      } else {
        asm volatile("prefetch.tensormap [%0];" ::"l"(&xmap) : "memory");
#pragma unroll
        for (int q = 0; q < 2; q++) {
          mbar_init(b0 + 8 * (BAR_ROW0 + q), 1);
          mbar_init(b0 + 8 * (BAR_READY + q), 1);
          mbar_expect_tx(b0 + 8 * (BAR_ROW0 + q), 2 * BOX_BYTES);
        }
        mbar_init(bar_w + 24, WWARPS);
      }
      asm volatile("fence.mbarrier_init.release.cluster;" ::: "memory");
      asm volatile("fence.proxy.async.shared::cta;" ::: "memory");
    }
  }
  DBG_T(c, 45);
  __syncthreads();
  asm volatile("barrier.cluster.arrive.relaxed.aligned;" ::: "memory");
  DBG_T(c, 41);
  const uint32_t row0 = sbase + (wg ? OFF_ROW0_1 : OFF_ROW0_0);
  const uint32_t bar_row0 = sbase + OFF_BAR + 8 * (BAR_ROW0 + wg);
  if (warp == 3) {
    if (elect_one()) {
      const Strip so = get_strip(cl, wg ^ 1);
#pragma unroll 1
      for (int k = 0; k < 6; k++) {
        const int code = ((cl < 64 ? RORD : RORDS) >> (4 * k)) & 15, g = code >> 2, m = code & 3;
        const uint32_t dst = m == 0 ? sbase + (g ? OFF_ROW0_1 : OFF_ROW0_0) : sbase + OFF_IN + g * WG_IN_BYTES + (m & 1) * STAGE_BYTES;
        const uint32_t bar = sbase + OFF_BAR + 8 * (m == 0 ? BAR_ROW0 + g : BAR_FULL + 2 * g + (m & 1));
        tma_load5(dst + wg * OFF_BOXB, &xmap, bar, c.c0, 2 * wg, (g == wg ? sp.seg : so.seg) * 16 - wg, 0, (g == wg ? sp.h0 : so.h0) + m * c.hstep);
      }
      asm volatile("prefetch.tensormap [%0];" ::"l"(&omap) : "memory");
      DBG_TA(49);
    }
    __syncwarp();
  }
  if (WASG != 0 || warp != 3) {
#pragma unroll 1
    for (int it = 0; it < 3; it++) {
      int item;
      if (WASG == 0) item = it * 6 + wg * 3 + warp;
      else if (WASG == 1) { item = it == 0 ? (wg ? warp : 4 + warp) : it == 1 ? (wg ? 8 + warp : 12 + warp) : 14 + warp; if (wg == 0 && (it == 2 || (it == 1 && warp >= 2))) break; }
      else { item = it * 8 + (wg ? warp : 4 + warp); if (item >= 18) break; }
      const int age = item / 6;
      const uint32_t base = sbase + OFF_W + item * 1536;
      mbar_wait(bar_w + 8 * age, 0);
      DBG_T(c, 42 + it);
      uint32_t wa[3][4], wb[3][4], wd[3][4];
      const uint32_t src = base + (lane >> 2) * 192 + (lane & 3) * 16;
#pragma unroll
      for (int m = 0; m < 3; m++) {
        lds4(wa[m], src + o_w0 + m * 64);
        lds4(wb[m], src + m * 64);
        lds4(wd[m], src + o_w2 + m * 64);
      }
      __syncwarp();
      const uint32_t dst = base + lane * 16;
#pragma unroll
      for (int m = 0; m < 3; m++) {
        uint32_t g1[4], g2[4];
        stsm4(dst + m * 512 + o_w0, wa[m][0], wa[m][1], wa[m][2], wa[m][3]);
        stsm4(dst + m * 512 + o_w2, wd[m][0], wd[m][1], wd[m][2], wd[m][3]);
#pragma unroll
        for (int ss = 0; ss < 4; ss++) {
          const uint32_t a = wa[m][ss], b = wb[m][ss], d = wd[m][ss];
          const float slo = __uint_as_float(a << 16) + __uint_as_float(d << 16);
          const float shi = __uint_as_float(a & 0xffff0000u) + __uint_as_float(d & 0xffff0000u);
          const float blo = 0.5f * __uint_as_float(b << 16), bhi = 0.5f * __uint_as_float(b & 0xffff0000u);
          g1[ss] = pack2(fmaf(slo, 0.5f, blo), fmaf(shi, 0.5f, bhi));
          g2[ss] = pack2(fmaf(slo, 0.5f, -blo), fmaf(shi, 0.5f, -bhi));
        }
        stsm4(dst + m * 512, g1[0], g1[1], g1[2], g1[3]);
        stsm4(dst + m * 512 + 9 * BT_BYTES, g2[0], g2[1], g2[2], g2[3]);
      }
    }
    asm volatile("fence.proxy.async.shared::cta;" ::: "memory");
    __syncwarp();
    if (elect_one()) mbar_arrive(bar_w + 24);
  }
  if (elect_one()) { mbar_expect_tx(c.xfull, X_TX); mbar_expect_tx(c.xfull + 64, X_TX); }
  DBG_T(c, 1);

  {
    const int g = lane & 7, mi = lane >> 3;
    const int rU = 8 * warp + g + ((mi & 1) ? 34 : 0);
    const int rE = 8 * warp + g + ((mi & 1) ? 2 : 70 + 34);
    const uint32_t pU = c.in_base + rU * 128, pE = c.in_base + rE * 128;
    c.aU = pU + (((mi >> 1) ^ ((pU >> 7) & 7)) << 4);
    c.aE = pE + (((mi >> 1) ^ ((pE >> 7) & 7)) << 4);
  }
  c.xbase = sbase + OFF_X + wg * 2 * XBUF_BYTES;
  c.xaddr = c.xbase + (warp * 8 + (lane >> 2)) * 192 + (lane & 3) * 16;
  c.omap = &omap;
  if (rank == 0) run_strip<0>(c, row0 - c.in_base, bar_row0); else run_strip<1>(c, row0 - c.in_base, bar_row0);
}

typedef CUresult (*EncodeTiledFn)(CUtensorMap*, CUtensorMapDataType, cuuint32_t, void*, const cuuint64_t*, const cuuint64_t*,
                                  const cuuint32_t*, const cuuint32_t*, CUtensorMapInterleave, CUtensorMapSwizzle,
                                  CUtensorMapL2promotion, CUtensorMapFloatOOBfill);

}

extern "C" void kernel_launch(void* const* d_in, const int* in_sizes, int n_in, void* d_out, int out_size) {
  (void)in_sizes; (void)n_in; (void)out_size;
  static EncodeTiledFn encode = nullptr;
  if (!encode) {
    void* fn = nullptr;
    cudaDriverEntryPointQueryResult qr;
    cudaGetDriverEntryPoint("cuTensorMapEncodeTiled", &fn, cudaEnableDefault, &qr);
    encode = (EncodeTiledFn)fn;
    cudaFuncSetAttribute(dilated_conv_wino_kernel, cudaFuncAttributeMaxDynamicSharedMemorySize, SMEM_BYTES);
  }
  CUtensorMap xmap;
  const cuuint64_t dims[5] = {CH, 4, IMG_W / 8, 2, IMG_H};
  const cuuint64_t strides[4] = {CH * 2, 8 * CH * 2, 4 * CH * 2, IMG_W * CH * 2};
  const cuuint32_t box[5] = {48, 2, 17, 2, 1};
  const cuuint32_t estr[5] = {1, 1, 1, 1, 1};
#define PROMO CU_TENSOR_MAP_L2_PROMOTION_L2_128B
  encode(&xmap, CU_TENSOR_MAP_DATA_TYPE_BFLOAT16, 5, d_in[0], dims, strides, box, estr, CU_TENSOR_MAP_INTERLEAVE_NONE,
         CU_TENSOR_MAP_SWIZZLE_128B, PROMO, CU_TENSOR_MAP_FLOAT_OOB_FILL_NONE);
  CUtensorMap omap;
  const cuuint64_t odims[5] = {2 * CH, IMG_W / 8, 2, 2, IMG_H};
  const cuuint64_t ostrides[4] = {8 * CH * 2, 4 * CH * 2, 2 * CH * 2, IMG_W * CH * 2};
  const cuuint32_t obox[5] = {2 * CH, 16, 2, 1, 1};
  encode(&omap, CU_TENSOR_MAP_DATA_TYPE_BFLOAT16, 5, d_out, odims, ostrides, obox, estr, CU_TENSOR_MAP_INTERLEAVE_NONE,
         CU_TENSOR_MAP_SWIZZLE_NONE, CU_TENSOR_MAP_L2_PROMOTION_NONE, CU_TENSOR_MAP_FLOAT_OOB_FILL_NONE);
  dilated_conv_wino_kernel<<<2 * NCL, 256, SMEM_BYTES>>>(xmap, omap, (const __nv_bfloat16*)d_in[0], (const __nv_bfloat16*)d_in[1]);
}
```

```cpp
#include <cuda_runtime.h>
#include <cuda_bf16.h>
#include <cuda.h>
#include <stdint.h>

namespace {

constexpr int IMG_H = 512, IMG_W = 512, CH = 96;
constexpr int NSTAGE = 2;

constexpr int BT_BYTES   = 3072;
constexpr int W_BYTES    = 36 * BT_BYTES;
constexpr int BOX_BYTES  = 68 * 96;
constexpr int OFF_BOXB   = 70 * 128;
constexpr int STAGE_BYTES = 144 * 128;
constexpr int OFF_V      = 72 * 128;
constexpr int WG_IN_BYTES = STAGE_BYTES + 138 * 128;
constexpr int OFF_W      = 0;
constexpr int OFF_IN     = OFF_W + W_BYTES;
constexpr int OFF_X      = OFF_IN + 2 * WG_IN_BYTES;
constexpr int X_BYTES    = 3072;
constexpr int XBUF_BYTES = 4 * X_BYTES;
constexpr int X_TX = X_BYTES;
constexpr int SMEM_BYTES = OFF_X + 4 * XBUF_BYTES;
constexpr int OFF_ROW0_0 = OFF_X + ((OFF_IN - OFF_X) & 1023);
constexpr int OFF_ROW0_1 = OFF_X + 2 * XBUF_BYTES + ((OFF_IN + WG_IN_BYTES - OFF_X) & 1023);
constexpr int OFF_BAR    = OFF_IN + 68 * 128;
constexpr int BAR_FULL = 0, BAR_XFULL = 8, BAR_W = 24, BAR_ROW0 = 28, BAR_READY = 30;
constexpr int OFF_DBG    = OFF_IN + 138 * 128;
static_assert(SMEM_BYTES <= 232448, "shared memory");
constexpr uint32_t SMEM_BASE = 1024;
constexpr uint64_t BDESC = (uint64_t)((SMEM_BASE + OFF_W) >> 4) | ((uint64_t)(1536 >> 4) << 16) | ((uint64_t)(128 >> 4) << 32);

__device__ __forceinline__ void wg_fence()  { asm volatile("wgmma.fence.sync.aligned;" ::: "memory"); }
__device__ __forceinline__ void wg_commit() { asm volatile("wgmma.commit_group.sync.aligned;" ::: "memory"); }
template <int N> __device__ __forceinline__ void wg_wait() { asm volatile("wgmma.wait_group.sync.aligned %0;" ::"n"(N) : "memory"); }

template <int SCALE_D>
__device__ __forceinline__ void wgmma96(float (&d)[48], const uint32_t (&a)[4], uint64_t DESC) {
  asm volatile(
      "{\n.reg .pred p;\nsetp.ne.b32 p, %53, 0;\n"
      "wgmma.mma_async.sync.aligned.m64n96k16.f32.bf16.bf16 "
      "{%0,%1,%2,%3,%4,%5,%6,%7,%8,%9,%10,%11,%12,%13,%14,%15,%16,%17,%18,%19,%20,%21,%22,%23,"
      "%24,%25,%26,%27,%28,%29,%30,%31,%32,%33,%34,%35,%36,%37,%38,%39,%40,%41,%42,%43,%44,%45,%46,%47}, "
      "{%48,%49,%50,%51}, %52, p, 1, 1, 1;\n}\n"
      : "+f"(d[0]), "+f"(d[1]), "+f"(d[2]), "+f"(d[3]), "+f"(d[4]), "+f"(d[5]), "+f"(d[6]), "+f"(d[7]),
        "+f"(d[8]), "+f"(d[9]), "+f"(d[10]), "+f"(d[11]), "+f"(d[12]), "+f"(d[13]), "+f"(d[14]), "+f"(d[15]),
        "+f"(d[16]), "+f"(d[17]), "+f"(d[18]), "+f"(d[19]), "+f"(d[20]), "+f"(d[21]), "+f"(d[22]), "+f"(d[23]),
        "+f"(d[24]), "+f"(d[25]), "+f"(d[26]), "+f"(d[27]), "+f"(d[28]), "+f"(d[29]), "+f"(d[30]), "+f"(d[31]),
        "+f"(d[32]), "+f"(d[33]), "+f"(d[34]), "+f"(d[35]), "+f"(d[36]), "+f"(d[37]), "+f"(d[38]), "+f"(d[39]),
        "+f"(d[40]), "+f"(d[41]), "+f"(d[42]), "+f"(d[43]), "+f"(d[44]), "+f"(d[45]), "+f"(d[46]), "+f"(d[47])
      : "r"(a[0]), "r"(a[1]), "r"(a[2]), "r"(a[3]), "l"(DESC), "n"(SCALE_D));
}

__device__ __forceinline__ void ldsm4(uint32_t (&r)[4], uint32_t addr) {
  asm volatile("ldmatrix.sync.aligned.m8n8.x4.shared.b16 {%0,%1,%2,%3}, [%4];"
               : "=r"(r[0]), "=r"(r[1]), "=r"(r[2]), "=r"(r[3]) : "r"(addr) : "memory");
}
__device__ __forceinline__ uint32_t badd(uint32_t a, uint32_t b) {
  uint32_t d; asm volatile("add.rn.bf16x2 %0, %1, %2;" : "=r"(d) : "r"(a), "r"(b)); return d;
}
__device__ __forceinline__ uint32_t bsub(uint32_t a, uint32_t b) {
  uint32_t d; asm volatile("sub.rn.bf16x2 %0, %1, %2;" : "=r"(d) : "r"(a), "r"(b)); return d;
}
__device__ __forceinline__ float bf_lo(uint32_t v) {
  return __uint_as_float(v << 16);
}
__device__ __forceinline__ float bf_hi(uint32_t v) { return __uint_as_float(v & 0xffff0000u); }
__device__ __forceinline__ uint32_t pack2(float lo, float hi) {
  uint32_t d; asm volatile("cvt.rn.bf16x2.f32 %0, %1, %2;" : "=r"(d) : "f"(hi), "f"(lo)); return d;
}

__device__ __forceinline__ void mbar_wait(uint32_t bar, uint32_t parity) {
  asm volatile(
      "{\n.reg .pred p;\n.reg .u32 it;\n"
      "mbarrier.try_wait.parity.shared::cta.b64 p, [%0], %1;\n"
      "@p bra WAIT_DONE;\n"
      "mov.u32 it, 0;\n"
      "WAIT_LOOP:\n"
      ".pragma \"nounroll\";\n"
      "mbarrier.try_wait.parity.shared::cta.b64 p, [%0], %1;\n"
      "@p bra WAIT_DONE;\n"
      "add.u32 it, it, 1;\n"
      "setp.lt.u32 p, it, 4194304;\n"
      "@p bra WAIT_LOOP;\n"
      "trap;\n"
      "WAIT_DONE:\n}\n" ::"r"(bar), "r"(parity) : "memory");
}
__device__ __forceinline__ bool mbar_try(uint32_t bar, uint32_t parity) {
  uint32_t ok;
  asm volatile("{\n.reg .pred p;\nmbarrier.test_wait.parity.shared::cta.b64 p, [%1], %2;\nselp.u32 %0, 1, 0, p;\n}\n"
               : "=r"(ok) : "r"(bar), "r"(parity) : "memory");
  return ok;
}
__device__ __forceinline__ void mbar_init(uint32_t bar, uint32_t count) {
  asm volatile("mbarrier.init.shared::cta.b64 [%0], %1;" ::"r"(bar), "r"(count) : "memory");
}
__device__ __forceinline__ void mbar_arrive(uint32_t bar) {
  asm volatile("mbarrier.arrive.shared::cta.b64 _, [%0];" ::"r"(bar) : "memory");
}
__device__ __forceinline__ void mbar_expect_tx(uint32_t bar, uint32_t bytes) {
  asm volatile("mbarrier.arrive.expect_tx.shared::cta.b64 _, [%0], %1;" ::"r"(bar), "r"(bytes) : "memory");
}
__device__ __forceinline__ void tma_load5(uint32_t dst, const CUtensorMap* map, uint32_t bar, int c0, int c1, int c2, int c3, int c4) {
  asm volatile("cp.async.bulk.tensor.5d.shared::cluster.global.mbarrier::complete_tx::bytes [%0], [%1, {%3,%4,%5,%6,%7}], [%2];"
               ::"r"(dst), "l"(map), "r"(bar), "r"(c0), "r"(c1), "r"(c2), "r"(c3), "r"(c4) : "memory");
}
__device__ __forceinline__ void bulk_load(uint32_t dst, const void* src, uint32_t bytes, uint32_t bar) {
  asm volatile("cp.async.bulk.shared::cluster.global.mbarrier::complete_tx::bytes [%0], [%1], %2, [%3];"
               ::"r"(dst), "l"(src), "r"(bytes), "r"(bar) : "memory");
}
template <int OFF>
__device__ __forceinline__ void st_async4(uint32_t cluster_addr, uint32_t cluster_bar, uint32_t a, uint32_t b, uint32_t c, uint32_t d) {
  asm volatile("st.async.shared::cluster.mbarrier::complete_tx::bytes.v4.b32 [%0+%6], {%2,%3,%4,%5}, [%1];"
               ::"r"(cluster_addr), "r"(cluster_bar), "r"(a), "r"(b), "r"(c), "r"(d), "n"(OFF) : "memory");
}
__device__ __forceinline__ void stsm4(uint32_t addr, uint32_t a, uint32_t b, uint32_t c, uint32_t d) {
  asm volatile("stmatrix.sync.aligned.m8n8.x4.shared.b16 [%0], {%1,%2,%3,%4};" ::"r"(addr), "r"(a), "r"(b), "r"(c), "r"(d) : "memory");
}
__device__ __forceinline__ uint32_t bfma(uint32_t a, uint32_t b, uint32_t c) {
  uint32_t d; asm volatile("fma.rn.bf16x2 %0, %1, %2, %3;" : "=r"(d) : "r"(a), "r"(b), "r"(c)); return d;
}
__device__ __forceinline__ void lds4(uint32_t (&r)[4], uint32_t addr) {
  asm volatile("ld.shared.v4.b32 {%0,%1,%2,%3}, [%4];" : "=r"(r[0]), "=r"(r[1]), "=r"(r[2]), "=r"(r[3]) : "r"(addr) : "memory");
}
__device__ __forceinline__ void sts4(uint32_t addr, const uint32_t (&r)[4]) {
  asm volatile("st.shared.v4.b32 [%0], {%1,%2,%3,%4};" ::"r"(addr), "r"(r[0]), "r"(r[1]), "r"(r[2]), "r"(r[3]) : "memory");
}
__device__ __forceinline__ void tma_store5(const CUtensorMap* map, uint32_t src, int c0, int c1, int c2, int c3, int c4) {
  asm volatile("cp.async.bulk.tensor.5d.global.shared::cta.bulk_group [%0, {%2,%3,%4,%5,%6}], [%1];"
               ::"l"(map), "r"(src), "r"(c0), "r"(c1), "r"(c2), "r"(c3), "r"(c4) : "memory");
  asm volatile("cp.async.bulk.commit_group;" ::: "memory");
}
__device__ __forceinline__ bool elect_one() {
  uint32_t p;
  asm volatile("{\n.reg .pred P;\nelect.sync _|P, 0xffffffff;\nselp.u32 %0, 1, 0, P;\n}\n" : "=r"(p));
  return p;
}
__device__ __forceinline__ uint32_t mapa(uint32_t addr, uint32_t rank) {
  uint32_t r; asm("mapa.shared::cluster.u32 %0, %1, %2;" : "=r"(r) : "r"(addr), "r"(rank)); return r;
}

__device__ __forceinline__ void tr_sum(uint32_t (&t)[3][4], const uint32_t (&U)[3][4], const uint32_t (&V)[3][4]) {
#pragma unroll
  for (int k = 0; k < 3; k++)
#pragma unroll
    for (int i = 0; i < 4; i++) t[k][i] = badd(U[k][i], V[k][i]);
}
__device__ __forceinline__ void tr_dif(uint32_t (&t)[3][4], const uint32_t (&U)[3][4], const uint32_t (&V)[3][4]) {
#pragma unroll
  for (int k = 0; k < 3; k++)
#pragma unroll
    for (int i = 0; i < 4; i++) t[k][i] = bsub(V[k][i], U[k][i]);
}
__device__ __forceinline__ void tr_t0(uint32_t (&t)[3][4], const uint32_t (&V)[3][4], const uint32_t (&E)[3][4]) {
#pragma unroll
  for (int k = 0; k < 3; k++) {
    t[k][0] = bsub(E[k][0], V[k][0]); t[k][1] = bsub(V[k][0], V[k][1]);
    t[k][2] = bsub(E[k][2], V[k][2]); t[k][3] = bsub(V[k][2], V[k][3]);
  }
}
__device__ __forceinline__ void tr_t3(uint32_t (&t)[3][4], const uint32_t (&U)[3][4], const uint32_t (&E)[3][4]) {
#pragma unroll
  for (int k = 0; k < 3; k++) {
    t[k][0] = bsub(U[k][1], U[k][0]); t[k][1] = bsub(E[k][1], U[k][1]);
    t[k][2] = bsub(U[k][3], U[k][2]); t[k][3] = bsub(E[k][3], U[k][3]);
  }
}
__device__ __forceinline__ void ld3(uint32_t (&R)[3][4], uint32_t aU, int off) {
#pragma unroll
  for (int k = 0; k < 3; k++) ldsm4(R[k], (aU ^ (32 * k)) + off);
}
template <int COMP, int AGE, int FIRST>
__device__ __forceinline__ void batch_(float (&acc)[48], const uint32_t (&t)[3][4], uint64_t bd) {
  constexpr int base = ((COMP * 3 + AGE) * 3) * BT_BYTES;
  wgmma96<FIRST ? 0 : 1>(acc, t[0], bd + ((base) >> 4));
  wgmma96<1>(acc, t[1], bd + ((base + BT_BYTES) >> 4));
  wgmma96<1>(acc, t[2], bd + ((base + 2 * BT_BYTES) >> 4));
  wg_commit();
}

template <int RANK, int I0, int I1>
__device__ __forceinline__ void butterfly(float (&X)[48], float (&Y)[48]) {
#pragma unroll
  for (int i = I0; i < I1; i++) {
    if (RANK == 0) asm volatile("sub.rn.f32 %0, %0, %1;\nfma.rn.f32 %1, %1, 0f40000000, %0;" : "+f"(X[i]), "+f"(Y[i]));
    else           asm volatile("add.rn.f32 %0, %0, %1;\nfma.rn.f32 %1, %1, 0fC0000000, %0;" : "+f"(X[i]), "+f"(Y[i]));
  }
}

#define DBG_T(c, idx)
#define DBG_TA(idx)
#define TL(c, k)
#define DBG_U(c, idx)
#define DBG_FLUSH(c)
#define DBG_G(c, idx)

struct Ctx {
  uint32_t aU, aE;
  uint32_t in_base;
  uint32_t bar_full;
  uint32_t bar_ready;
  uint32_t xaddr, xfull;
  uint32_t xbase;
  const CUtensorMap* omap;
  const CUtensorMap* map;
  const char* xseg;
  int wg, warp;
  int c0, u0, h0, hstep;
  int nrows;
  bool producer;
};

__device__ __forceinline__ void prefetch_row(const Ctx& c, int h) {
  if ((unsigned)h < (unsigned)IMG_H)
    asm volatile("cp.async.bulk.prefetch.L2.global [%0], %1;" ::"l"(c.xseg + (size_t)h * (IMG_W * CH * 2)), "r"(64 * CH * 2) : "memory");
}

template <int BUF, int C0, int C1>
__device__ __forceinline__ void load_partner(const Ctx& c, uint32_t (&P)[6][4]) {
#pragma unroll
  for (int ch = C0; ch < C1; ch++) lds4(P[ch], c.xaddr + BUF * XBUF_BYTES + (ch & 1) * 6144 + (ch >> 1) * 64);
}
template <int BUF, int C0, int C1>
__device__ __forceinline__ void finish_chunks(const Ctx& c, const float (&Y)[48], uint32_t (&P)[6][4]) {
#pragma unroll
  for (int ch = C0; ch < C1; ch++) {
    const int m = ch >> 1, s = ch & 1;
#pragma unroll
    for (int ss = 0; ss < 4; ss++) P[ch][ss] = badd(pack2(Y[16 * m + 4 * ss + 2 * s], Y[16 * m + 4 * ss + 2 * s + 1]), P[ch][ss]);
    sts4(c.xaddr + BUF * XBUF_BYTES + s * 6144 + m * 64, P[ch]);
  }
}
template <int RANK, int BUF, int CH0>
__device__ __forceinline__ void send_chunk(const Ctx& c, const float (&X)[48]) {
  constexpr uint32_t RDELTA = RANK ? 0xFF000000u : 0x01000000u;
  constexpr int m = CH0 >> 1, s = CH0 & 1;
  uint32_t o[4];
#pragma unroll
  for (int ss = 0; ss < 4; ss++) o[ss] = pack2(X[16 * m + 4 * ss + 2 * s], X[16 * m + 4 * ss + 2 * s + 1]);
  st_async4<BUF * XBUF_BYTES + s * 6144 + m * 64>(c.xaddr + RDELTA, c.xfull + BUF * 64 + RDELTA, o[0], o[1], o[2], o[3]);
}

#define SLOTV 0
#define FULLSKIP 3
#define LATE3 1
#define PF_START 2
#define R3POS 1
#define WI1 0x0f0901u
#define WI0 0x0d05u
#define WI0N 2
#define PF_DIST 1
#define RORD 0x654210
#define RORDS 0x6251
#define NOROW0 1

struct Regs {
  float X[48], Y[48];
  uint32_t T[4][2][3][4];
  uint32_t U[3][4], V[3][4], E[3][4];
  uint32_t Z[6][4], P[6][4];
};

template <int RANK, int OLD>
__device__ __forceinline__ void tma_slot(const Ctx& c, int n) {
  constexpr int MID = 1 - OLD;
  const int h = c.h0 + n * c.hstep;
  asm volatile("fence.proxy.async.shared::cta;" ::: "memory");
  asm volatile("bar.sync %0, 128;" ::"r"(2 + c.wg) : "memory");
  if (elect_one()) {
    if (c.warp < 2) {
      if (n + 2 < c.nrows) {
        mbar_expect_tx(c.bar_full + 8 * OLD, BOX_BYTES);
        tma_load5(c.in_base + OLD * STAGE_BYTES + c.warp * OFF_BOXB, c.map, c.bar_full + 8 * OLD, c.c0, 2 * c.warp, c.u0 - c.warp, 0,
                  h + 4 * c.hstep);
      } else {
        mbar_arrive(c.bar_full + 8 * OLD);
      }
    } else if (c.warp == 2) {
      if (OLD == 1 || n > 0) tma_store5(c.omap, c.xbase + MID * XBUF_BYTES, 0, c.u0, 0, RANK, h);
    } else {
      if (PF_DIST > 0 && n >= PF_START && n + 2 + PF_DIST < c.nrows) prefetch_row(c, h + (4 + PF_DIST) * c.hstep);
    }
  }
  __syncwarp();
}
template <int RANK, int OLD>
__device__ __forceinline__ void release_xbuf(const Ctx& c) {
  constexpr uint32_t RDELTA = RANK ? 0xFF000000u : 0x01000000u;
  asm volatile("cp.async.bulk.wait_group.read 0;" ::: "memory");
  asm volatile("{\n.reg .pred p, q;\nelect.sync _|q, 0xffffffff;\nsetp.eq.and.u32 p, %1, 2, q;\n@p mbarrier.arrive.shared::cluster.b64 _, [%0];\n}\n"
               ::"r"(c.bar_full + 8 * (1 - OLD) + RDELTA), "r"(c.warp) : "memory");
}
template <int C0, int C1>
__device__ __forceinline__ void pack_acc(uint32_t (&Z)[6][4], const float (&Y)[48]) {
#pragma unroll
  for (int ch = C0; ch < C1; ch++)
#pragma unroll
    for (int ss = 0; ss < 4; ss++) {
      const int i = 16 * (ch >> 1) + 4 * ss + 2 * (ch & 1);
      Z[ch][ss] = pack2(Y[i], Y[i + 1]);
    }
}
template <int BUF, int C0, int C1>
__device__ __forceinline__ void add_stage(const Ctx& c, uint32_t (&Z)[6][4], const uint32_t (&P)[6][4]) {
#pragma unroll
  for (int ch = C0; ch < C1; ch++)
#pragma unroll
    for (int ss = 0; ss < 4; ss++) Z[ch][ss] = badd(Z[ch][ss], P[ch][ss]);
#pragma unroll
  for (int ch = C0; ch < C1; ch++) sts4(c.xaddr + BUF * XBUF_BYTES + (ch & 1) * 6144 + (ch >> 1) * 64, Z[ch]);
}

__device__ __forceinline__ uint64_t get_bd(const Ctx& c, int n) {
  return BDESC;
}
#define G1  batch_<0, 0, 1>(r.X, r.T[0][OLD], bd);
#define G2  batch_<0, 1, 0>(r.X, r.T[0][MID], bd);
#define G3  batch_<0, 2, 0>(r.X, r.T[0][OLD], bd);
#define G4  batch_<1, 0, 1>(r.Y, r.T[1][OLD], bd);
#define G5  batch_<1, 1, 0>(r.Y, r.T[1][MID], bd);
#define G6  batch_<1, 2, 0>(r.Y, r.T[1][OLD], bd);
#define G7  if (OLD == 1 || !(FULLSKIP & 1)) batch_<2, 0, 0>(r.X, r.T[2][OLD], bd); else { if (!skip) { F batch_<2, 0, 0>(r.X, r.T[2][OLD], bd); } else { F wg_commit(); } F }
#define G8  batch_<2, 1, 0>(r.X, r.T[2][MID], bd);
#define G9  batch_<2, 2, 0>(r.X, r.T[2][OLD], bd);
#define G10 if (OLD == 1 || !(FULLSKIP & 2)) batch_<3, 0, 0>(r.Y, r.T[3][OLD], bd); else { if (!skip) { F batch_<3, 0, 0>(r.Y, r.T[3][OLD], bd); } else { F wg_commit(); } F }
#define G11 batch_<3, 1, 0>(r.Y, r.T[3][MID], bd);
#define G12 batch_<3, 2, 0>(r.Y, r.T[3][OLD], bd);
#define F   wg_fence();
#define W(k) wg_wait<k>();
#define PACK pack_acc<0, 6>(r.Z, r.Y);
#define PK(a, b) pack_acc<a, b>(r.Z, r.Y);
#define XW  mbar_wait(c.xfull + MID * 64, ((n - 1) >> 1) & 1); FIX3
#define ARM if (elect_one()) mbar_expect_tx(c.xfull + MID * 64, X_TX);
#define REL release_xbuf<RANK, OLD>(c);
#define LP(a, b) load_partner<MID, a, b>(c, r.P);
#define AS(a, b) add_stage<MID, a, b>(c, r.Z, r.P);
#define LV1 if (RANK == 0) ld3(r.V, c.aU, OLD * STAGE_BYTES + OFF_V); else ld3(r.U, c.aU, OLD * STAGE_BYTES);
#define LU1 if (RANK == 0) ld3(r.U, c.aU, OLD * STAGE_BYTES); else ld3(r.V, c.aU, OLD * STAGE_BYTES + OFF_V);
#define LU2 if (RANK == 0) ld3(r.U, c.aU, MID * STAGE_BYTES); else ld3(r.V, c.aU, MID * STAGE_BYTES + OFF_V);
#define LE  ld3(r.E, c.aE, OLD * STAGE_BYTES);
#define LEk(k)  ldsm4(r.E[k], (c.aE ^ (32 * k)) + OLD * STAGE_BYTES);
#define LV1k(k) if (RANK == 0) ldsm4(r.V[k], (c.aU ^ (32 * k)) + OLD * STAGE_BYTES + OFF_V); else ldsm4(r.U[k], (c.aU ^ (32 * k)) + OLD * STAGE_BYTES);
#define LV2k(k) if (RANK == 0) ldsm4(r.V[k], (c.aU ^ (32 * k)) + MID * STAGE_BYTES + OFF_V); else ldsm4(r.U[k], (c.aU ^ (32 * k)) + MID * STAGE_BYTES);
#define LU1k(k) if (RANK == 0) ldsm4(r.U[k], (c.aU ^ (32 * k)) + OLD * STAGE_BYTES); else ldsm4(r.V[k], (c.aU ^ (32 * k)) + OLD * STAGE_BYTES + OFF_V);
#define LU2k(k) if (RANK == 0) ldsm4(r.U[k], (c.aU ^ (32 * k)) + MID * STAGE_BYTES); else ldsm4(r.V[k], (c.aU ^ (32 * k)) + MID * STAGE_BYTES + OFF_V);
#define TRS tr_sum(r.T[0][OLD], r.U, r.V);
#define TRF tr_dif(r.T[1][OLD], r.U, r.V);
#define TRC if (RANK == 0) tr_t3(r.T[2][OLD], r.U, r.E); else tr_t0(r.T[2][OLD], r.V, r.E);
#define TRD if (RANK == 0) tr_t0(r.T[3][OLD], r.V, r.E); else tr_t3(r.T[3][OLD], r.U, r.E);
#define SLOT tma_slot<RANK, OLD>(c, n);
#define FW  if (OLD == 1) mbar_wait(c.bar_full, ((n + 2) >> 1) & 1); \
            else mbar_wait(n ? c.bar_full + 8 : c.bar_ready, n ? ((n + 3) >> 1) & 1 : 0);
#define FIX3 if (OLD == 1 && n == 1) { DBG_T(c, 36); mbar_wait(c.bar_full + 8, 1); DBG_T(c, 37); SCHED_FIX3 }
#define SND(k) send_chunk<RANK, OLD, k>(c, r.X);
#define SCHED1 F G1 G2 XW W(2) PK(0,1) ARM LP(0,1) PK(1,2) LP(1,2) LP(2,3) REL AS(0,1) PK(2,3) PK(3,4) PK(4,5) AS(1,2) LP(3,4) PK(5,6) LP(4,5) AS(2,3) LP(5,6) LV1k(0) LV1k(1) LV1k(2) F G4 G5 W(3) TRS F G3 AS(3,4) AS(4,5) W(2) TRF LEk(0) LEk(1) LEk(2) AS(5,6) F G6 SLOT
#define SCHED1_FIRST LEk(0) LEk(1) LEk(2) SLOT
#define SCHED_FIX3 LU1k(0) LU1k(1) LU1k(2)
#define SCHED2 F G7 G8 FW W(1) TRC LU2k(0) F G9 LU2k(1) LU2k(2) F G10 W(1) SND(0) SND(1) SND(2) F G11 SND(3) W(1) TRD SND(4) SND(5) F G12

__device__ __forceinline__ void load_row3(const Ctx& c) {
  mbar_expect_tx(c.bar_full + 8, BOX_BYTES);
  tma_load5(c.in_base + STAGE_BYTES + c.warp * OFF_BOXB, c.map, c.bar_full + 8, c.c0, 2 * c.warp, c.u0 - c.warp, 0, c.h0 + 3 * c.hstep);
}
template <int RANK, int OLD, bool FIRST>
__device__ __forceinline__ void phase1(const Ctx& c, int n, Regs& r) {
  constexpr int MID = 1 - OLD;
  const uint64_t bd = get_bd(c, n);
  if (FIRST) {
    wg_fence();
    batch_<0, 1, 1>(r.X, r.T[0][MID], bd);
    batch_<1, 1, 1>(r.Y, r.T[1][MID], bd);
    if ((unsigned)c.h0 < (unsigned)IMG_H) {
      wg_fence();
      batch_<0, 0, 0>(r.X, r.T[0][OLD], bd);
      batch_<1, 0, 0>(r.Y, r.T[1][OLD], bd);
    }
    DBG_T(c, 47);
    mbar_wait(c.bar_full + 8 * OLD, 0);
    DBG_T(c, 48);
    if (R3POS == 1) { if (c.warp < 2 && elect_one()) load_row3(c); __syncwarp(); }
    LU1 LV1 W(1) TRS F G3 W(1) TRF F G6
    if (R3POS == 2) { if (c.warp < 2 && elect_one()) load_row3(c); __syncwarp(); }
    SCHED1_FIRST
  } else {
    SCHED1
  }
  wg_wait<0>();
  DBG_U(c, 4 + n);
}

template <int RANK, int OLD>
__device__ __forceinline__ void phase2(const Ctx& c, int n, Regs& r) {
  constexpr int MID = 1 - OLD;
  const uint64_t bd = get_bd(c, n);
  butterfly<RANK, 0, 48>(r.X, r.Y);
  const bool skip = (unsigned)(c.h0 + n * c.hstep) >= (unsigned)IMG_H;
  SCHED2
}

template <int RANK, int BUF>
__device__ __forceinline__ void finish_strip(const Ctx& c, Regs& r) {
  DBG_T(c, 35);
  uint32_t P[6][4];
  mbar_wait(c.xfull + BUF * 64, ((c.nrows - 1) >> 1) & 1);
  load_partner<BUF, 0, 6>(c, P);
  wg_wait<0>();
  finish_chunks<BUF, 0, 6>(c, r.Y, P);
  asm volatile("fence.proxy.async.shared::cta;" ::: "memory");
  asm volatile("bar.sync %0, 128;" ::"r"(2 + c.wg) : "memory");
  if (c.warp == 2 && elect_one()) {
    tma_store5(c.omap, c.xbase + BUF * XBUF_BYTES, 0, c.u0, 0, RANK, c.h0 + c.nrows * c.hstep);
    asm volatile("cp.async.bulk.wait_group.read 0;" ::: "memory");
  }
  DBG_T(c, 40); DBG_G(c, 1);
  DBG_FLUSH(c);
}

template <int RANK>
__device__ __forceinline__ void run_strip(const Ctx& c, uint32_t row0_off, uint32_t bar_row0) {
  Regs r;
#pragma unroll
  for (int m = 0; m < 2; m++) {
    const uint32_t off = m ? STAGE_BYTES : row0_off;
    mbar_wait(m ? c.bar_full + 8 : bar_row0, 0);
    DBG_T(c, 50 + m);
    ld3(r.U, c.aU, off);
    ld3(r.V, c.aU, off + OFF_V);
    ld3(r.E, c.aE, off);
    tr_sum(r.T[0][m], r.U, r.V);
    tr_dif(r.T[1][m], r.U, r.V);
    tr_t3(r.T[RANK == 0 ? 2 : 3][m], r.U, r.E);
    tr_t0(r.T[RANK == 0 ? 3 : 2][m], r.V, r.E);
  }
  asm volatile("bar.sync %0, 128;" ::"r"(2 + c.wg) : "memory");
  asm volatile("barrier.cluster.wait.aligned;" ::: "memory");
  if (elect_one()) {
    if (c.warp < 2) {
      if (R3POS == 0) load_row3(c);
    } else if (c.warp == 2) {
      asm volatile("mbarrier.arrive.shared::cluster.b64 _, [%0];" ::"r"(c.bar_ready ^ 0x01000000u) : "memory");
    } else {
      mbar_arrive(c.bar_full + 8);
    }
  }
  __syncwarp();
  DBG_T(c, 46);
  mbar_wait(SMEM_BASE + (RANK << 24) + OFF_BAR + 8 * BAR_W + 24, 0);
  DBG_T(c, 3);
#pragma unroll
  for (int i = 0; i < 48; i++) { r.X[i] = 0.f; r.Y[i] = 0.f; r.Z[i % 6][i / 12] = 0; r.P[i % 6][i / 12] = 0; }
  phase1<RANK, 0, true>(c, 0, r);
  DBG_T(c, 52);
  if (!LATE3) mbar_wait(c.bar_ready, 0);
#pragma unroll 1
  for (int n = 0;; n += 2) {
    phase2<RANK, 0>(c, n, r);
    if (n + 1 == c.nrows) { finish_strip<RANK, 0>(c, r); break; }
    phase1<RANK, 1, false>(c, n + 1, r);
    phase2<RANK, 1>(c, n + 1, r);
    if (n + 2 == c.nrows) { finish_strip<RANK, 1>(c, r); break; }
    phase1<RANK, 0, false>(c, n + 2, r);
  }
}

constexpr int NCL = 66;
struct Strip { int seg, h0, nrows; };
__device__ __forceinline__ bool is_down(int cl) { return cl < 2 || !((cl - 2) & 4); }
__device__ __forceinline__ Strip get_strip(int cl, int wg) {
  const int k = cl - 2, i = k >> 2;
  const int q = (i & 1) ? (wg ? 16 + 15 * i : 16 * i + 16) : (wg ? 30 + 15 * i : 16 * i - 1);
  return cl < 2 ? Strip{2 * cl + wg, -1, 16} : Strip{k & 3, 2 * q + wg, 16 - wg};
}

__global__ void __cluster_dims__(2, 1, 1) __launch_bounds__(256, 1)
dilated_conv_wino_kernel(const __grid_constant__ CUtensorMap xmap, const __grid_constant__ CUtensorMap omap,
                         const __nv_bfloat16* __restrict__ x, const __nv_bfloat16* __restrict__ w) {
  extern __shared__ uint8_t smem_raw[];
  const int tid = threadIdx.x;
  const int w8 = __shfl_sync(0xffffffff, tid >> 5, 0);
  const int wg = w8 >> 2, warp = w8 & 3;
  const int lane = tid & 31;
  const int rank = blockIdx.x & 1;
  const int cl = blockIdx.x >> 1;
  const bool down = is_down(cl);
  const uint32_t sbase = SMEM_BASE + (rank << 24);
  const uint32_t b0 = sbase + OFF_BAR;
  const uint32_t bar_w = b0 + 8 * BAR_W;
  const uint32_t o_w0 = (rank ? 2 : 3) * 9 * BT_BYTES, o_w2 = (rank ? 3 : 2) * 9 * BT_BYTES;
  Ctx c;
  c.producer = (tid & 127) == 0;
  DBG_G(c, 0); DBG_T(c, 0);

  if (w8 >= 5) {
    if (elect_one()) {
      const int a = w8 - 5, i = down ? a : 2 - a;
      const char* src = reinterpret_cast<const char*>(w) + (uint32_t)((i * 6 + rank) * (3 * BT_BYTES));
      const uint32_t dst = sbase + OFF_W + a * 3 * BT_BYTES;
      mbar_init(bar_w + 8 * a, 1);
      mbar_expect_tx(bar_w + 8 * a, 9 * BT_BYTES);
      bulk_load(dst + o_w0, src, 3 * BT_BYTES, bar_w + 8 * a);
      bulk_load(dst, src + 6 * BT_BYTES, 3 * BT_BYTES, bar_w + 8 * a);
      bulk_load(dst + o_w2, src + 12 * BT_BYTES, 3 * BT_BYTES, bar_w + 8 * a);
      DBG_TA(53);
    }
  } else if (elect_one()) {
    if (w8 < 4) {
      mbar_init(b0 + 8 * w8, 3);
#pragma unroll
      for (int q = 0; q < 4; q++) mbar_init(b0 + 8 * (BAR_XFULL + 4 * w8 + q), 1);
      mbar_expect_tx(b0 + 8 * w8, 2 * BOX_BYTES);
      asm volatile("mbarrier.arrive.shared::cta.b64 _, [%0], 2;" ::"r"(b0 + 8 * w8) : "memory");
    } else {
      asm volatile("prefetch.tensormap [%0];" ::"l"(&xmap) : "memory");
#pragma unroll
      for (int q = 0; q < 2; q++) {
        mbar_init(b0 + 8 * (BAR_ROW0 + q), 1);
        mbar_init(b0 + 8 * (BAR_READY + q), 1);
      }
      mbar_init(bar_w + 24, 8);
#pragma unroll
      for (int q = 0; q < 2; q++) mbar_expect_tx(b0 + 8 * (BAR_ROW0 + q), 2 * BOX_BYTES);
    }
    asm volatile("fence.mbarrier_init.release.cluster;" ::: "memory");
  }
  DBG_T(c, 45);
  __syncthreads();
  asm volatile("barrier.cluster.arrive.relaxed.aligned;" ::: "memory");
  DBG_T(c, 41);
  const Strip s0 = get_strip(cl, 0), s1 = get_strip(cl, 1);
  c.map = &xmap;
  c.omap = &omap;
  c.wg = wg;
  c.warp = warp;
  c.in_base = sbase + OFF_IN + wg * WG_IN_BYTES;
  c.bar_full = b0 + 8 * (BAR_FULL + wg * NSTAGE);
  c.bar_ready = b0 + 8 * (BAR_READY + wg);
  c.c0 = rank * 48;
  c.u0 = (wg ? s1.seg : s0.seg) * 16;
  c.h0 = wg ? s1.h0 : s0.h0;
  c.hstep = down ? 2 : -2;
  c.nrows = wg ? s1.nrows : s0.nrows;
  c.xfull = b0 + 8 * (BAR_XFULL + w8);
  c.xseg = reinterpret_cast<const char*>(x) + (c.u0 * 8 + rank * 64) * (CH * 2);
  if (warp == 3) {
    if (elect_one()) {
#pragma unroll 1
      for (uint32_t order = cl < 2 ? RORDS : RORD; order; order >>= 4) {
        const int g = (order >> 2) & 1, m = order & 3;
        const uint32_t dst = m == 0 ? sbase + (g ? OFF_ROW0_1 : OFF_ROW0_0) : sbase + OFF_IN + g * WG_IN_BYTES + (m & 1) * STAGE_BYTES;
        const uint32_t bar = b0 + 8 * (m == 0 ? BAR_ROW0 + g : BAR_FULL + 2 * g + (m & 1));
        tma_load5(dst + wg * OFF_BOXB, &xmap, bar, c.c0, 2 * wg, (g ? s1.seg : s0.seg) * 16 - wg, 0, (g ? s1.h0 : s0.h0) + m * c.hstep);
      }
      asm volatile("prefetch.tensormap [%0];" ::"l"(&omap) : "memory");
      DBG_TA(49);
    }
    __syncwarp();
  }
  if ((uint32_t)__cvta_generic_to_shared(smem_raw) != sbase || mapa(sbase, rank ^ 1) != (sbase ^ 0x01000000u)) __trap();
  if (elect_one()) { mbar_expect_tx(c.xfull, X_TX); mbar_expect_tx(c.xfull + 64, X_TX); }
  {
    const int g = lane & 7, mi = lane >> 3;
    const int rU = 8 * warp + g + ((mi & 1) ? 34 : 0);
    const int rE = 8 * warp + g + ((mi & 1) ? 2 : 70 + 34);
    const uint32_t pU = c.in_base + rU * 128, pE = c.in_base + rE * 128;
    c.aU = pU + (((mi >> 1) ^ ((pU >> 7) & 7)) << 4);
    c.aE = pE + (((mi >> 1) ^ ((pE >> 7) & 7)) << 4);
  }
  c.xbase = sbase + OFF_X + wg * 2 * XBUF_BYTES;
  c.xaddr = c.xbase + (warp * 8 + (lane >> 2)) * 192 + (lane & 3) * 16;

#pragma unroll 1
  for (uint32_t items = wg ? WI1 + warp * 0x010101u : warp < WI0N ? WI0 + warp * 0x0101u : (WI0 & 255) + warp; items; items >>= 8) {
    const int item = (items & 255) - 1;
    if (item >= 18) break;
    const uint32_t base = sbase + OFF_W + item * 1536;
    mbar_wait(bar_w + 8 * (item / 6), 0);
    uint32_t wa[3][4], wb[3][4], wd[3][4];
    const uint32_t src = base + (lane >> 2) * 192 + (lane & 3) * 16;
#pragma unroll
    for (int m = 0; m < 3; m++) lds4(wa[m], src + o_w0 + m * 64);
#pragma unroll
    for (int m = 0; m < 3; m++) lds4(wd[m], src + o_w2 + m * 64);
#pragma unroll
    for (int m = 0; m < 3; m++) lds4(wb[m], src + m * 64);
    __syncwarp();
    const uint32_t dst = base + lane * 16;
#pragma unroll
    for (int m = 0; m < 3; m++) stsm4(dst + m * 512 + o_w0, wa[m][0], wa[m][1], wa[m][2], wa[m][3]);
#pragma unroll
    for (int m = 0; m < 3; m++) stsm4(dst + m * 512 + o_w2, wd[m][0], wd[m][1], wd[m][2], wd[m][3]);
#pragma unroll
    for (int m = 0; m < 3; m++) {
      uint32_t g1[4], g2[4];
#pragma unroll
      for (int ss = 0; ss < 4; ss++) {
        const uint32_t a = wa[m][ss], b = wb[m][ss], d = wd[m][ss];
        const float slo = 0.5f * (bf_lo(a) + bf_lo(d)), shi = 0.5f * (bf_hi(a) + bf_hi(d));
        const float blo = bf_lo(b), bhi = bf_hi(b);
        g1[ss] = pack2(fmaf(blo, 0.5f, slo), fmaf(bhi, 0.5f, shi));
        g2[ss] = pack2(fmaf(blo, -0.5f, slo), fmaf(bhi, -0.5f, shi));
      }
      stsm4(dst + m * 512, g1[0], g1[1], g1[2], g1[3]);
      stsm4(dst + m * 512 + 9 * BT_BYTES, g2[0], g2[1], g2[2], g2[3]);
    }
  }
  asm volatile("fence.proxy.async.shared::cta;" ::: "memory");
  __syncwarp();
  if (elect_one()) mbar_arrive(bar_w + 24);
  DBG_T(c, 1);

  const uint32_t row0_off = sbase + (wg ? OFF_ROW0_1 : OFF_ROW0_0) - c.in_base;
  const uint32_t bar_row0 = NOROW0 && cl < 2 ? bar_w : b0 + 8 * (BAR_ROW0 + wg);
  if (rank == 0) run_strip<0>(c, row0_off, bar_row0); else run_strip<1>(c, row0_off, bar_row0);
}

typedef CUresult (*EncodeTiledFn)(CUtensorMap*, CUtensorMapDataType, cuuint32_t, void*, const cuuint64_t*, const cuuint64_t*,
                                  const cuuint32_t*, const cuuint32_t*, CUtensorMapInterleave, CUtensorMapSwizzle,
                                  CUtensorMapL2promotion, CUtensorMapFloatOOBfill);

}

extern "C" void kernel_launch(void* const* d_in, const int* in_sizes, int n_in, void* d_out, int out_size) {
  (void)in_sizes; (void)n_in; (void)out_size;
  static EncodeTiledFn encode = nullptr;
  if (!encode) {
    void* fn = nullptr;
    cudaDriverEntryPointQueryResult qr;
    cudaGetDriverEntryPoint("cuTensorMapEncodeTiled", &fn, cudaEnableDefault, &qr);
    encode = (EncodeTiledFn)fn;
    cudaFuncSetAttribute(dilated_conv_wino_kernel, cudaFuncAttributeMaxDynamicSharedMemorySize, SMEM_BYTES);
  }
  CUtensorMap xmap;
  const cuuint64_t dims[5] = {CH, 4, IMG_W / 8, 2, IMG_H};
  const cuuint64_t strides[4] = {CH * 2, 8 * CH * 2, 4 * CH * 2, IMG_W * CH * 2};
  const cuuint32_t box[5] = {48, 2, 17, 2, 1};
  const cuuint32_t estr[5] = {1, 1, 1, 1, 1};
#define PROMO CU_TENSOR_MAP_L2_PROMOTION_L2_128B
  encode(&xmap, CU_TENSOR_MAP_DATA_TYPE_BFLOAT16, 5, d_in[0], dims, strides, box, estr, CU_TENSOR_MAP_INTERLEAVE_NONE,
         CU_TENSOR_MAP_SWIZZLE_128B, PROMO, CU_TENSOR_MAP_FLOAT_OOB_FILL_NONE);
  CUtensorMap omap;
  const cuuint64_t odims[5] = {2 * CH, IMG_W / 8, 2, 2, IMG_H};
  const cuuint64_t ostrides[4] = {8 * CH * 2, 4 * CH * 2, 2 * CH * 2, IMG_W * CH * 2};
  const cuuint32_t obox[5] = {2 * CH, 16, 2, 1, 1};
  encode(&omap, CU_TENSOR_MAP_DATA_TYPE_BFLOAT16, 5, d_out, odims, ostrides, obox, estr, CU_TENSOR_MAP_INTERLEAVE_NONE,
         CU_TENSOR_MAP_SWIZZLE_NONE, CU_TENSOR_MAP_L2_PROMOTION_NONE, CU_TENSOR_MAP_FLOAT_OOB_FILL_NONE);
  dilated_conv_wino_kernel<<<2 * NCL, 256, SMEM_BYTES>>>(xmap, omap, (const __nv_bfloat16*)d_in[0], (const __nv_bfloat16*)d_in[1]);
}
```

```cpp
#include <cuda_runtime.h>
#include <cuda_bf16.h>
#include <cuda.h>
#include <stdint.h>

namespace {

constexpr int IMG_H = 512, IMG_W = 512, CH = 96;
constexpr int NSTAGE = 2;

constexpr int BT_BYTES   = 3072;
constexpr int W_BYTES    = 36 * BT_BYTES;
constexpr int BOX_BYTES  = 68 * 96;
constexpr int OFF_BOXB   = 70 * 128;
constexpr int STAGE_BYTES = 144 * 128;
constexpr int OFF_V      = 72 * 128;
constexpr int WG_IN_BYTES = STAGE_BYTES + 138 * 128;
constexpr int OFF_W      = 0;
constexpr int OFF_IN     = OFF_W + W_BYTES;
constexpr int OFF_X      = OFF_IN + 2 * WG_IN_BYTES;
constexpr int X_BYTES    = 3072;
constexpr int XBUF_BYTES = 4 * X_BYTES;
constexpr int SMEM_BYTES = OFF_X + 4 * XBUF_BYTES;
constexpr int OFF_ROW0_0 = OFF_X + ((OFF_IN - OFF_X) & 1023);
constexpr int OFF_ROW0_1 = OFF_X + 2 * XBUF_BYTES + ((OFF_IN + WG_IN_BYTES - OFF_X) & 1023);
constexpr int OFF_BAR    = OFF_IN + 68 * 128;
constexpr int BAR_FULL = 0, BAR_XFULL = 8, BAR_W = 24, BAR_ROW0 = 28, BAR_READY = 30;
static_assert(SMEM_BYTES <= 232448, "shared memory");
constexpr uint32_t SMEM_BASE = 1024;
constexpr uint64_t BDESC = (uint64_t)((SMEM_BASE + OFF_W) >> 4) | ((uint64_t)(1536 >> 4) << 16) | ((uint64_t)(128 >> 4) << 32);

__device__ __forceinline__ void wg_fence()  { asm volatile("wgmma.fence.sync.aligned;" ::: "memory"); }
__device__ __forceinline__ void wg_commit() { asm volatile("wgmma.commit_group.sync.aligned;" ::: "memory"); }
template <int N> __device__ __forceinline__ void wg_wait() { asm volatile("wgmma.wait_group.sync.aligned %0;" ::"n"(N) : "memory"); }

template <int SCALE_D>
__device__ __forceinline__ void wgmma96(float (&d)[48], const uint32_t (&a)[4], uint64_t DESC) {
  asm volatile(
      "{\n.reg .pred p;\nsetp.ne.b32 p, %53, 0;\n"
      "wgmma.mma_async.sync.aligned.m64n96k16.f32.bf16.bf16 "
      "{%0,%1,%2,%3,%4,%5,%6,%7,%8,%9,%10,%11,%12,%13,%14,%15,%16,%17,%18,%19,%20,%21,%22,%23,"
      "%24,%25,%26,%27,%28,%29,%30,%31,%32,%33,%34,%35,%36,%37,%38,%39,%40,%41,%42,%43,%44,%45,%46,%47}, "
      "{%48,%49,%50,%51}, %52, p, 1, 1, 1;\n}\n"
      : "+f"(d[0]), "+f"(d[1]), "+f"(d[2]), "+f"(d[3]), "+f"(d[4]), "+f"(d[5]), "+f"(d[6]), "+f"(d[7]),
        "+f"(d[8]), "+f"(d[9]), "+f"(d[10]), "+f"(d[11]), "+f"(d[12]), "+f"(d[13]), "+f"(d[14]), "+f"(d[15]),
        "+f"(d[16]), "+f"(d[17]), "+f"(d[18]), "+f"(d[19]), "+f"(d[20]), "+f"(d[21]), "+f"(d[22]), "+f"(d[23]),
        "+f"(d[24]), "+f"(d[25]), "+f"(d[26]), "+f"(d[27]), "+f"(d[28]), "+f"(d[29]), "+f"(d[30]), "+f"(d[31]),
        "+f"(d[32]), "+f"(d[33]), "+f"(d[34]), "+f"(d[35]), "+f"(d[36]), "+f"(d[37]), "+f"(d[38]), "+f"(d[39]),
        "+f"(d[40]), "+f"(d[41]), "+f"(d[42]), "+f"(d[43]), "+f"(d[44]), "+f"(d[45]), "+f"(d[46]), "+f"(d[47])
      : "r"(a[0]), "r"(a[1]), "r"(a[2]), "r"(a[3]), "l"(DESC), "n"(SCALE_D));
}

__device__ __forceinline__ void ldsm4(uint32_t (&r)[4], uint32_t addr) {
  asm volatile("ldmatrix.sync.aligned.m8n8.x4.shared.b16 {%0,%1,%2,%3}, [%4];"
               : "=r"(r[0]), "=r"(r[1]), "=r"(r[2]), "=r"(r[3]) : "r"(addr) : "memory");
}
__device__ __forceinline__ uint32_t badd(uint32_t a, uint32_t b) {
  uint32_t d; asm volatile("add.rn.bf16x2 %0, %1, %2;" : "=r"(d) : "r"(a), "r"(b)); return d;
}
__device__ __forceinline__ uint32_t bsub(uint32_t a, uint32_t b) {
  uint32_t d; asm volatile("sub.rn.bf16x2 %0, %1, %2;" : "=r"(d) : "r"(a), "r"(b)); return d;
}
__device__ __forceinline__ float bf_lo(uint32_t v) {
  return __uint_as_float(v << 16);
}
__device__ __forceinline__ float bf_hi(uint32_t v) { return __uint_as_float(v & 0xffff0000u); }
__device__ __forceinline__ uint32_t pack2(float lo, float hi) {
  uint32_t d; asm volatile("cvt.rn.bf16x2.f32 %0, %1, %2;" : "=r"(d) : "f"(hi), "f"(lo)); return d;
}

__device__ __forceinline__ void mbar_wait(uint32_t bar, uint32_t parity) {
  asm volatile(
      "{\n.reg .pred p;\n.reg .u32 it;\n"
      "mbarrier.try_wait.parity.shared::cta.b64 p, [%0], %1;\n"
      "@p bra WAIT_DONE;\n"
      "mov.u32 it, 0;\n"
      "WAIT_LOOP:\n"
      ".pragma \"nounroll\";\n"
      "mbarrier.try_wait.parity.shared::cta.b64 p, [%0], %1;\n"
      "@p bra WAIT_DONE;\n"
      "add.u32 it, it, 1;\n"
      "setp.lt.u32 p, it, 4194304;\n"
      "@p bra WAIT_LOOP;\n"
      "trap;\n"
      "WAIT_DONE:\n}\n" ::"r"(bar), "r"(parity) : "memory");
}
__device__ __forceinline__ void mbar_init(uint32_t bar, uint32_t count) {
  asm volatile("mbarrier.init.shared::cta.b64 [%0], %1;" ::"r"(bar), "r"(count) : "memory");
}
__device__ __forceinline__ void mbar_arrive(uint32_t bar) {
  asm volatile("mbarrier.arrive.shared::cta.b64 _, [%0];" ::"r"(bar) : "memory");
}
__device__ __forceinline__ void mbar_expect_tx(uint32_t bar, uint32_t bytes) {
  asm volatile("mbarrier.arrive.expect_tx.shared::cta.b64 _, [%0], %1;" ::"r"(bar), "r"(bytes) : "memory");
}
__device__ __forceinline__ void tma_load5(uint32_t dst, const CUtensorMap* map, uint32_t bar, int c0, int c1, int c2, int c3, int c4) {
  asm volatile("cp.async.bulk.tensor.5d.shared::cluster.global.mbarrier::complete_tx::bytes [%0], [%1, {%3,%4,%5,%6,%7}], [%2];"
               ::"r"(dst), "l"(map), "r"(bar), "r"(c0), "r"(c1), "r"(c2), "r"(c3), "r"(c4) : "memory");
}
__device__ __forceinline__ void bulk_load(uint32_t dst, const void* src, uint32_t bytes, uint32_t bar) {
  asm volatile("cp.async.bulk.shared::cluster.global.mbarrier::complete_tx::bytes [%0], [%1], %2, [%3];"
               ::"r"(dst), "l"(src), "r"(bytes), "r"(bar) : "memory");
}
template <int OFF>
__device__ __forceinline__ void st_async4(uint32_t cluster_addr, uint32_t cluster_bar, uint32_t a, uint32_t b, uint32_t c, uint32_t d) {
  asm volatile("st.async.shared::cluster.mbarrier::complete_tx::bytes.v4.b32 [%0+%6], {%2,%3,%4,%5}, [%1];"
               ::"r"(cluster_addr), "r"(cluster_bar), "r"(a), "r"(b), "r"(c), "r"(d), "n"(OFF) : "memory");
}
__device__ __forceinline__ void stsm4(uint32_t addr, uint32_t a, uint32_t b, uint32_t c, uint32_t d) {
  asm volatile("stmatrix.sync.aligned.m8n8.x4.shared.b16 [%0], {%1,%2,%3,%4};" ::"r"(addr), "r"(a), "r"(b), "r"(c), "r"(d) : "memory");
}
__device__ __forceinline__ void lds4(uint32_t (&r)[4], uint32_t addr) {
  asm volatile("ld.shared.v4.b32 {%0,%1,%2,%3}, [%4];" : "=r"(r[0]), "=r"(r[1]), "=r"(r[2]), "=r"(r[3]) : "r"(addr) : "memory");
}
__device__ __forceinline__ void sts4(uint32_t addr, const uint32_t (&r)[4]) {
  asm volatile("st.shared.v4.b32 [%0], {%1,%2,%3,%4};" ::"r"(addr), "r"(r[0]), "r"(r[1]), "r"(r[2]), "r"(r[3]) : "memory");
}
__device__ __forceinline__ void tma_store5(const CUtensorMap* map, uint32_t src, int c0, int c1, int c2, int c3, int c4) {
  asm volatile("cp.async.bulk.tensor.5d.global.shared::cta.bulk_group [%0, {%2,%3,%4,%5,%6}], [%1];"
               ::"l"(map), "r"(src), "r"(c0), "r"(c1), "r"(c2), "r"(c3), "r"(c4) : "memory");
  asm volatile("cp.async.bulk.commit_group;" ::: "memory");
}
__device__ __forceinline__ bool elect_one() {
  uint32_t p;
  asm volatile("{\n.reg .pred P;\nelect.sync _|P, 0xffffffff;\nselp.u32 %0, 1, 0, P;\n}\n" : "=r"(p));
  return p;
}
__device__ __forceinline__ uint32_t mapa(uint32_t addr, uint32_t rank) {
  uint32_t r; asm("mapa.shared::cluster.u32 %0, %1, %2;" : "=r"(r) : "r"(addr), "r"(rank)); return r;
}

__device__ __forceinline__ void tr_sum(uint32_t (&t)[3][4], const uint32_t (&U)[3][4], const uint32_t (&V)[3][4]) {
#pragma unroll
  for (int k = 0; k < 3; k++)
#pragma unroll
    for (int i = 0; i < 4; i++) t[k][i] = badd(U[k][i], V[k][i]);
}
__device__ __forceinline__ void tr_dif(uint32_t (&t)[3][4], const uint32_t (&U)[3][4], const uint32_t (&V)[3][4]) {
#pragma unroll
  for (int k = 0; k < 3; k++)
#pragma unroll
    for (int i = 0; i < 4; i++) t[k][i] = bsub(V[k][i], U[k][i]);
}
__device__ __forceinline__ void tr_t0(uint32_t (&t)[3][4], const uint32_t (&V)[3][4], const uint32_t (&E)[3][4]) {
#pragma unroll
  for (int k = 0; k < 3; k++) {
    t[k][0] = bsub(E[k][0], V[k][0]); t[k][1] = bsub(V[k][0], V[k][1]);
    t[k][2] = bsub(E[k][2], V[k][2]); t[k][3] = bsub(V[k][2], V[k][3]);
  }
}
__device__ __forceinline__ void tr_t3(uint32_t (&t)[3][4], const uint32_t (&U)[3][4], const uint32_t (&E)[3][4]) {
#pragma unroll
  for (int k = 0; k < 3; k++) {
    t[k][0] = bsub(U[k][1], U[k][0]); t[k][1] = bsub(E[k][1], U[k][1]);
    t[k][2] = bsub(U[k][3], U[k][2]); t[k][3] = bsub(E[k][3], U[k][3]);
  }
}
__device__ __forceinline__ void ld3(uint32_t (&R)[3][4], uint32_t aU, int off) {
#pragma unroll
  for (int k = 0; k < 3; k++) ldsm4(R[k], (aU ^ (32 * k)) + off);
}
template <int COMP, int AGE, int FIRST>
__device__ __forceinline__ void batch_(float (&acc)[48], const uint32_t (&t)[3][4], uint64_t bd) {
  constexpr int base = ((COMP * 3 + AGE) * 3) * BT_BYTES;
  wgmma96<FIRST ? 0 : 1>(acc, t[0], bd + ((base) >> 4));
  wgmma96<1>(acc, t[1], bd + ((base + BT_BYTES) >> 4));
  wgmma96<1>(acc, t[2], bd + ((base + 2 * BT_BYTES) >> 4));
  wg_commit();
}

template <int RANK, int I0, int I1>
__device__ __forceinline__ void butterfly(float (&X)[48], float (&Y)[48]) {
#pragma unroll
  for (int i = I0; i < I1; i++) {
    if (RANK == 0) asm volatile("sub.rn.f32 %0, %0, %1;\nfma.rn.f32 %1, %1, 0f40000000, %0;" : "+f"(X[i]), "+f"(Y[i]));
    else           asm volatile("add.rn.f32 %0, %0, %1;\nfma.rn.f32 %1, %1, 0fC0000000, %0;" : "+f"(X[i]), "+f"(Y[i]));
  }
}

struct Ctx {
  uint32_t aU, aE;
  uint32_t in_base;
  uint32_t bar_full;
  uint32_t bar_ready;
  uint32_t xaddr, xfull;
  uint32_t xbase;
  const CUtensorMap* omap;
  const CUtensorMap* map;
  const char* xseg;
  int wg, warp;
  int c0, u0, h0, hstep;
  int nrows;
};

__device__ __forceinline__ void prefetch_row(const Ctx& c, int h) {
  if ((unsigned)h < (unsigned)IMG_H)
    asm volatile("cp.async.bulk.prefetch.L2.global [%0], %1;" ::"l"(c.xseg + (size_t)h * (IMG_W * CH * 2)), "r"(64 * CH * 2) : "memory");
}

template <int BUF, int C0, int C1>
__device__ __forceinline__ void load_partner(const Ctx& c, uint32_t (&P)[6][4]) {
#pragma unroll
  for (int ch = C0; ch < C1; ch++) lds4(P[ch], c.xaddr + BUF * XBUF_BYTES + (ch & 1) * 6144 + (ch >> 1) * 64);
}
template <int BUF, int C0, int C1>
__device__ __forceinline__ void finish_chunks(const Ctx& c, const float (&Y)[48], uint32_t (&P)[6][4]) {
#pragma unroll
  for (int ch = C0; ch < C1; ch++) {
    const int m = ch >> 1, s = ch & 1;
#pragma unroll
    for (int ss = 0; ss < 4; ss++) P[ch][ss] = badd(pack2(Y[16 * m + 4 * ss + 2 * s], Y[16 * m + 4 * ss + 2 * s + 1]), P[ch][ss]);
    sts4(c.xaddr + BUF * XBUF_BYTES + s * 6144 + m * 64, P[ch]);
  }
}
template <int RANK, int BUF, int CH0>
__device__ __forceinline__ void send_chunk(const Ctx& c, const float (&X)[48]) {
  constexpr uint32_t RDELTA = RANK ? 0xFF000000u : 0x01000000u;
  constexpr int m = CH0 >> 1, s = CH0 & 1;
  uint32_t o[4];
#pragma unroll
  for (int ss = 0; ss < 4; ss++) o[ss] = pack2(X[16 * m + 4 * ss + 2 * s], X[16 * m + 4 * ss + 2 * s + 1]);
  st_async4<BUF * XBUF_BYTES + s * 6144 + m * 64>(c.xaddr + RDELTA, c.xfull + BUF * 64 + RDELTA, o[0], o[1], o[2], o[3]);
}

#define PF_START 2
#define WI1 0x0f0901u
#define WI0 0x0d05u
#define WI0N 2
#define PF_DIST 1
#define RORD 0x654210
#define RORDS 0x6251
#define NOROW0 1

struct Regs {
  float X[48], Y[48];
  uint32_t T[4][2][3][4];
  uint32_t U[3][4], V[3][4], E[3][4];
  uint32_t Z[6][4], P[6][4];
};

template <int RANK, int OLD>
__device__ __forceinline__ void tma_slot(const Ctx& c, int n) {
  constexpr int MID = 1 - OLD;
  const int h = c.h0 + n * c.hstep;
  asm volatile("fence.proxy.async.shared::cta;" ::: "memory");
  asm volatile("bar.sync %0, 128;" ::"r"(2 + c.wg) : "memory");
  if (elect_one()) {
    if (c.warp < 2) {
      if (n + 2 < c.nrows) {
        mbar_expect_tx(c.bar_full + 8 * OLD, BOX_BYTES);
        tma_load5(c.in_base + OLD * STAGE_BYTES + c.warp * OFF_BOXB, c.map, c.bar_full + 8 * OLD, c.c0, 2 * c.warp, c.u0 - c.warp, 0,
                  h + 4 * c.hstep);
      } else {
        mbar_arrive(c.bar_full + 8 * OLD);
      }
    } else if (c.warp == 2) {
      if (OLD == 1 || n > 0) tma_store5(c.omap, c.xbase + MID * XBUF_BYTES, 0, c.u0, 0, RANK, h);
    } else {
      if (PF_DIST > 0 && n >= PF_START && n + 2 + PF_DIST < c.nrows) prefetch_row(c, h + (4 + PF_DIST) * c.hstep);
    }
  }
  __syncwarp();
}
template <int RANK, int OLD>
__device__ __forceinline__ void release_xbuf(const Ctx& c) {
  constexpr uint32_t RDELTA = RANK ? 0xFF000000u : 0x01000000u;
  asm volatile("cp.async.bulk.wait_group.read 0;" ::: "memory");
  asm volatile("{\n.reg .pred p, q;\nelect.sync _|q, 0xffffffff;\nsetp.eq.and.u32 p, %1, 2, q;\n@p mbarrier.arrive.shared::cluster.b64 _, [%0];\n}\n"
               ::"r"(c.bar_full + 8 * (1 - OLD) + RDELTA), "r"(c.warp) : "memory");
}
template <int C0, int C1>
__device__ __forceinline__ void pack_acc(uint32_t (&Z)[6][4], const float (&Y)[48]) {
#pragma unroll
  for (int ch = C0; ch < C1; ch++)
#pragma unroll
    for (int ss = 0; ss < 4; ss++) {
      const int i = 16 * (ch >> 1) + 4 * ss + 2 * (ch & 1);
      Z[ch][ss] = pack2(Y[i], Y[i + 1]);
    }
}
template <int BUF, int C0, int C1>
__device__ __forceinline__ void add_stage(const Ctx& c, uint32_t (&Z)[6][4], const uint32_t (&P)[6][4]) {
#pragma unroll
  for (int ch = C0; ch < C1; ch++)
#pragma unroll
    for (int ss = 0; ss < 4; ss++) Z[ch][ss] = badd(Z[ch][ss], P[ch][ss]);
#pragma unroll
  for (int ch = C0; ch < C1; ch++) sts4(c.xaddr + BUF * XBUF_BYTES + (ch & 1) * 6144 + (ch >> 1) * 64, Z[ch]);
}

__device__ __forceinline__ uint64_t get_bd(const Ctx& c, int n) {
  return BDESC + (uint64_t)(uint32_t)(n >> 8);
}
#define G1  batch_<0, 0, 1>(r.X, r.T[0][OLD], bd);
#define G2  batch_<0, 1, 0>(r.X, r.T[0][MID], bd);
#define G3  batch_<0, 2, 0>(r.X, r.T[0][OLD], bd);
#define G4  batch_<1, 0, 1>(r.Y, r.T[1][OLD], bd);
#define G5  batch_<1, 1, 0>(r.Y, r.T[1][MID], bd);
#define G6  batch_<1, 2, 0>(r.Y, r.T[1][OLD], bd);
#define G7  if (OLD == 1) batch_<2, 0, 0>(r.X, r.T[2][OLD], bd); else { if (!skip) { F batch_<2, 0, 0>(r.X, r.T[2][OLD], bd); } else { F wg_commit(); } F }
#define G8  batch_<2, 1, 0>(r.X, r.T[2][MID], bd);
#define G9  batch_<2, 2, 0>(r.X, r.T[2][OLD], bd);
#define G10 if (OLD == 1) batch_<3, 0, 0>(r.Y, r.T[3][OLD], bd); else { if (!skip) { F batch_<3, 0, 0>(r.Y, r.T[3][OLD], bd); } else { F wg_commit(); } F }
#define G11 batch_<3, 1, 0>(r.Y, r.T[3][MID], bd);
#define G12 batch_<3, 2, 0>(r.Y, r.T[3][OLD], bd);
#define F   wg_fence();
#define W(k) wg_wait<k>();
#define PACK pack_acc<0, 6>(r.Z, r.Y);
#define PK(a, b) pack_acc<a, b>(r.Z, r.Y);
#define XW  mbar_wait(c.xfull + MID * 64, ((n - 1) >> 1) & 1); FIX3
#define ARM if (elect_one()) mbar_expect_tx(c.xfull + MID * 64, X_BYTES);
#define REL release_xbuf<RANK, OLD>(c);
#define LP(a, b) load_partner<MID, a, b>(c, r.P);
#define AS(a, b) add_stage<MID, a, b>(c, r.Z, r.P);
#define LV1 if (RANK == 0) ld3(r.V, c.aU, OLD * STAGE_BYTES + OFF_V); else ld3(r.U, c.aU, OLD * STAGE_BYTES);
#define LU1 if (RANK == 0) ld3(r.U, c.aU, OLD * STAGE_BYTES); else ld3(r.V, c.aU, OLD * STAGE_BYTES + OFF_V);
#define LU2 if (RANK == 0) ld3(r.U, c.aU, MID * STAGE_BYTES); else ld3(r.V, c.aU, MID * STAGE_BYTES + OFF_V);
#define LE  ld3(r.E, c.aE, OLD * STAGE_BYTES);
#define LEk(k)  ldsm4(r.E[k], (c.aE ^ (32 * k)) + OLD * STAGE_BYTES);
#define LV1k(k) if (RANK == 0) ldsm4(r.V[k], (c.aU ^ (32 * k)) + OLD * STAGE_BYTES + OFF_V); else ldsm4(r.U[k], (c.aU ^ (32 * k)) + OLD * STAGE_BYTES);
#define LV2k(k) if (RANK == 0) ldsm4(r.V[k], (c.aU ^ (32 * k)) + MID * STAGE_BYTES + OFF_V); else ldsm4(r.U[k], (c.aU ^ (32 * k)) + MID * STAGE_BYTES);
#define LU1k(k) if (RANK == 0) ldsm4(r.U[k], (c.aU ^ (32 * k)) + OLD * STAGE_BYTES); else ldsm4(r.V[k], (c.aU ^ (32 * k)) + OLD * STAGE_BYTES + OFF_V);
#define LU2k(k) if (RANK == 0) ldsm4(r.U[k], (c.aU ^ (32 * k)) + MID * STAGE_BYTES); else ldsm4(r.V[k], (c.aU ^ (32 * k)) + MID * STAGE_BYTES + OFF_V);
#define TRS tr_sum(r.T[0][OLD], r.U, r.V);
#define TRF tr_dif(r.T[1][OLD], r.U, r.V);
#define TRC if (RANK == 0) tr_t3(r.T[2][OLD], r.U, r.E); else tr_t0(r.T[2][OLD], r.V, r.E);
#define TRD if (RANK == 0) tr_t0(r.T[3][OLD], r.V, r.E); else tr_t3(r.T[3][OLD], r.U, r.E);
#define SLOT tma_slot<RANK, OLD>(c, n);
#define FW  if (OLD == 1) mbar_wait(c.bar_full, ((n + 2) >> 1) & 1); \
            else mbar_wait(n ? c.bar_full + 8 : c.bar_ready, n ? ((n + 3) >> 1) & 1 : 0);
#define FIX3 if (OLD == 1 && n == 1) { mbar_wait(c.bar_full + 8, 1); SCHED_FIX3 }
#define SND(k) send_chunk<RANK, OLD, k>(c, r.X);
#define SCHED1 F G1 W(1) PK(0,1) PK(1,2) PK(2,3) PK(3,4) F G2 PK(4,5) PK(5,6) F G4 XW LP(0,1) LP(1,2) ARM LP(2,3) AS(0,1) REL AS(1,2) LP(3,4) LV1k(0) LV1k(1) AS(2,3) LV1k(2) F G5 W(3) TRS LP(4,5) F G3 LP(5,6) W(2) TRF F G6 LEk(0) AS(3,4) AS(4,5) AS(5,6) LEk(1) LEk(2)
#define SCHED1_FIRST LEk(0) LEk(1) LEk(2)
#define SCHED_FIX3 LU1k(0) LU1k(1) LU1k(2)
#define SCHED2 F G7 SLOT F G8 W(1) TRC F G9 FW LU2k(0) W(0) SND(0) LU2k(1) F G10 SND(1) LU2k(2) F G11 SND(2) SND(3) SND(4) SND(5) W(1) TRD F G12

__device__ __forceinline__ void load_row3(const Ctx& c) {
  mbar_expect_tx(c.bar_full + 8, BOX_BYTES);
  tma_load5(c.in_base + STAGE_BYTES + c.warp * OFF_BOXB, c.map, c.bar_full + 8, c.c0, 2 * c.warp, c.u0 - c.warp, 0, c.h0 + 3 * c.hstep);
}
template <int RANK, int OLD, bool FIRST>
__device__ __forceinline__ void phase1(const Ctx& c, int n, Regs& r) {
  constexpr int MID = 1 - OLD;
  const uint64_t bd = get_bd(c, n);
  if (FIRST) {
    wg_fence();
    batch_<0, 1, 1>(r.X, r.T[0][MID], bd);
    batch_<1, 1, 1>(r.Y, r.T[1][MID], bd);
    if ((unsigned)c.h0 < (unsigned)IMG_H) {
      wg_fence();
      batch_<0, 0, 0>(r.X, r.T[0][OLD], bd);
      batch_<1, 0, 0>(r.Y, r.T[1][OLD], bd);
    }
    mbar_wait(c.bar_full + 8 * OLD, 0);
    if (c.warp < 2 && elect_one()) load_row3(c);
    __syncwarp();
    LU1 LV1 W(1) TRS F G3 W(1) TRF F G6
    SCHED1_FIRST
  } else {
    SCHED1
  }
  wg_wait<0>();
}

template <int RANK, int OLD>
__device__ __forceinline__ void phase2(const Ctx& c, int n, Regs& r) {
  constexpr int MID = 1 - OLD;
  const uint64_t bd = get_bd(c, n);
  butterfly<RANK, 0, 48>(r.X, r.Y);
  const bool skip = (unsigned)(c.h0 + n * c.hstep) >= (unsigned)IMG_H;
  SCHED2
}

template <int RANK, int BUF>
__device__ __forceinline__ void finish_strip(const Ctx& c, Regs& r) {
  uint32_t P[6][4];
  mbar_wait(c.xfull + BUF * 64, ((c.nrows - 1) >> 1) & 1);
  load_partner<BUF, 0, 6>(c, P);
  wg_wait<0>();
  finish_chunks<BUF, 0, 6>(c, r.Y, P);
  asm volatile("fence.proxy.async.shared::cta;" ::: "memory");
  asm volatile("bar.sync %0, 128;" ::"r"(2 + c.wg) : "memory");
  if (c.warp == 2 && elect_one()) {
    tma_store5(c.omap, c.xbase + BUF * XBUF_BYTES, 0, c.u0, 0, RANK, c.h0 + c.nrows * c.hstep);
    asm volatile("cp.async.bulk.wait_group.read 0;" ::: "memory");
  }
}

template <int RANK>
__device__ __forceinline__ void run_strip(const Ctx& c, uint32_t row0_off, uint32_t bar_row0) {
  Regs r;
#pragma unroll
  for (int m = 0; m < 2; m++) {
    const uint32_t off = m ? STAGE_BYTES : row0_off;
    mbar_wait(m ? c.bar_full + 8 : bar_row0, 0);
    ld3(r.U, c.aU, off);
    ld3(r.V, c.aU, off + OFF_V);
    ld3(r.E, c.aE, off);
    tr_sum(r.T[0][m], r.U, r.V);
    tr_dif(r.T[1][m], r.U, r.V);
    tr_t3(r.T[RANK == 0 ? 2 : 3][m], r.U, r.E);
    tr_t0(r.T[RANK == 0 ? 3 : 2][m], r.V, r.E);
  }
  asm volatile("bar.sync %0, 128;" ::"r"(2 + c.wg) : "memory");
  asm volatile("barrier.cluster.wait.aligned;" ::: "memory");
  if (elect_one()) {
    if (c.warp == 2) {
      asm volatile("mbarrier.arrive.shared::cluster.b64 _, [%0];" ::"r"(c.bar_ready ^ 0x01000000u) : "memory");
    } else if (c.warp == 3) {
      mbar_arrive(c.bar_full + 8);
    }
  }
  __syncwarp();
  mbar_wait(SMEM_BASE + (RANK << 24) + OFF_BAR + 8 * BAR_W + 24, 0);
#pragma unroll
  for (int i = 0; i < 48; i++) { r.X[i] = 0.f; r.Y[i] = 0.f; r.Z[i % 6][i / 12] = 0; r.P[i % 6][i / 12] = 0; }
  phase1<RANK, 0, true>(c, 0, r);
#pragma unroll 1
  for (int n = 0;; n += 2) {
    phase2<RANK, 0>(c, n, r);
    if (n + 1 == c.nrows) { finish_strip<RANK, 0>(c, r); break; }
    phase1<RANK, 1, false>(c, n + 1, r);
    phase2<RANK, 1>(c, n + 1, r);
    if (n + 2 == c.nrows) { finish_strip<RANK, 1>(c, r); break; }
    phase1<RANK, 0, false>(c, n + 2, r);
  }
}

constexpr int NCL = 66;
struct Strip { int seg, h0, nrows; };
__device__ __forceinline__ bool is_down(int cl) { return cl < 2 || !((cl - 2) & 4); }
__device__ __forceinline__ Strip get_strip(int cl, int wg) {
  const int k = cl - 2, i = k >> 2;
  const int q = (i & 1) ? (wg ? 16 + 15 * i : 16 * i + 16) : (wg ? 30 + 15 * i : 16 * i - 1);
  return cl < 2 ? Strip{2 * cl + wg, -1, 16} : Strip{k & 3, 2 * q + wg, 16 - wg};
}

__global__ void __cluster_dims__(2, 1, 1) __launch_bounds__(256, 1)
dilated_conv_wino_kernel(const __grid_constant__ CUtensorMap xmap, const __grid_constant__ CUtensorMap omap,
                         const __nv_bfloat16* __restrict__ x, const __nv_bfloat16* __restrict__ w) {
  extern __shared__ uint8_t smem_raw[];
  const int tid = threadIdx.x;
  const int w8 = __shfl_sync(0xffffffff, tid >> 5, 0);
  const int wg = w8 >> 2, warp = w8 & 3;
  const int lane = tid & 31;
  const int rank = blockIdx.x & 1;
  const int cl = blockIdx.x >> 1;
  const bool down = is_down(cl);
  const uint32_t sbase = SMEM_BASE + (rank << 24);
  const uint32_t b0 = sbase + OFF_BAR;
  const uint32_t bar_w = b0 + 8 * BAR_W;
  const uint32_t o_w0 = (rank ? 2 : 3) * 9 * BT_BYTES, o_w2 = (rank ? 3 : 2) * 9 * BT_BYTES;
  Ctx c;

  if (w8 >= 5) {
    if (elect_one()) {
      const int a = w8 - 5, i = down ? a : 2 - a;
      const char* src = reinterpret_cast<const char*>(w) + (uint32_t)((i * 6 + rank) * (3 * BT_BYTES));
      const uint32_t dst = sbase + OFF_W + a * 3 * BT_BYTES;
      mbar_init(bar_w + 8 * a, 1);
      mbar_expect_tx(bar_w + 8 * a, 9 * BT_BYTES);
      bulk_load(dst + o_w0, src, 3 * BT_BYTES, bar_w + 8 * a);
      bulk_load(dst, src + 6 * BT_BYTES, 3 * BT_BYTES, bar_w + 8 * a);
      bulk_load(dst + o_w2, src + 12 * BT_BYTES, 3 * BT_BYTES, bar_w + 8 * a);
    }
  } else if (elect_one()) {
    if (w8 < 4) {
      mbar_init(b0 + 8 * w8, 3);
#pragma unroll
      for (int q = 0; q < 4; q++) mbar_init(b0 + 8 * (BAR_XFULL + 4 * w8 + q), 1);
      mbar_expect_tx(b0 + 8 * w8, 2 * BOX_BYTES);
      asm volatile("mbarrier.arrive.shared::cta.b64 _, [%0], 2;" ::"r"(b0 + 8 * w8) : "memory");
    } else {
      asm volatile("prefetch.tensormap [%0];" ::"l"(&xmap) : "memory");
#pragma unroll
      for (int q = 0; q < 2; q++) {
        mbar_init(b0 + 8 * (BAR_ROW0 + q), 1);
        mbar_init(b0 + 8 * (BAR_READY + q), 1);
      }
      mbar_init(bar_w + 24, 8);
#pragma unroll
      for (int q = 0; q < 2; q++) mbar_expect_tx(b0 + 8 * (BAR_ROW0 + q), 2 * BOX_BYTES);
    }
    asm volatile("fence.mbarrier_init.release.cluster;" ::: "memory");
  }
  __syncthreads();
  asm volatile("barrier.cluster.arrive.relaxed.aligned;" ::: "memory");
  const Strip s0 = get_strip(cl, 0), s1 = get_strip(cl, 1);
  c.map = &xmap;
  c.omap = &omap;
  c.wg = wg;
  c.warp = warp;
  c.in_base = sbase + OFF_IN + wg * WG_IN_BYTES;
  c.bar_full = b0 + 8 * (BAR_FULL + wg * NSTAGE);
  c.bar_ready = b0 + 8 * (BAR_READY + wg);
  c.c0 = rank * 48;
  c.u0 = (wg ? s1.seg : s0.seg) * 16;
  c.h0 = wg ? s1.h0 : s0.h0;
  c.hstep = down ? 2 : -2;
  c.nrows = wg ? s1.nrows : s0.nrows;
  c.xfull = b0 + 8 * (BAR_XFULL + w8);
  c.xseg = reinterpret_cast<const char*>(x) + (c.u0 * 8 + rank * 64) * (CH * 2);
  if (warp == 3) {
    if (elect_one()) {
#pragma unroll 1
      for (uint32_t order = cl < 2 ? RORDS : RORD; order; order >>= 4) {
        const int g = (order >> 2) & 1, m = order & 3;
        const uint32_t dst = m == 0 ? sbase + (g ? OFF_ROW0_1 : OFF_ROW0_0) : sbase + OFF_IN + g * WG_IN_BYTES + (m & 1) * STAGE_BYTES;
        const uint32_t bar = b0 + 8 * (m == 0 ? BAR_ROW0 + g : BAR_FULL + 2 * g + (m & 1));
        tma_load5(dst + wg * OFF_BOXB, &xmap, bar, c.c0, 2 * wg, (g ? s1.seg : s0.seg) * 16 - wg, 0, (g ? s1.h0 : s0.h0) + m * c.hstep);
      }
      asm volatile("prefetch.tensormap [%0];" ::"l"(&omap) : "memory");
    }
    __syncwarp();
  }
  if ((uint32_t)__cvta_generic_to_shared(smem_raw) != sbase || mapa(sbase, rank ^ 1) != (sbase ^ 0x01000000u)) __trap();
  if (elect_one()) { mbar_expect_tx(c.xfull, X_BYTES); mbar_expect_tx(c.xfull + 64, X_BYTES); }
  {
    const int g = lane & 7, mi = lane >> 3;
    const int rU = 8 * warp + g + ((mi & 1) ? 34 : 0);
    const int rE = 8 * warp + g + ((mi & 1) ? 2 : 70 + 34);
    const uint32_t pU = c.in_base + rU * 128, pE = c.in_base + rE * 128;
    c.aU = pU + (((mi >> 1) ^ ((pU >> 7) & 7)) << 4);
    c.aE = pE + (((mi >> 1) ^ ((pE >> 7) & 7)) << 4);
  }
  c.xbase = sbase + OFF_X + wg * 2 * XBUF_BYTES;
  c.xaddr = c.xbase + (warp * 8 + (lane >> 2)) * 192 + (lane & 3) * 16;

#pragma unroll 1
  for (uint32_t items = wg ? WI1 + warp * 0x010101u : warp < WI0N ? WI0 + warp * 0x0101u : (WI0 & 255) + warp; items; items >>= 8) {
    const int item = (items & 255) - 1;
    if (item >= 18) break;
    const uint32_t base = sbase + OFF_W + item * 1536;
    mbar_wait(bar_w + 8 * (item / 6), 0);
    uint32_t wa[3][4], wb[3][4], wd[3][4];
    const uint32_t src = base + (lane >> 2) * 192 + (lane & 3) * 16;
#pragma unroll
    for (int m = 0; m < 3; m++) lds4(wa[m], src + o_w0 + m * 64);
#pragma unroll
    for (int m = 0; m < 3; m++) lds4(wd[m], src + o_w2 + m * 64);
#pragma unroll
    for (int m = 0; m < 3; m++) lds4(wb[m], src + m * 64);
    __syncwarp();
    const uint32_t dst = base + lane * 16;
#pragma unroll
    for (int m = 0; m < 3; m++) stsm4(dst + m * 512 + o_w0, wa[m][0], wa[m][1], wa[m][2], wa[m][3]);
#pragma unroll
    for (int m = 0; m < 3; m++) stsm4(dst + m * 512 + o_w2, wd[m][0], wd[m][1], wd[m][2], wd[m][3]);
#pragma unroll
    for (int m = 0; m < 3; m++) {
      uint32_t g1[4], g2[4];
#pragma unroll
      for (int ss = 0; ss < 4; ss++) {
        const uint32_t a = wa[m][ss], b = wb[m][ss], d = wd[m][ss];
        const float slo = 0.5f * (bf_lo(a) + bf_lo(d)), shi = 0.5f * (bf_hi(a) + bf_hi(d));
        const float blo = bf_lo(b), bhi = bf_hi(b);
        g1[ss] = pack2(fmaf(blo, 0.5f, slo), fmaf(bhi, 0.5f, shi));
        g2[ss] = pack2(fmaf(blo, -0.5f, slo), fmaf(bhi, -0.5f, shi));
      }
      stsm4(dst + m * 512, g1[0], g1[1], g1[2], g1[3]);
      stsm4(dst + m * 512 + 9 * BT_BYTES, g2[0], g2[1], g2[2], g2[3]);
    }
  }
  asm volatile("fence.proxy.async.shared::cta;" ::: "memory");
  __syncwarp();
  if (elect_one()) mbar_arrive(bar_w + 24);

  const uint32_t row0_off = sbase + (wg ? OFF_ROW0_1 : OFF_ROW0_0) - c.in_base;
  const uint32_t bar_row0 = NOROW0 && cl < 2 ? bar_w : b0 + 8 * (BAR_ROW0 + wg);
  if (rank == 0) run_strip<0>(c, row0_off, bar_row0); else run_strip<1>(c, row0_off, bar_row0);
}

typedef CUresult (*EncodeTiledFn)(CUtensorMap*, CUtensorMapDataType, cuuint32_t, void*, const cuuint64_t*, const cuuint64_t*,
                                  const cuuint32_t*, const cuuint32_t*, CUtensorMapInterleave, CUtensorMapSwizzle,
                                  CUtensorMapL2promotion, CUtensorMapFloatOOBfill);

}

extern "C" void kernel_launch(void* const* d_in, const int* in_sizes, int n_in, void* d_out, int out_size) {
  (void)in_sizes; (void)n_in; (void)out_size;
  static EncodeTiledFn encode = nullptr;
  if (!encode) {
    void* fn = nullptr;
    cudaDriverEntryPointQueryResult qr;
    cudaGetDriverEntryPoint("cuTensorMapEncodeTiled", &fn, cudaEnableDefault, &qr);
    encode = (EncodeTiledFn)fn;
    cudaFuncSetAttribute(dilated_conv_wino_kernel, cudaFuncAttributeMaxDynamicSharedMemorySize, SMEM_BYTES);
  }
  CUtensorMap xmap;
  const cuuint64_t dims[5] = {CH, 4, IMG_W / 8, 2, IMG_H};
  const cuuint64_t strides[4] = {CH * 2, 8 * CH * 2, 4 * CH * 2, IMG_W * CH * 2};
  const cuuint32_t box[5] = {48, 2, 17, 2, 1};
  const cuuint32_t estr[5] = {1, 1, 1, 1, 1};
#define PROMO CU_TENSOR_MAP_L2_PROMOTION_L2_128B
  encode(&xmap, CU_TENSOR_MAP_DATA_TYPE_BFLOAT16, 5, d_in[0], dims, strides, box, estr, CU_TENSOR_MAP_INTERLEAVE_NONE,
         CU_TENSOR_MAP_SWIZZLE_128B, PROMO, CU_TENSOR_MAP_FLOAT_OOB_FILL_NONE);
  CUtensorMap omap;
  const cuuint64_t odims[5] = {2 * CH, IMG_W / 8, 2, 2, IMG_H};
  const cuuint64_t ostrides[4] = {8 * CH * 2, 4 * CH * 2, 2 * CH * 2, IMG_W * CH * 2};
  const cuuint32_t obox[5] = {2 * CH, 16, 2, 1, 1};
  encode(&omap, CU_TENSOR_MAP_DATA_TYPE_BFLOAT16, 5, d_out, odims, ostrides, obox, estr, CU_TENSOR_MAP_INTERLEAVE_NONE,
         CU_TENSOR_MAP_SWIZZLE_NONE, CU_TENSOR_MAP_L2_PROMOTION_NONE, CU_TENSOR_MAP_FLOAT_OOB_FILL_NONE);
  dilated_conv_wino_kernel<<<2 * NCL, 256, SMEM_BYTES>>>(xmap, omap, (const __nv_bfloat16*)d_in[0], (const __nv_bfloat16*)d_in[1]);
}
```

```cpp
#include <cuda_runtime.h>
#include <cuda_bf16.h>
#include <cuda.h>
#include <stdint.h>

namespace {

constexpr int IMG_H = 512, IMG_W = 512, CH = 96;
constexpr int NSTAGE = 2;

constexpr int BT_BYTES   = 3072;
constexpr int W_BYTES    = 36 * BT_BYTES;
constexpr int BOX_BYTES  = 68 * 96;
constexpr int OFF_BOXB   = 70 * 128;
constexpr int STAGE_BYTES = 144 * 128;
constexpr int OFF_V      = 72 * 128;
constexpr int WG_IN_BYTES = STAGE_BYTES + 138 * 128;
constexpr int OFF_W      = 0;
constexpr int OFF_IN     = OFF_W + W_BYTES;
constexpr int OFF_X      = OFF_IN + 2 * WG_IN_BYTES;
constexpr int X_BYTES    = 3072;
constexpr int XBUF_BYTES = 4 * X_BYTES;
constexpr int SMEM_BYTES = OFF_X + 4 * XBUF_BYTES;
constexpr int OFF_ROW0_0 = OFF_X + ((OFF_IN - OFF_X) & 1023);
constexpr int OFF_ROW0_1 = OFF_X + 2 * XBUF_BYTES + ((OFF_IN + WG_IN_BYTES - OFF_X) & 1023);
constexpr int OFF_BAR    = OFF_IN + 68 * 128;
constexpr int BAR_FULL = 0, BAR_XFULL = 8, BAR_W = 24, BAR_ROW0 = 28, BAR_READY = 30;
static_assert(SMEM_BYTES <= 232448, "shared memory");
constexpr uint32_t SMEM_BASE = 1024;
constexpr uint64_t BDESC = (uint64_t)((SMEM_BASE + OFF_W) >> 4) | ((uint64_t)(1536 >> 4) << 16) | ((uint64_t)(128 >> 4) << 32);

__device__ __forceinline__ void wg_fence()  { asm volatile("wgmma.fence.sync.aligned;" ::: "memory"); }
__device__ __forceinline__ void wg_commit() { asm volatile("wgmma.commit_group.sync.aligned;" ::: "memory"); }
template <int N> __device__ __forceinline__ void wg_wait() { asm volatile("wgmma.wait_group.sync.aligned %0;" ::"n"(N) : "memory"); }

template <int SCALE_D>
__device__ __forceinline__ void wgmma96(float (&d)[48], const uint32_t (&a)[4], uint64_t DESC) {
  asm volatile(
      "{\n.reg .pred p;\nsetp.ne.b32 p, %53, 0;\n"
      "wgmma.mma_async.sync.aligned.m64n96k16.f32.bf16.bf16 "
      "{%0,%1,%2,%3,%4,%5,%6,%7,%8,%9,%10,%11,%12,%13,%14,%15,%16,%17,%18,%19,%20,%21,%22,%23,"
      "%24,%25,%26,%27,%28,%29,%30,%31,%32,%33,%34,%35,%36,%37,%38,%39,%40,%41,%42,%43,%44,%45,%46,%47}, "
      "{%48,%49,%50,%51}, %52, p, 1, 1, 1;\n}\n"
      : "+f"(d[0]), "+f"(d[1]), "+f"(d[2]), "+f"(d[3]), "+f"(d[4]), "+f"(d[5]), "+f"(d[6]), "+f"(d[7]),
        "+f"(d[8]), "+f"(d[9]), "+f"(d[10]), "+f"(d[11]), "+f"(d[12]), "+f"(d[13]), "+f"(d[14]), "+f"(d[15]),
        "+f"(d[16]), "+f"(d[17]), "+f"(d[18]), "+f"(d[19]), "+f"(d[20]), "+f"(d[21]), "+f"(d[22]), "+f"(d[23]),
        "+f"(d[24]), "+f"(d[25]), "+f"(d[26]), "+f"(d[27]), "+f"(d[28]), "+f"(d[29]), "+f"(d[30]), "+f"(d[31]),
        "+f"(d[32]), "+f"(d[33]), "+f"(d[34]), "+f"(d[35]), "+f"(d[36]), "+f"(d[37]), "+f"(d[38]), "+f"(d[39]),
        "+f"(d[40]), "+f"(d[41]), "+f"(d[42]), "+f"(d[43]), "+f"(d[44]), "+f"(d[45]), "+f"(d[46]), "+f"(d[47])
      : "r"(a[0]), "r"(a[1]), "r"(a[2]), "r"(a[3]), "l"(DESC), "n"(SCALE_D));
}

__device__ __forceinline__ void ldsm4(uint32_t (&r)[4], uint32_t addr) {
  asm volatile("ldmatrix.sync.aligned.m8n8.x4.shared.b16 {%0,%1,%2,%3}, [%4];"
               : "=r"(r[0]), "=r"(r[1]), "=r"(r[2]), "=r"(r[3]) : "r"(addr) : "memory");
}
__device__ __forceinline__ uint32_t badd(uint32_t a, uint32_t b) {
  uint32_t d; asm volatile("add.rn.bf16x2 %0, %1, %2;" : "=r"(d) : "r"(a), "r"(b)); return d;
}
__device__ __forceinline__ uint32_t bsub(uint32_t a, uint32_t b) {
  uint32_t d; asm volatile("sub.rn.bf16x2 %0, %1, %2;" : "=r"(d) : "r"(a), "r"(b)); return d;
}
__device__ __forceinline__ float bf_lo(uint32_t v) {
  return __uint_as_float(v << 16);
}
__device__ __forceinline__ float bf_hi(uint32_t v) { return __uint_as_float(v & 0xffff0000u); }
__device__ __forceinline__ uint32_t pack2(float lo, float hi) {
  uint32_t d; asm volatile("cvt.rn.bf16x2.f32 %0, %1, %2;" : "=r"(d) : "f"(hi), "f"(lo)); return d;
}

__device__ __forceinline__ void mbar_wait(uint32_t bar, uint32_t parity) {
  asm volatile(
      "{\n.reg .pred p;\n.reg .u32 it;\n"
      "mbarrier.try_wait.parity.shared::cta.b64 p, [%0], %1;\n"
      "@p bra WAIT_DONE;\n"
      "mov.u32 it, 0;\n"
      "WAIT_LOOP:\n"
      ".pragma \"nounroll\";\n"
      "mbarrier.try_wait.parity.shared::cta.b64 p, [%0], %1;\n"
      "@p bra WAIT_DONE;\n"
      "add.u32 it, it, 1;\n"
      "setp.lt.u32 p, it, 4194304;\n"
      "@p bra WAIT_LOOP;\n"
      "trap;\n"
      "WAIT_DONE:\n}\n" ::"r"(bar), "r"(parity) : "memory");
}
__device__ __forceinline__ void mbar_init(uint32_t bar, uint32_t count) {
  asm volatile("mbarrier.init.shared::cta.b64 [%0], %1;" ::"r"(bar), "r"(count) : "memory");
}
__device__ __forceinline__ void mbar_arrive(uint32_t bar) {
  asm volatile("mbarrier.arrive.shared::cta.b64 _, [%0];" ::"r"(bar) : "memory");
}
__device__ __forceinline__ void mbar_expect_tx(uint32_t bar, uint32_t bytes) {
  asm volatile("mbarrier.arrive.expect_tx.shared::cta.b64 _, [%0], %1;" ::"r"(bar), "r"(bytes) : "memory");
}
__device__ __forceinline__ void tma_load5(uint32_t dst, const CUtensorMap* map, uint32_t bar, int c0, int c1, int c2, int c3, int c4) {
  asm volatile("cp.async.bulk.tensor.5d.shared::cluster.global.mbarrier::complete_tx::bytes [%0], [%1, {%3,%4,%5,%6,%7}], [%2];"
               ::"r"(dst), "l"(map), "r"(bar), "r"(c0), "r"(c1), "r"(c2), "r"(c3), "r"(c4) : "memory");
}
__device__ __forceinline__ void bulk_load(uint32_t dst, const void* src, uint32_t bytes, uint32_t bar) {
  asm volatile("cp.async.bulk.shared::cluster.global.mbarrier::complete_tx::bytes [%0], [%1], %2, [%3];"
               ::"r"(dst), "l"(src), "r"(bytes), "r"(bar) : "memory");
}
template <int OFF>
__device__ __forceinline__ void st_async4(uint32_t cluster_addr, uint32_t cluster_bar, uint32_t a, uint32_t b, uint32_t c, uint32_t d) {
  asm volatile("st.async.shared::cluster.mbarrier::complete_tx::bytes.v4.b32 [%0+%6], {%2,%3,%4,%5}, [%1];"
               ::"r"(cluster_addr), "r"(cluster_bar), "r"(a), "r"(b), "r"(c), "r"(d), "n"(OFF) : "memory");
}
__device__ __forceinline__ void stsm4(uint32_t addr, uint32_t a, uint32_t b, uint32_t c, uint32_t d) {
  asm volatile("stmatrix.sync.aligned.m8n8.x4.shared.b16 [%0], {%1,%2,%3,%4};" ::"r"(addr), "r"(a), "r"(b), "r"(c), "r"(d) : "memory");
}
__device__ __forceinline__ void lds4(uint32_t (&r)[4], uint32_t addr) {
  asm volatile("ld.shared.v4.b32 {%0,%1,%2,%3}, [%4];" : "=r"(r[0]), "=r"(r[1]), "=r"(r[2]), "=r"(r[3]) : "r"(addr) : "memory");
}
__device__ __forceinline__ void sts4(uint32_t addr, const uint32_t (&r)[4]) {
  asm volatile("st.shared.v4.b32 [%0], {%1,%2,%3,%4};" ::"r"(addr), "r"(r[0]), "r"(r[1]), "r"(r[2]), "r"(r[3]) : "memory");
}
__device__ __forceinline__ void tma_store5(const CUtensorMap* map, uint32_t src, int c0, int c1, int c2, int c3, int c4) {
  asm volatile("cp.async.bulk.tensor.5d.global.shared::cta.bulk_group [%0, {%2,%3,%4,%5,%6}], [%1];"
               ::"l"(map), "r"(src), "r"(c0), "r"(c1), "r"(c2), "r"(c3), "r"(c4) : "memory");
  asm volatile("cp.async.bulk.commit_group;" ::: "memory");
}
__device__ __forceinline__ bool elect_one() {
  uint32_t p;
  asm volatile("{\n.reg .pred P;\nelect.sync _|P, 0xffffffff;\nselp.u32 %0, 1, 0, P;\n}\n" : "=r"(p));
  return p;
}
__device__ __forceinline__ uint32_t mapa(uint32_t addr, uint32_t rank) {
  uint32_t r; asm("mapa.shared::cluster.u32 %0, %1, %2;" : "=r"(r) : "r"(addr), "r"(rank)); return r;
}

__device__ __forceinline__ void tr_sum(uint32_t (&t)[3][4], const uint32_t (&U)[3][4], const uint32_t (&V)[3][4]) {
#pragma unroll
  for (int k = 0; k < 3; k++)
#pragma unroll
    for (int i = 0; i < 4; i++) t[k][i] = badd(U[k][i], V[k][i]);
}
__device__ __forceinline__ void tr_dif(uint32_t (&t)[3][4], const uint32_t (&U)[3][4], const uint32_t (&V)[3][4]) {
#pragma unroll
  for (int k = 0; k < 3; k++)
#pragma unroll
    for (int i = 0; i < 4; i++) t[k][i] = bsub(V[k][i], U[k][i]);
}
__device__ __forceinline__ void tr_t0(uint32_t (&t)[3][4], const uint32_t (&V)[3][4], const uint32_t (&E)[3][4]) {
#pragma unroll
  for (int k = 0; k < 3; k++) {
    t[k][0] = bsub(E[k][0], V[k][0]); t[k][1] = bsub(V[k][0], V[k][1]);
    t[k][2] = bsub(E[k][2], V[k][2]); t[k][3] = bsub(V[k][2], V[k][3]);
  }
}
__device__ __forceinline__ void tr_t3(uint32_t (&t)[3][4], const uint32_t (&U)[3][4], const uint32_t (&E)[3][4]) {
#pragma unroll
  for (int k = 0; k < 3; k++) {
    t[k][0] = bsub(U[k][1], U[k][0]); t[k][1] = bsub(E[k][1], U[k][1]);
    t[k][2] = bsub(U[k][3], U[k][2]); t[k][3] = bsub(E[k][3], U[k][3]);
  }
}
__device__ __forceinline__ void ld3(uint32_t (&R)[3][4], uint32_t aU, int off) {
#pragma unroll
  for (int k = 0; k < 3; k++) ldsm4(R[k], (aU ^ (32 * k)) + off);
}
template <int COMP, int AGE, int FIRST>
__device__ __forceinline__ void batch_(float (&acc)[48], const uint32_t (&t)[3][4], uint64_t bd) {
  constexpr int base = ((COMP * 3 + AGE) * 3) * BT_BYTES;
  wgmma96<FIRST ? 0 : 1>(acc, t[0], bd + ((base) >> 4));
  wgmma96<1>(acc, t[1], bd + ((base + BT_BYTES) >> 4));
  wgmma96<1>(acc, t[2], bd + ((base + 2 * BT_BYTES) >> 4));
  wg_commit();
}

template <int RANK, int I0, int I1>
__device__ __forceinline__ void butterfly(float (&X)[48], float (&Y)[48]) {
#pragma unroll
  for (int i = I0; i < I1; i++) {
    if (RANK == 0) asm volatile("sub.rn.f32 %0, %0, %1;\nfma.rn.f32 %1, %1, 0f40000000, %0;" : "+f"(X[i]), "+f"(Y[i]));
    else           asm volatile("add.rn.f32 %0, %0, %1;\nfma.rn.f32 %1, %1, 0fC0000000, %0;" : "+f"(X[i]), "+f"(Y[i]));
  }
}

struct Ctx {
  uint32_t aU, aE;
  uint32_t in_base;
  uint32_t bar_full;
  uint32_t bar_ready;
  uint32_t xaddr, xfull;
  uint32_t xbase;
  const CUtensorMap* omap;
  char* out;
  const CUtensorMap* map;
  const char* xseg;
  int wg, warp;
  int c0, u0, h0, hstep;
  int nrows;
};

__device__ __forceinline__ void prefetch_row(const Ctx& c, int h) {
  if ((unsigned)h < (unsigned)IMG_H)
    asm volatile("cp.async.bulk.prefetch.L2.global [%0], %1;" ::"l"(c.xseg + (size_t)h * (IMG_W * CH * 2)), "r"(64 * CH * 2) : "memory");
}

template <int BUF, int C0, int C1>
__device__ __forceinline__ void load_partner(const Ctx& c, uint32_t (&P)[6][4]) {
#pragma unroll
  for (int ch = C0; ch < C1; ch++) lds4(P[ch], c.xaddr + BUF * XBUF_BYTES + (ch & 1) * 6144 + (ch >> 1) * 64);
}
template <int RANK, int BUF, int CH0>
__device__ __forceinline__ void send_chunk(const Ctx& c, const float (&X)[48]) {
  constexpr uint32_t RDELTA = RANK ? 0xFF000000u : 0x01000000u;
  constexpr int m = CH0 >> 1, s = CH0 & 1;
  uint32_t o[4];
#pragma unroll
  for (int ss = 0; ss < 4; ss++) o[ss] = pack2(X[16 * m + 4 * ss + 2 * s], X[16 * m + 4 * ss + 2 * s + 1]);
  st_async4<BUF * XBUF_BYTES + s * 6144 + m * 64>(c.xaddr + RDELTA, c.xfull + BUF * 64 + RDELTA, o[0], o[1], o[2], o[3]);
}

#define PF_START 2
#define WI1 0x0f0901u
#define WI0 0x0d05u
#define WI0N 2
#define SK0 1
#define SPW 1
#define PF_DIST 1
#define RORD 0x654210
#define RORDS 0x6521
#define NOROW0 1

struct Regs {
  float X[48], Y[48];
  uint32_t T[4][2][3][4];
  uint32_t U[3][4], V[3][4], E[3][4];
  uint32_t Z[6][4], P[6][4];
};

template <int RANK, int OLD>
__device__ __forceinline__ void tma_slot(const Ctx& c, int n) {
  constexpr int MID = 1 - OLD;
  const int h = c.h0 + n * c.hstep;
  asm volatile("fence.proxy.async.shared::cta;" ::: "memory");
  asm volatile("bar.sync %0, 128;" ::"r"(2 + c.wg) : "memory");
  if (elect_one()) {
    if (c.warp < 2) {
      if (n + 2 < c.nrows) {
        mbar_expect_tx(c.bar_full + 8 * OLD, BOX_BYTES);
        tma_load5(c.in_base + OLD * STAGE_BYTES + c.warp * OFF_BOXB, c.map, c.bar_full + 8 * OLD, c.c0, 2 * c.warp, c.u0 - c.warp, 0,
                  h + 4 * c.hstep);
      } else {
        mbar_arrive(c.bar_full + 8 * OLD);
      }
    } else if (c.warp == 2) {
      if (OLD == 1 || n > 0) tma_store5(c.omap, c.xbase + MID * XBUF_BYTES, 0, c.u0, 0, RANK, h);
    } else {
      if (PF_DIST > 0 && n >= PF_START && n + 2 + PF_DIST < c.nrows) prefetch_row(c, h + (4 + PF_DIST) * c.hstep);
    }
  }
  __syncwarp();
}
template <int RANK, int OLD>
__device__ __forceinline__ void release_xbuf(const Ctx& c) {
  constexpr uint32_t RDELTA = RANK ? 0xFF000000u : 0x01000000u;
  asm volatile("cp.async.bulk.wait_group.read 0;" ::: "memory");
  asm volatile("{\n.reg .pred p, q;\nelect.sync _|q, 0xffffffff;\nsetp.eq.and.u32 p, %1, 2, q;\n@p mbarrier.arrive.shared::cluster.b64 _, [%0];\n}\n"
               ::"r"(c.bar_full + 8 * (1 - OLD) + RDELTA), "r"(c.warp) : "memory");
}
template <int C0, int C1>
__device__ __forceinline__ void pack_acc(uint32_t (&Z)[6][4], const float (&Y)[48]) {
#pragma unroll
  for (int ch = C0; ch < C1; ch++)
#pragma unroll
    for (int ss = 0; ss < 4; ss++) {
      const int i = 16 * (ch >> 1) + 4 * ss + 2 * (ch & 1);
      Z[ch][ss] = pack2(Y[i], Y[i + 1]);
    }
}
template <int BUF, int C0, int C1>
__device__ __forceinline__ void add_stage(const Ctx& c, uint32_t (&Z)[6][4], const uint32_t (&P)[6][4]) {
#pragma unroll
  for (int ch = C0; ch < C1; ch++)
#pragma unroll
    for (int ss = 0; ss < 4; ss++) Z[ch][ss] = badd(Z[ch][ss], P[ch][ss]);
#pragma unroll
  for (int ch = C0; ch < C1; ch++) sts4(c.xaddr + BUF * XBUF_BYTES + (ch & 1) * 6144 + (ch >> 1) * 64, Z[ch]);
}

__device__ __forceinline__ uint64_t get_bd(const Ctx& c, int n) {
  return BDESC + (uint64_t)(uint32_t)(n >> 8);
}
#define G1  batch_<0, 0, 1>(r.X, r.T[0][OLD], bd);
#define G2  batch_<0, 1, 0>(r.X, r.T[0][MID], bd);
#define G3  batch_<0, 2, 0>(r.X, r.T[0][OLD], bd);
#define G4  batch_<1, 0, 1>(r.Y, r.T[1][OLD], bd);
#define G5  batch_<1, 1, 0>(r.Y, r.T[1][MID], bd);
#define G6  batch_<1, 2, 0>(r.Y, r.T[1][OLD], bd);
#define G7  if (OLD == 1) batch_<2, 0, 0>(r.X, r.T[2][OLD], bd); else { if (!skip) { F batch_<2, 0, 0>(r.X, r.T[2][OLD], bd); } else { F wg_commit(); } F }
#define G8  batch_<2, 1, 0>(r.X, r.T[2][MID], bd);
#define G9  batch_<2, 2, 0>(r.X, r.T[2][OLD], bd);
#define G10 if (OLD == 1) batch_<3, 0, 0>(r.Y, r.T[3][OLD], bd); else { if (!skip) { F batch_<3, 0, 0>(r.Y, r.T[3][OLD], bd); } else { F wg_commit(); } F }
#define G11 batch_<3, 1, 0>(r.Y, r.T[3][MID], bd);
#define G12 batch_<3, 2, 0>(r.Y, r.T[3][OLD], bd);
#define F   wg_fence();
#define W(k) wg_wait<k>();
#define PACK pack_acc<0, 6>(r.Z, r.Y);
#define PK(a, b) pack_acc<a, b>(r.Z, r.Y);
#define XW  mbar_wait(c.xfull + MID * 64, ((n - 1) >> 1) & 1); FIX3
#define ARM if (elect_one()) mbar_expect_tx(c.xfull + MID * 64, X_BYTES);
#define REL release_xbuf<RANK, OLD>(c);
#define LP(a, b) load_partner<MID, a, b>(c, r.P);
#define AS(a, b) add_stage<MID, a, b>(c, r.Z, r.P);
#define LV1 if (RANK == 0) ld3(r.V, c.aU, OLD * STAGE_BYTES + OFF_V); else ld3(r.U, c.aU, OLD * STAGE_BYTES);
#define LU1 if (RANK == 0) ld3(r.U, c.aU, OLD * STAGE_BYTES); else ld3(r.V, c.aU, OLD * STAGE_BYTES + OFF_V);
#define LU2 if (RANK == 0) ld3(r.U, c.aU, MID * STAGE_BYTES); else ld3(r.V, c.aU, MID * STAGE_BYTES + OFF_V);
#define LE  ld3(r.E, c.aE, OLD * STAGE_BYTES);
#define LEk(k)  ldsm4(r.E[k], (c.aE ^ (32 * k)) + OLD * STAGE_BYTES);
#define LV1k(k) if (RANK == 0) ldsm4(r.V[k], (c.aU ^ (32 * k)) + OLD * STAGE_BYTES + OFF_V); else ldsm4(r.U[k], (c.aU ^ (32 * k)) + OLD * STAGE_BYTES);
#define LV2k(k) if (RANK == 0) ldsm4(r.V[k], (c.aU ^ (32 * k)) + MID * STAGE_BYTES + OFF_V); else ldsm4(r.U[k], (c.aU ^ (32 * k)) + MID * STAGE_BYTES);
#define LU1k(k) if (RANK == 0) ldsm4(r.U[k], (c.aU ^ (32 * k)) + OLD * STAGE_BYTES); else ldsm4(r.V[k], (c.aU ^ (32 * k)) + OLD * STAGE_BYTES + OFF_V);
#define LU2k(k) if (RANK == 0) ldsm4(r.U[k], (c.aU ^ (32 * k)) + MID * STAGE_BYTES); else ldsm4(r.V[k], (c.aU ^ (32 * k)) + MID * STAGE_BYTES + OFF_V);
#define TRS tr_sum(r.T[0][OLD], r.U, r.V);
#define TRF tr_dif(r.T[1][OLD], r.U, r.V);
#define TRC if (RANK == 0) tr_t3(r.T[2][OLD], r.U, r.E); else tr_t0(r.T[2][OLD], r.V, r.E);
#define TRD if (RANK == 0) tr_t0(r.T[3][OLD], r.V, r.E); else tr_t3(r.T[3][OLD], r.U, r.E);
#define SLOT tma_slot<RANK, OLD>(c, n);
#define FW  if (OLD == 1) mbar_wait(c.bar_full, ((n + 2) >> 1) & 1); \
            else mbar_wait(n ? c.bar_full + 8 : c.bar_ready, n ? ((n + 3) >> 1) & 1 : 0);
#define FIX3 if (OLD == 1 && n == 1) { mbar_wait(c.bar_full + 8, 1); SCHED_FIX3 }
#define SND(k) send_chunk<RANK, OLD, k>(c, r.X);
#define SCHED1 F G1 W(1) PK(0,1) PK(1,2) PK(2,3) PK(3,4) F G2 PK(4,5) PK(5,6) F G4 XW LP(0,1) LP(1,2) ARM LP(2,3) AS(0,1) REL AS(1,2) LP(3,4) LV1k(0) LV1k(1) AS(2,3) LV1k(2) F G5 W(3) TRS LP(4,5) F G3 LP(5,6) W(2) TRF F G6 LEk(0) AS(3,4) AS(4,5) AS(5,6) LEk(1) LEk(2)
#define SCHED1_FIRST LEk(0) LEk(1) LEk(2)
#define SCHED_FIX3 LU1k(0) LU1k(1) LU1k(2)
#define SCHED2 F G7 SLOT F G8 W(1) TRC F G9 FW LU2k(0) W(0) SND(0) LU2k(1) F G10 SND(1) LU2k(2) F G11 SND(2) SND(3) SND(4) SND(5) W(1) TRD F G12

__device__ __forceinline__ void load_row3(const Ctx& c) {
  mbar_expect_tx(c.bar_full + 8, BOX_BYTES);
  tma_load5(c.in_base + STAGE_BYTES + c.warp * OFF_BOXB, c.map, c.bar_full + 8, c.c0, 2 * c.warp, c.u0 - c.warp, 0, c.h0 + 3 * c.hstep);
}
template <int RANK, int OLD, bool FIRST>
__device__ __forceinline__ void phase1(const Ctx& c, int n, Regs& r) {
  constexpr int MID = 1 - OLD;
  const uint64_t bd = get_bd(c, n);
  if (FIRST) {
    wg_fence();
    batch_<0, 1, 1>(r.X, r.T[0][MID], bd);
    batch_<1, 1, 1>(r.Y, r.T[1][MID], bd);
    if ((unsigned)c.h0 < (unsigned)IMG_H) {
      wg_fence();
      batch_<0, 0, 0>(r.X, r.T[0][OLD], bd);
      batch_<1, 0, 0>(r.Y, r.T[1][OLD], bd);
    }
    mbar_wait(c.bar_full + 8 * OLD, 0);
    if (c.warp < 2 && elect_one()) load_row3(c);
    __syncwarp();
    LU1 LV1 W(1) TRS F G3 W(1) TRF F G6
    SCHED1_FIRST
  } else {
    SCHED1
  }
}

template <int RANK, int OLD>
__device__ __forceinline__ void phase2(const Ctx& c, int n, Regs& r) {
  constexpr int MID = 1 - OLD;
  const uint64_t bd = get_bd(c, n);
  wg_wait<0>();
  butterfly<RANK, 0, 48>(r.X, r.Y);
  const bool skip = (unsigned)(c.h0 + n * c.hstep) >= (unsigned)IMG_H;
  SCHED2
}

template <int RANK>
__device__ __forceinline__ void finish_strip(const Ctx& c, Regs& r, int buf) {
  wg_wait<0>();
  pack_acc<0, 6>(r.Z, r.Y);
  const int lane = threadIdx.x & 31, g = lane >> 2;
  const int px = 8 * (c.u0 + 4 * c.warp + (g >> 1)) + (g & 1) + 2 * RANK;
  char* o = c.out + ((size_t)(c.h0 + c.nrows * c.hstep) * IMG_W + px) * (CH * 2) + (lane & 3) * 16;
  mbar_wait(c.xfull + buf * 64, ((c.nrows - 1) >> 1) & 1);
#pragma unroll
  for (int ch = 0; ch < 6; ch++) lds4(r.P[ch], c.xaddr + buf * XBUF_BYTES + (ch & 1) * 6144 + (ch >> 1) * 64);
#pragma unroll
  for (int ch = 0; ch < 6; ch++)
    asm volatile("st.global.v4.b32 [%0], {%1,%2,%3,%4};" ::"l"(o + (ch & 1) * (4 * CH * 2) + (ch >> 1) * 64), "r"(badd(r.Z[ch][0], r.P[ch][0])),
                 "r"(badd(r.Z[ch][1], r.P[ch][1])), "r"(badd(r.Z[ch][2], r.P[ch][2])), "r"(badd(r.Z[ch][3], r.P[ch][3])) : "memory");
  asm volatile("cp.async.bulk.wait_group.read 0;" ::: "memory");
}

__device__ __forceinline__ void transform_weights(uint32_t sbase, int rank, int wg, int warp, int lane) {
  const uint32_t bar_w = sbase + OFF_BAR + 8 * BAR_W;
  const uint32_t o_w0 = (rank ? 2 : 3) * 9 * BT_BYTES, o_w2 = (rank ? 3 : 2) * 9 * BT_BYTES;
#pragma unroll 1
  for (uint32_t items = SPW && blockIdx.x < 4 ? 0x110901u + ((wg ^ 1) * 4 + warp) * 0x010101u : wg ? WI1 + warp * 0x010101u : warp < WI0N ? WI0 + warp * 0x0101u : (WI0 & 255) + warp; items; items >>= 8) {
    const int item = (items & 255) - 1;
    if (item >= 18) break;
    const uint32_t base = sbase + OFF_W + item * 1536;
    mbar_wait(bar_w + 8 * (item / 6), 0);
    uint32_t wa[3][4], wb[3][4], wd[3][4];
    const uint32_t src = base + (lane >> 2) * 192 + (lane & 3) * 16;
#pragma unroll
    for (int m = 0; m < 3; m++) lds4(wa[m], src + o_w0 + m * 64);
#pragma unroll
    for (int m = 0; m < 3; m++) lds4(wd[m], src + o_w2 + m * 64);
#pragma unroll
    for (int m = 0; m < 3; m++) lds4(wb[m], src + m * 64);
    __syncwarp();
    const uint32_t dst = base + lane * 16;
#pragma unroll
    for (int m = 0; m < 3; m++) stsm4(dst + m * 512 + o_w0, wa[m][0], wa[m][1], wa[m][2], wa[m][3]);
#pragma unroll
    for (int m = 0; m < 3; m++) stsm4(dst + m * 512 + o_w2, wd[m][0], wd[m][1], wd[m][2], wd[m][3]);
#pragma unroll
    for (int m = 0; m < 3; m++) {
      uint32_t g1[4], g2[4];
#pragma unroll
      for (int ss = 0; ss < 4; ss++) {
        const uint32_t a = wa[m][ss], b = wb[m][ss], d = wd[m][ss];
        const float slo = 0.5f * (bf_lo(a) + bf_lo(d)), shi = 0.5f * (bf_hi(a) + bf_hi(d));
        const float blo = bf_lo(b), bhi = bf_hi(b);
        g1[ss] = pack2(fmaf(blo, 0.5f, slo), fmaf(bhi, 0.5f, shi));
        g2[ss] = pack2(fmaf(blo, -0.5f, slo), fmaf(bhi, -0.5f, shi));
      }
      stsm4(dst + m * 512, g1[0], g1[1], g1[2], g1[3]);
      stsm4(dst + m * 512 + 9 * BT_BYTES, g2[0], g2[1], g2[2], g2[3]);
    }
  }
  asm volatile("fence.proxy.async.shared::cta;" ::: "memory");
  __syncwarp();
  if (elect_one()) mbar_arrive(bar_w + 24);
}

template <int RANK>
__device__ __forceinline__ void run_strip(const Ctx& c, uint32_t row0_off, uint32_t bar_row0) {
  transform_weights(SMEM_BASE + (RANK << 24), RANK, c.wg, c.warp, threadIdx.x & 31);
  Regs r;
#pragma unroll
  for (int m = 0; m < 2; m++) {
    const uint32_t off = m ? STAGE_BYTES : row0_off;
    mbar_wait(m ? c.bar_full + 8 : bar_row0, 0);
    if (SK0 && m == 0 && (unsigned)c.h0 >= (unsigned)IMG_H) {
#pragma unroll
      for (int i = 0; i < 48; i++) asm volatile("" : "=r"(r.T[i / 12][0][(i / 4) % 3][i % 4]));
      continue;
    }
    ld3(r.U, c.aU, off);
    ld3(r.V, c.aU, off + OFF_V);
    ld3(r.E, c.aE, off);
    tr_sum(r.T[0][m], r.U, r.V);
    tr_dif(r.T[1][m], r.U, r.V);
    tr_t3(r.T[RANK == 0 ? 2 : 3][m], r.U, r.E);
    tr_t0(r.T[RANK == 0 ? 3 : 2][m], r.V, r.E);
  }
  asm volatile("bar.sync %0, 128;" ::"r"(2 + c.wg) : "memory");
  asm volatile("barrier.cluster.wait.aligned;" ::: "memory");
  if (elect_one()) {
    if (c.warp == 2) {
      asm volatile("mbarrier.arrive.shared::cluster.b64 _, [%0];" ::"r"(c.bar_ready ^ 0x01000000u) : "memory");
    } else if (c.warp == 3) {
      mbar_arrive(c.bar_full + 8);
    }
  }
  __syncwarp();
  mbar_wait(SMEM_BASE + (RANK << 24) + OFF_BAR + 8 * BAR_W + 24, 0);
#pragma unroll
  for (int i = 0; i < 48; i++) { r.X[i] = 0.f; r.Y[i] = 0.f; r.Z[i % 6][i / 12] = 0; r.P[i % 6][i / 12] = 0; }
  phase1<RANK, 0, true>(c, 0, r);
#pragma unroll 1
  for (int n = 0;; n += 2) {
    phase2<RANK, 0>(c, n, r);
    if (n + 1 == c.nrows) break;
    phase1<RANK, 1, false>(c, n + 1, r);
    phase2<RANK, 1>(c, n + 1, r);
    if (n + 2 == c.nrows) break;
    phase1<RANK, 0, false>(c, n + 2, r);
  }
  finish_strip<RANK>(c, r, (c.nrows - 1) & 1);
}

constexpr int NCL = 66;
struct Strip { int seg, h0, nrows; };
__device__ __forceinline__ bool is_down(int cl) { return cl < 2 || !((cl - 2) & 4); }
__device__ __forceinline__ Strip get_strip(int cl, int wg) {
  const int k = cl - 2, i = k >> 2;
  const int q = (i & 1) ? (wg ? 16 + 15 * i : 16 * i + 16) : (wg ? 30 + 15 * i : 16 * i - 1);
  return cl < 2 ? Strip{2 * cl + wg, -1, 16} : Strip{k & 3, 2 * q + wg, 16 - wg};
}

__global__ void __cluster_dims__(2, 1, 1) __launch_bounds__(256, 1)
dilated_conv_wino_kernel(const __grid_constant__ CUtensorMap xmap, const __grid_constant__ CUtensorMap omap,
                         const __nv_bfloat16* __restrict__ x, const __nv_bfloat16* __restrict__ w, __nv_bfloat16* __restrict__ out) {
  extern __shared__ uint8_t smem_raw[];
  const int tid = threadIdx.x;
  const int w8 = __shfl_sync(0xffffffff, tid >> 5, 0);
  const int wg = w8 >> 2, warp = w8 & 3;
  const int lane = tid & 31;
  const int rank = blockIdx.x & 1;
  const int cl = blockIdx.x >> 1;
  const bool down = is_down(cl);
  const uint32_t sbase = SMEM_BASE + (rank << 24);
  const uint32_t b0 = sbase + OFF_BAR;
  const uint32_t bar_w = b0 + 8 * BAR_W;
  const uint32_t o_w0 = (rank ? 2 : 3) * 9 * BT_BYTES, o_w2 = (rank ? 3 : 2) * 9 * BT_BYTES;
  Ctx c;

  if (w8 >= 5) {
    if (elect_one()) {
      const int a = w8 - 5, i = down ? a : 2 - a;
      const char* src = reinterpret_cast<const char*>(w) + (uint32_t)((i * 6 + rank) * (3 * BT_BYTES));
      const uint32_t dst = sbase + OFF_W + a * 3 * BT_BYTES;
      mbar_init(bar_w + 8 * a, 1);
      mbar_expect_tx(bar_w + 8 * a, 9 * BT_BYTES);
      bulk_load(dst + o_w0, src, 3 * BT_BYTES, bar_w + 8 * a);
      bulk_load(dst, src + 6 * BT_BYTES, 3 * BT_BYTES, bar_w + 8 * a);
      bulk_load(dst + o_w2, src + 12 * BT_BYTES, 3 * BT_BYTES, bar_w + 8 * a);
    }
  } else if (elect_one()) {
    if (w8 < 4) {
      mbar_init(b0 + 8 * w8, 3);
#pragma unroll
      for (int q = 0; q < 4; q++) mbar_init(b0 + 8 * (BAR_XFULL + 4 * w8 + q), 1);
      mbar_expect_tx(b0 + 8 * w8, 2 * BOX_BYTES);
      asm volatile("mbarrier.arrive.shared::cta.b64 _, [%0], 2;" ::"r"(b0 + 8 * w8) : "memory");
    } else {
      asm volatile("prefetch.tensormap [%0];" ::"l"(&xmap) : "memory");
#pragma unroll
      for (int q = 0; q < 2; q++) {
        mbar_init(b0 + 8 * (BAR_ROW0 + q), 1);
        mbar_init(b0 + 8 * (BAR_READY + q), 1);
      }
      mbar_init(bar_w + 24, 8);
#pragma unroll
      for (int q = 0; q < 2; q++) mbar_expect_tx(b0 + 8 * (BAR_ROW0 + q), 2 * BOX_BYTES);
    }
    asm volatile("fence.mbarrier_init.release.cluster;" ::: "memory");
  }
  __syncthreads();
  asm volatile("barrier.cluster.arrive.relaxed.aligned;" ::: "memory");
  const Strip s0 = get_strip(cl, 0), s1 = get_strip(cl, 1);
  c.map = &xmap;
  c.omap = &omap;
  c.out = reinterpret_cast<char*>(out);
  c.wg = wg;
  c.warp = warp;
  c.in_base = sbase + OFF_IN + wg * WG_IN_BYTES;
  c.bar_full = b0 + 8 * (BAR_FULL + wg * NSTAGE);
  c.bar_ready = b0 + 8 * (BAR_READY + wg);
  c.c0 = rank * 48;
  c.u0 = (wg ? s1.seg : s0.seg) * 16;
  c.h0 = wg ? s1.h0 : s0.h0;
  c.hstep = down ? 2 : -2;
  c.nrows = wg ? s1.nrows : s0.nrows;
  c.xfull = b0 + 8 * (BAR_XFULL + w8);
  c.xseg = reinterpret_cast<const char*>(x) + (c.u0 * 8 + rank * 64) * (CH * 2);
  if (warp == 3) {
    if (elect_one()) {
#pragma unroll 1
      for (uint32_t order = cl < 2 ? RORDS : RORD; order; order >>= 4) {
        const int g = (order >> 2) & 1, m = order & 3;
        const uint32_t dst = m == 0 ? sbase + (g ? OFF_ROW0_1 : OFF_ROW0_0) : sbase + OFF_IN + g * WG_IN_BYTES + (m & 1) * STAGE_BYTES;
        const uint32_t bar = b0 + 8 * (m == 0 ? BAR_ROW0 + g : BAR_FULL + 2 * g + (m & 1));
        tma_load5(dst + wg * OFF_BOXB, &xmap, bar, c.c0, 2 * wg, (g ? s1.seg : s0.seg) * 16 - wg, 0, (g ? s1.h0 : s0.h0) + m * c.hstep);
      }
      asm volatile("prefetch.tensormap [%0];" ::"l"(&omap) : "memory");
    }
    __syncwarp();
  }
  if ((uint32_t)__cvta_generic_to_shared(smem_raw) != sbase || mapa(sbase, rank ^ 1) != (sbase ^ 0x01000000u)) __trap();
  if (elect_one()) { mbar_expect_tx(c.xfull, X_BYTES); mbar_expect_tx(c.xfull + 64, X_BYTES); }
  {
    const int g = lane & 7, mi = lane >> 3;
    const int rU = 8 * warp + g + ((mi & 1) ? 34 : 0);
    const int rE = 8 * warp + g + ((mi & 1) ? 2 : 70 + 34);
    const uint32_t pU = c.in_base + rU * 128, pE = c.in_base + rE * 128;
    c.aU = pU + (((mi >> 1) ^ ((pU >> 7) & 7)) << 4);
    c.aE = pE + (((mi >> 1) ^ ((pE >> 7) & 7)) << 4);
  }
  c.xbase = sbase + OFF_X + wg * 2 * XBUF_BYTES;
  c.xaddr = c.xbase + (warp * 8 + (lane >> 2)) * 192 + (lane & 3) * 16;

  const uint32_t row0_off = sbase + (wg ? OFF_ROW0_1 : OFF_ROW0_0) - c.in_base;
  const uint32_t bar_row0 = NOROW0 && cl < 2 ? bar_w : b0 + 8 * (BAR_ROW0 + wg);
  if (rank == 0) run_strip<0>(c, row0_off, bar_row0); else run_strip<1>(c, row0_off, bar_row0);
}

typedef CUresult (*EncodeTiledFn)(CUtensorMap*, CUtensorMapDataType, cuuint32_t, void*, const cuuint64_t*, const cuuint64_t*,
                                  const cuuint32_t*, const cuuint32_t*, CUtensorMapInterleave, CUtensorMapSwizzle,
                                  CUtensorMapL2promotion, CUtensorMapFloatOOBfill);

}

extern "C" void kernel_launch(void* const* d_in, const int* in_sizes, int n_in, void* d_out, int out_size) {
  (void)in_sizes; (void)n_in; (void)out_size;
  static EncodeTiledFn encode = nullptr;
  if (!encode) {
    void* fn = nullptr;
    cudaDriverEntryPointQueryResult qr;
    cudaGetDriverEntryPoint("cuTensorMapEncodeTiled", &fn, cudaEnableDefault, &qr);
    encode = (EncodeTiledFn)fn;
    cudaFuncSetAttribute(dilated_conv_wino_kernel, cudaFuncAttributeMaxDynamicSharedMemorySize, SMEM_BYTES);
  }
  CUtensorMap xmap;
  const cuuint64_t dims[5] = {CH, 4, IMG_W / 8, 2, IMG_H};
  const cuuint64_t strides[4] = {CH * 2, 8 * CH * 2, 4 * CH * 2, IMG_W * CH * 2};
  const cuuint32_t box[5] = {48, 2, 17, 2, 1};
  const cuuint32_t estr[5] = {1, 1, 1, 1, 1};
#define PROMO CU_TENSOR_MAP_L2_PROMOTION_L2_128B
  encode(&xmap, CU_TENSOR_MAP_DATA_TYPE_BFLOAT16, 5, d_in[0], dims, strides, box, estr, CU_TENSOR_MAP_INTERLEAVE_NONE,
         CU_TENSOR_MAP_SWIZZLE_128B, PROMO, CU_TENSOR_MAP_FLOAT_OOB_FILL_NONE);
  CUtensorMap omap;
  const cuuint64_t odims[5] = {2 * CH, IMG_W / 8, 2, 2, IMG_H};
  const cuuint64_t ostrides[4] = {8 * CH * 2, 4 * CH * 2, 2 * CH * 2, IMG_W * CH * 2};
  const cuuint32_t obox[5] = {2 * CH, 16, 2, 1, 1};
  encode(&omap, CU_TENSOR_MAP_DATA_TYPE_BFLOAT16, 5, d_out, odims, ostrides, obox, estr, CU_TENSOR_MAP_INTERLEAVE_NONE,
         CU_TENSOR_MAP_SWIZZLE_NONE, CU_TENSOR_MAP_L2_PROMOTION_NONE, CU_TENSOR_MAP_FLOAT_OOB_FILL_NONE);
  dilated_conv_wino_kernel<<<2 * NCL, 256, SMEM_BYTES>>>(xmap, omap, (const __nv_bfloat16*)d_in[0], (const __nv_bfloat16*)d_in[1], (__nv_bfloat16*)d_out);
}
```

```cpp
#include <cuda_runtime.h>
#include <cuda_bf16.h>
#include <cuda.h>
#include <stdint.h>

namespace {

constexpr int IMG_H = 512, IMG_W = 512, CH = 96;
constexpr int NSTAGE = 2;

constexpr int BT_BYTES   = 3072;
constexpr int W_BYTES    = 36 * BT_BYTES;
constexpr int BOX_BYTES  = 68 * 96;
constexpr int OFF_BOXB   = 70 * 128;
constexpr int STAGE_BYTES = 144 * 128;
constexpr int OFF_V      = 72 * 128;
constexpr int WG_IN_BYTES = STAGE_BYTES + 138 * 128;
constexpr int OFF_W      = 0;
constexpr int OFF_IN     = OFF_W + W_BYTES;
constexpr int OFF_X      = OFF_IN + 2 * WG_IN_BYTES;
constexpr int X_BYTES    = 3072;
constexpr int XBUF_BYTES = 4 * X_BYTES;
constexpr int SMEM_BYTES = OFF_X + 4 * XBUF_BYTES;
constexpr int OFF_ROW0_0 = OFF_X + ((OFF_IN - OFF_X) & 1023);
constexpr int OFF_ROW0_1 = OFF_X + 2 * XBUF_BYTES + ((OFF_IN + WG_IN_BYTES - OFF_X) & 1023);
constexpr int OFF_BAR    = OFF_IN + 138 * 128;
constexpr int BAR_FULL = 0, BAR_EMPTY = 4, BAR_STAGED = 8, BAR_XFULL = 12, BAR_W = 28, BAR_ROW0 = 32, BAR_READY = 34;
static_assert(SMEM_BYTES <= 232448, "shared memory");
constexpr uint32_t SMEM_BASE = 1024;
constexpr uint64_t BDESC = (uint64_t)((SMEM_BASE + OFF_W) >> 4) | ((uint64_t)(1536 >> 4) << 16) | ((uint64_t)(128 >> 4) << 32);

__device__ __forceinline__ void wg_fence()  { asm volatile("wgmma.fence.sync.aligned;" ::: "memory"); }
__device__ __forceinline__ void wg_commit() { asm volatile("wgmma.commit_group.sync.aligned;" ::: "memory"); }
template <int N> __device__ __forceinline__ void wg_wait() { asm volatile("wgmma.wait_group.sync.aligned %0;" ::"n"(N) : "memory"); }

template <int SCALE_D>
__device__ __forceinline__ void wgmma96(float (&d)[48], const uint32_t (&a)[4], uint64_t DESC) {
  asm volatile(
      "{\n.reg .pred p;\nsetp.ne.b32 p, %53, 0;\n"
      "wgmma.mma_async.sync.aligned.m64n96k16.f32.bf16.bf16 "
      "{%0,%1,%2,%3,%4,%5,%6,%7,%8,%9,%10,%11,%12,%13,%14,%15,%16,%17,%18,%19,%20,%21,%22,%23,"
      "%24,%25,%26,%27,%28,%29,%30,%31,%32,%33,%34,%35,%36,%37,%38,%39,%40,%41,%42,%43,%44,%45,%46,%47}, "
      "{%48,%49,%50,%51}, %52, p, 1, 1, 1;\n}\n"
      : "+f"(d[0]), "+f"(d[1]), "+f"(d[2]), "+f"(d[3]), "+f"(d[4]), "+f"(d[5]), "+f"(d[6]), "+f"(d[7]),
        "+f"(d[8]), "+f"(d[9]), "+f"(d[10]), "+f"(d[11]), "+f"(d[12]), "+f"(d[13]), "+f"(d[14]), "+f"(d[15]),
        "+f"(d[16]), "+f"(d[17]), "+f"(d[18]), "+f"(d[19]), "+f"(d[20]), "+f"(d[21]), "+f"(d[22]), "+f"(d[23]),
        "+f"(d[24]), "+f"(d[25]), "+f"(d[26]), "+f"(d[27]), "+f"(d[28]), "+f"(d[29]), "+f"(d[30]), "+f"(d[31]),
        "+f"(d[32]), "+f"(d[33]), "+f"(d[34]), "+f"(d[35]), "+f"(d[36]), "+f"(d[37]), "+f"(d[38]), "+f"(d[39]),
        "+f"(d[40]), "+f"(d[41]), "+f"(d[42]), "+f"(d[43]), "+f"(d[44]), "+f"(d[45]), "+f"(d[46]), "+f"(d[47])
      : "r"(a[0]), "r"(a[1]), "r"(a[2]), "r"(a[3]), "l"(DESC), "n"(SCALE_D));
}

__device__ __forceinline__ void ldsm4(uint32_t (&r)[4], uint32_t addr) {
  asm volatile("ldmatrix.sync.aligned.m8n8.x4.shared.b16 {%0,%1,%2,%3}, [%4];"
               : "=r"(r[0]), "=r"(r[1]), "=r"(r[2]), "=r"(r[3]) : "r"(addr) : "memory");
}
__device__ __forceinline__ uint32_t badd(uint32_t a, uint32_t b) {
  uint32_t d; asm volatile("add.rn.bf16x2 %0, %1, %2;" : "=r"(d) : "r"(a), "r"(b)); return d;
}
__device__ __forceinline__ uint32_t bsub(uint32_t a, uint32_t b) {
  uint32_t d; asm volatile("sub.rn.bf16x2 %0, %1, %2;" : "=r"(d) : "r"(a), "r"(b)); return d;
}
__device__ __forceinline__ float bf_lo(uint32_t v) {
  return __uint_as_float(v << 16);
}
__device__ __forceinline__ float bf_hi(uint32_t v) { return __uint_as_float(v & 0xffff0000u); }
__device__ __forceinline__ uint32_t pack2(float lo, float hi) {
  uint32_t d; asm volatile("cvt.rn.bf16x2.f32 %0, %1, %2;" : "=r"(d) : "f"(hi), "f"(lo)); return d;
}

__device__ __forceinline__ void mbar_wait(uint32_t bar, uint32_t parity) {
  asm volatile(
      "{\n.reg .pred p;\n.reg .u32 it;\n"
      "mbarrier.try_wait.parity.shared::cta.b64 p, [%0], %1;\n"
      "@p bra WAIT_DONE;\n"
      "mov.u32 it, 0;\n"
      "WAIT_LOOP:\n"
      ".pragma \"nounroll\";\n"
      "mbarrier.try_wait.parity.shared::cta.b64 p, [%0], %1;\n"
      "@p bra WAIT_DONE;\n"
      "add.u32 it, it, 1;\n"
      "setp.lt.u32 p, it, 4194304;\n"
      "@p bra WAIT_LOOP;\n"
      "trap;\n"
      "WAIT_DONE:\n}\n" ::"r"(bar), "r"(parity) : "memory");
}
__device__ __forceinline__ void mbar_init(uint32_t bar, uint32_t count) {
  asm volatile("mbarrier.init.shared::cta.b64 [%0], %1;" ::"r"(bar), "r"(count) : "memory");
}
__device__ __forceinline__ void mbar_arrive(uint32_t bar) {
  asm volatile("mbarrier.arrive.shared::cta.b64 _, [%0];" ::"r"(bar) : "memory");
}
__device__ __forceinline__ void mbar_expect_tx(uint32_t bar, uint32_t bytes) {
  asm volatile("mbarrier.arrive.expect_tx.shared::cta.b64 _, [%0], %1;" ::"r"(bar), "r"(bytes) : "memory");
}
__device__ __forceinline__ void tma_load5(uint32_t dst, const CUtensorMap* map, uint32_t bar, int c0, int c1, int c2, int c3, int c4) {
  asm volatile("cp.async.bulk.tensor.5d.shared::cluster.global.mbarrier::complete_tx::bytes [%0], [%1, {%3,%4,%5,%6,%7}], [%2];"
               ::"r"(dst), "l"(map), "r"(bar), "r"(c0), "r"(c1), "r"(c2), "r"(c3), "r"(c4) : "memory");
}
__device__ __forceinline__ void bulk_load(uint32_t dst, const void* src, uint32_t bytes, uint32_t bar) {
  asm volatile("cp.async.bulk.shared::cluster.global.mbarrier::complete_tx::bytes [%0], [%1], %2, [%3];"
               ::"r"(dst), "l"(src), "r"(bytes), "r"(bar) : "memory");
}
template <int OFF>
__device__ __forceinline__ void st_async4(uint32_t cluster_addr, uint32_t cluster_bar, uint32_t a, uint32_t b, uint32_t c, uint32_t d) {
  asm volatile("st.async.shared::cluster.mbarrier::complete_tx::bytes.v4.b32 [%0+%6], {%2,%3,%4,%5}, [%1];"
               ::"r"(cluster_addr), "r"(cluster_bar), "r"(a), "r"(b), "r"(c), "r"(d), "n"(OFF) : "memory");
}
__device__ __forceinline__ void stsm4(uint32_t addr, uint32_t a, uint32_t b, uint32_t c, uint32_t d) {
  asm volatile("stmatrix.sync.aligned.m8n8.x4.shared.b16 [%0], {%1,%2,%3,%4};" ::"r"(addr), "r"(a), "r"(b), "r"(c), "r"(d) : "memory");
}
__device__ __forceinline__ void lds4(uint32_t (&r)[4], uint32_t addr) {
  asm volatile("ld.shared.v4.b32 {%0,%1,%2,%3}, [%4];" : "=r"(r[0]), "=r"(r[1]), "=r"(r[2]), "=r"(r[3]) : "r"(addr) : "memory");
}
__device__ __forceinline__ void sts4(uint32_t addr, const uint32_t (&r)[4]) {
  asm volatile("st.shared.v4.b32 [%0], {%1,%2,%3,%4};" ::"r"(addr), "r"(r[0]), "r"(r[1]), "r"(r[2]), "r"(r[3]) : "memory");
}
__device__ __forceinline__ void tma_store5(const CUtensorMap* map, uint32_t src, int c0, int c1, int c2, int c3, int c4) {
  asm volatile("cp.async.bulk.tensor.5d.global.shared::cta.bulk_group [%0, {%2,%3,%4,%5,%6}], [%1];"
               ::"l"(map), "r"(src), "r"(c0), "r"(c1), "r"(c2), "r"(c3), "r"(c4) : "memory");
  asm volatile("cp.async.bulk.commit_group;" ::: "memory");
}
__device__ __forceinline__ bool elect_one() {
  uint32_t p;
  asm volatile("{\n.reg .pred P;\nelect.sync _|P, 0xffffffff;\nselp.u32 %0, 1, 0, P;\n}\n" : "=r"(p));
  return p;
}
__device__ __forceinline__ uint32_t mapa(uint32_t addr, uint32_t rank) {
  uint32_t r; asm("mapa.shared::cluster.u32 %0, %1, %2;" : "=r"(r) : "r"(addr), "r"(rank)); return r;
}

__device__ __forceinline__ void tr_sum(uint32_t (&t)[3][4], const uint32_t (&U)[3][4], const uint32_t (&V)[3][4]) {
#pragma unroll
  for (int k = 0; k < 3; k++)
#pragma unroll
    for (int i = 0; i < 4; i++) t[k][i] = badd(U[k][i], V[k][i]);
}
__device__ __forceinline__ void tr_dif(uint32_t (&t)[3][4], const uint32_t (&U)[3][4], const uint32_t (&V)[3][4]) {
#pragma unroll
  for (int k = 0; k < 3; k++)
#pragma unroll
    for (int i = 0; i < 4; i++) t[k][i] = bsub(V[k][i], U[k][i]);
}
__device__ __forceinline__ void tr_t0(uint32_t (&t)[3][4], const uint32_t (&V)[3][4], const uint32_t (&E)[3][4]) {
#pragma unroll
  for (int k = 0; k < 3; k++) {
    t[k][0] = bsub(E[k][0], V[k][0]); t[k][1] = bsub(V[k][0], V[k][1]);
    t[k][2] = bsub(E[k][2], V[k][2]); t[k][3] = bsub(V[k][2], V[k][3]);
  }
}
__device__ __forceinline__ void tr_t3(uint32_t (&t)[3][4], const uint32_t (&U)[3][4], const uint32_t (&E)[3][4]) {
#pragma unroll
  for (int k = 0; k < 3; k++) {
    t[k][0] = bsub(U[k][1], U[k][0]); t[k][1] = bsub(E[k][1], U[k][1]);
    t[k][2] = bsub(U[k][3], U[k][2]); t[k][3] = bsub(E[k][3], U[k][3]);
  }
}
__device__ __forceinline__ void ld3(uint32_t (&R)[3][4], uint32_t aU, int off) {
#pragma unroll
  for (int k = 0; k < 3; k++) ldsm4(R[k], (aU ^ (32 * k)) + off);
}
template <int COMP, int AGE, int FIRST>
__device__ __forceinline__ void batch_(float (&acc)[48], const uint32_t (&t)[3][4], uint64_t bd) {
  constexpr int base = ((COMP * 3 + AGE) * 3) * BT_BYTES;
  wgmma96<FIRST ? 0 : 1>(acc, t[0], bd + ((base) >> 4));
  wgmma96<1>(acc, t[1], bd + ((base + BT_BYTES) >> 4));
  wgmma96<1>(acc, t[2], bd + ((base + 2 * BT_BYTES) >> 4));
  wg_commit();
}

template <int RANK, int I0, int I1>
__device__ __forceinline__ void butterfly(float (&X)[48], float (&Y)[48]) {
#pragma unroll
  for (int i = I0; i < I1; i++) {
    if (RANK == 0) asm volatile("sub.rn.f32 %0, %0, %1;\nfma.rn.f32 %1, %1, 0f40000000, %0;" : "+f"(X[i]), "+f"(Y[i]));
    else           asm volatile("add.rn.f32 %0, %0, %1;\nfma.rn.f32 %1, %1, 0fC0000000, %0;" : "+f"(X[i]), "+f"(Y[i]));
  }
}

struct Ctx {
  uint32_t aU, aE;
  uint32_t bar_full;
  uint32_t bar_ready;
  uint32_t xaddr, xfull;
  char* out;
  int warp;
  int u0, h0, hstep;
  int nrows;
};

template <int BUF, int C0, int C1>
__device__ __forceinline__ void load_partner(const Ctx& c, uint32_t (&P)[6][4]) {
#pragma unroll
  for (int ch = C0; ch < C1; ch++) lds4(P[ch], c.xaddr + BUF * XBUF_BYTES + (ch & 1) * 6144 + (ch >> 1) * 64);
}
template <int RANK, int BUF, int CH0>
__device__ __forceinline__ void send_chunk(const Ctx& c, const float (&X)[48]) {
  constexpr uint32_t RDELTA = RANK ? 0xFF000000u : 0x01000000u;
  constexpr int m = CH0 >> 1, s = CH0 & 1;
  uint32_t o[4];
#pragma unroll
  for (int ss = 0; ss < 4; ss++) o[ss] = pack2(X[16 * m + 4 * ss + 2 * s], X[16 * m + 4 * ss + 2 * s + 1]);
  st_async4<BUF * XBUF_BYTES + s * 6144 + m * 64>(c.xaddr + RDELTA, c.xfull + BUF * 64 + RDELTA, o[0], o[1], o[2], o[3]);
}

#define PF_START 2
#define WI0 0x404001u
#define WI1 0x110d05u
#define WI2 0x404009u
#define PF_DIST 1
#define RORD 0x654210
#define RORDS 0x6521

struct Regs {
  float X[48], Y[48];
  uint32_t T[4][2][3][4];
  uint32_t U[3][4], V[3][4], E[3][4];
  uint32_t Z[6][4], P[6][4];
};

__device__ __forceinline__ void warp_done(uint32_t bar) {
  asm volatile("fence.proxy.async.shared::cta;" ::: "memory");
  __syncwarp();
  asm volatile("{\n.reg .pred q;\nelect.sync _|q, 0xffffffff;\n@q mbarrier.arrive.shared::cta.b64 _, [%0];\n}\n" ::"r"(bar) : "memory");
}
__device__ __forceinline__ void warp_release(uint32_t bar, uint32_t a, uint32_t b, uint32_t c, uint32_t d, uint32_t zero) {
  asm volatile("{\n.reg .pred q;\n.reg .b32 t;\nlop3.b32 t, %1, %4, %5, 0x80;\nlop3.b32 t, t, %2, %3, 0x80;\nor.b32 t, t, 1;\n"
               "elect.sync _|q, 0xffffffff;\n@q mbarrier.arrive.shared::cta.b64 _, [%0], t;\n}\n"
               ::"r"(bar), "r"(a), "r"(b), "r"(c), "r"(d), "r"(zero) : "memory");
}
template <int C0, int C1>
__device__ __forceinline__ void pack_acc(uint32_t (&Z)[6][4], const float (&Y)[48]) {
#pragma unroll
  for (int ch = C0; ch < C1; ch++)
#pragma unroll
    for (int ss = 0; ss < 4; ss++) {
      const int i = 16 * (ch >> 1) + 4 * ss + 2 * (ch & 1);
      Z[ch][ss] = pack2(Y[i], Y[i + 1]);
    }
}
template <int BUF, int C0, int C1>
__device__ __forceinline__ void add_stage(const Ctx& c, uint32_t (&Z)[6][4], const uint32_t (&P)[6][4]) {
#pragma unroll
  for (int ch = C0; ch < C1; ch++)
#pragma unroll
    for (int ss = 0; ss < 4; ss++) Z[ch][ss] = badd(Z[ch][ss], P[ch][ss]);
#pragma unroll
  for (int ch = C0; ch < C1; ch++) sts4(c.xaddr + BUF * XBUF_BYTES + (ch & 1) * 6144 + (ch >> 1) * 64, Z[ch]);
}

__device__ __forceinline__ uint64_t get_bd(const Ctx& c, int n) {
  return BDESC + (uint64_t)(uint32_t)(n >> 8);
}
#define G1  batch_<0, 0, 1>(r.X, r.T[0][OLD], bd);
#define G2  batch_<0, 1, 0>(r.X, r.T[0][MID], bd);
#define G3  batch_<0, 2, 0>(r.X, r.T[0][OLD], bd);
#define G4  batch_<1, 0, 1>(r.Y, r.T[1][OLD], bd);
#define G5  batch_<1, 1, 0>(r.Y, r.T[1][MID], bd);
#define G6  batch_<1, 2, 0>(r.Y, r.T[1][OLD], bd);
#define G7  if (OLD == 1) batch_<2, 0, 0>(r.X, r.T[2][OLD], bd); else { if (!skip) { F batch_<2, 0, 0>(r.X, r.T[2][OLD], bd); } else { F wg_commit(); } F }
#define G8  batch_<2, 1, 0>(r.X, r.T[2][MID], bd);
#define G9  batch_<2, 2, 0>(r.X, r.T[2][OLD], bd);
#define G10 if (OLD == 1) batch_<3, 0, 0>(r.Y, r.T[3][OLD], bd); else { if (!skip) { F batch_<3, 0, 0>(r.Y, r.T[3][OLD], bd); } else { F wg_commit(); } F }
#define G11 batch_<3, 1, 0>(r.Y, r.T[3][MID], bd);
#define G12 batch_<3, 2, 0>(r.Y, r.T[3][OLD], bd);
#define F   wg_fence();
#define W(k) wg_wait<k>();
#define PACK pack_acc<0, 6>(r.Z, r.Y);
#define PK(a, b) pack_acc<a, b>(r.Z, r.Y);
#define XW  mbar_wait(c.xfull + MID * 64, ((n - 1) >> 1) & 1); FIX3
#define LP(a, b) load_partner<MID, a, b>(c, r.P);
#define AS(a, b) add_stage<MID, a, b>(c, r.Z, r.P);
#define LV1 if (RANK == 0) ld3(r.V, c.aU, OLD * STAGE_BYTES + OFF_V); else ld3(r.U, c.aU, OLD * STAGE_BYTES);
#define LU1 if (RANK == 0) ld3(r.U, c.aU, OLD * STAGE_BYTES); else ld3(r.V, c.aU, OLD * STAGE_BYTES + OFF_V);
#define LU2 if (RANK == 0) ld3(r.U, c.aU, MID * STAGE_BYTES); else ld3(r.V, c.aU, MID * STAGE_BYTES + OFF_V);
#define LE  ld3(r.E, c.aE, OLD * STAGE_BYTES);
#define LEk(k)  ldsm4(r.E[k], (c.aE ^ (32 * k)) + OLD * STAGE_BYTES);
#define LV1k(k) if (RANK == 0) ldsm4(r.V[k], (c.aU ^ (32 * k)) + OLD * STAGE_BYTES + OFF_V); else ldsm4(r.U[k], (c.aU ^ (32 * k)) + OLD * STAGE_BYTES);
#define LV2k(k) if (RANK == 0) ldsm4(r.V[k], (c.aU ^ (32 * k)) + MID * STAGE_BYTES + OFF_V); else ldsm4(r.U[k], (c.aU ^ (32 * k)) + MID * STAGE_BYTES);
#define LU1k(k) if (RANK == 0) ldsm4(r.U[k], (c.aU ^ (32 * k)) + OLD * STAGE_BYTES); else ldsm4(r.V[k], (c.aU ^ (32 * k)) + OLD * STAGE_BYTES + OFF_V);
#define LU2k(k) if (RANK == 0) ldsm4(r.U[k], (c.aU ^ (32 * k)) + MID * STAGE_BYTES); else ldsm4(r.V[k], (c.aU ^ (32 * k)) + MID * STAGE_BYTES + OFF_V);
#define TRS tr_sum(r.T[0][OLD], r.U, r.V);
#define TRF tr_dif(r.T[1][OLD], r.U, r.V);
#define TRC if (RANK == 0) tr_t3(r.T[2][OLD], r.U, r.E); else tr_t0(r.T[2][OLD], r.V, r.E);
#define TRD if (RANK == 0) tr_t0(r.T[3][OLD], r.V, r.E); else tr_t3(r.T[3][OLD], r.U, r.E);
#define DONE warp_done(c.bar_full + 8 * (BAR_STAGED - BAR_FULL + MID));
#define EMP warp_release(c.bar_full + 8 * (BAR_EMPTY - BAR_FULL + OLD), r.E[0][RANK], r.E[1][RANK], r.E[2][RANK], __float_as_uint(r.Y[47]), n >> 8);
#define FW  if (OLD == 1) mbar_wait(c.bar_full, ((n + 2) >> 1) & 1); \
            else mbar_wait(n ? c.bar_full + 8 : c.bar_ready, n ? ((n + 3) >> 1) & 1 : 0);
#define FIX3 if (OLD == 1 && n == 1) { mbar_wait(c.bar_full + 8, 1); SCHED_FIX3 }
#define SND(k) send_chunk<RANK, OLD, k>(c, r.X);
#define SCHED1 F G1 LV1k(0) LU1k(2) XW LP(0,1) LP(1,2) LP(2,3) LP(3,4) W(1) PK(0,1) PK(1,2) LP(4,5) LP(5,6) AS(0,1) AS(1,2) PK(2,3) AS(2,3) LV1k(1) PK(3,4) LV1k(2) PK(4,5) PK(5,6) F G2 AS(3,4) AS(4,5) AS(5,6) W(1) TRS F G4 LEk(0) F G5 W(1) TRF LEk(1) F G3 G6 LEk(2)
#define SCHED1_FIRST LEk(0) LEk(1) LEk(2)
#define SCHED_FIX3 LU1k(0) LU1k(1) LU1k(2) LV1k(0)
#define SCHED2 F G7 G8 EMP W(1) TRC F G9 DONE FW W(0) SND(0) LU2k(0) F G10 SND(1) F G11 SND(2) LU2k(1) SND(3) SND(4) W(1) TRD SND(5) F G12

template <int RANK, int OLD, bool FIRST>
__device__ __forceinline__ void phase1(const Ctx& c, int n, Regs& r) {
  constexpr int MID = 1 - OLD;
  const uint64_t bd = get_bd(c, n);
  if (FIRST) {
    wg_fence();
    batch_<0, 1, 1>(r.X, r.T[0][MID], bd);
    batch_<1, 1, 1>(r.Y, r.T[1][MID], bd);
    if ((unsigned)c.h0 < (unsigned)IMG_H) {
      wg_fence();
      batch_<0, 0, 0>(r.X, r.T[0][OLD], bd);
      batch_<1, 0, 0>(r.Y, r.T[1][OLD], bd);
    }
    mbar_wait(c.bar_full + 8 * OLD, 0);
    LU1 LV1 W(1) TRS F G3 W(1) TRF F G6
    SCHED1_FIRST
  } else {
    SCHED1
  }
}

template <int RANK, int OLD>
__device__ __forceinline__ void phase2(const Ctx& c, int n, Regs& r) {
  constexpr int MID = 1 - OLD;
  const uint64_t bd = get_bd(c, n);
  wg_wait<0>();
  butterfly<RANK, 0, 48>(r.X, r.Y);
  const bool skip = (unsigned)(c.h0 + n * c.hstep) >= (unsigned)IMG_H;
  SCHED2
}

template <int RANK>
__device__ __forceinline__ void finish_strip(const Ctx& c, Regs& r, int buf) {
  wg_wait<0>();
  pack_acc<0, 6>(r.Z, r.Y);
  const int lane = threadIdx.x & 31, g = lane >> 2;
  const int px = 8 * (c.u0 + 4 * c.warp + (g >> 1)) + (g & 1) + 2 * RANK;
  char* o = c.out + ((size_t)(c.h0 + c.nrows * c.hstep) * IMG_W + px) * (CH * 2) + (lane & 3) * 16;
  mbar_wait(c.xfull + buf * 64, ((c.nrows - 1) >> 1) & 1);
#pragma unroll
  for (int ch = 0; ch < 6; ch++) lds4(r.P[ch], c.xaddr + buf * XBUF_BYTES + (ch & 1) * 6144 + (ch >> 1) * 64);
#pragma unroll
  for (int ch = 0; ch < 6; ch++)
    asm volatile("st.global.v4.b32 [%0], {%1,%2,%3,%4};" ::"l"(o + (ch & 1) * (4 * CH * 2) + (ch >> 1) * 64), "r"(badd(r.Z[ch][0], r.P[ch][0])),
                 "r"(badd(r.Z[ch][1], r.P[ch][1])), "r"(badd(r.Z[ch][2], r.P[ch][2])), "r"(badd(r.Z[ch][3], r.P[ch][3])) : "memory");
}

__device__ __forceinline__ void transform_weights(uint32_t sbase, int rank, uint32_t items, int lane) {
  const uint32_t bar_w = sbase + OFF_BAR + 8 * BAR_W;
  const uint32_t o_w0 = (rank ? 2 : 3) * 9 * BT_BYTES, o_w2 = (rank ? 3 : 2) * 9 * BT_BYTES;
#pragma unroll 1
  for (; items; items >>= 8) {
    const int item = (items & 255) - 1;
    if (item >= 18) break;
    const uint32_t base = sbase + OFF_W + item * 1536;
    mbar_wait(bar_w + 8 * (item / 6), 0);
    uint32_t wa[3][4], wb[3][4], wd[3][4];
    const uint32_t src = base + (lane >> 2) * 192 + (lane & 3) * 16;
#pragma unroll
    for (int m = 0; m < 3; m++) lds4(wa[m], src + o_w0 + m * 64);
#pragma unroll
    for (int m = 0; m < 3; m++) lds4(wd[m], src + o_w2 + m * 64);
#pragma unroll
    for (int m = 0; m < 3; m++) lds4(wb[m], src + m * 64);
    __syncwarp();
    const uint32_t dst = base + lane * 16;
#pragma unroll
    for (int m = 0; m < 3; m++) stsm4(dst + m * 512 + o_w0, wa[m][0], wa[m][1], wa[m][2], wa[m][3]);
#pragma unroll
    for (int m = 0; m < 3; m++) stsm4(dst + m * 512 + o_w2, wd[m][0], wd[m][1], wd[m][2], wd[m][3]);
#pragma unroll
    for (int m = 0; m < 3; m++) {
      uint32_t g1[4], g2[4];
#pragma unroll
      for (int ss = 0; ss < 4; ss++) {
        const uint32_t a = wa[m][ss], b = wb[m][ss], d = wd[m][ss];
        const float slo = 0.5f * (bf_lo(a) + bf_lo(d)), shi = 0.5f * (bf_hi(a) + bf_hi(d));
        const float blo = bf_lo(b), bhi = bf_hi(b);
        g1[ss] = pack2(fmaf(blo, 0.5f, slo), fmaf(bhi, 0.5f, shi));
        g2[ss] = pack2(fmaf(blo, -0.5f, slo), fmaf(bhi, -0.5f, shi));
      }
      stsm4(dst + m * 512, g1[0], g1[1], g1[2], g1[3]);
      stsm4(dst + m * 512 + 9 * BT_BYTES, g2[0], g2[1], g2[2], g2[3]);
    }
  }
  asm volatile("fence.proxy.async.shared::cta;" ::: "memory");
  __syncwarp();
  if (elect_one()) mbar_arrive(bar_w + 24);
}

template <int RANK>
__device__ __forceinline__ void run_strip(const Ctx& c, uint32_t row0_off, uint32_t bar_row0) {
  Regs r;
#pragma unroll
  for (int m = 0; m < 2; m++) {
    const uint32_t off = m ? STAGE_BYTES : row0_off;
    mbar_wait(m ? c.bar_full + 8 : bar_row0, 0);
    if (m == 0 && (unsigned)c.h0 >= (unsigned)IMG_H) {
#pragma unroll
      for (int i = 0; i < 48; i++) asm volatile("" : "=r"(r.T[i / 12][0][(i / 4) % 3][i % 4]));
      continue;
    }
    ld3(r.U, c.aU, off);
    ld3(r.V, c.aU, off + OFF_V);
    ld3(r.E, c.aE, off);
    tr_sum(r.T[0][m], r.U, r.V);
    tr_dif(r.T[1][m], r.U, r.V);
    tr_t3(r.T[RANK == 0 ? 2 : 3][m], r.U, r.E);
    tr_t0(r.T[RANK == 0 ? 3 : 2][m], r.V, r.E);
  }
  warp_done(c.bar_full + 8 * (BAR_EMPTY - BAR_FULL + 1));
  mbar_wait(SMEM_BASE + (RANK << 24) + OFF_BAR + 8 * BAR_W + 24, 0);
#pragma unroll
  for (int i = 0; i < 48; i++) { r.X[i] = 0.f; r.Y[i] = 0.f; r.Z[i % 6][i / 12] = 0; r.P[i % 6][i / 12] = 0; }
  phase1<RANK, 0, true>(c, 0, r);
#pragma unroll 1
  for (int n = 0;; n += 2) {
    phase2<RANK, 0>(c, n, r);
    if (n + 1 == c.nrows) break;
    phase1<RANK, 1, false>(c, n + 1, r);
    phase2<RANK, 1>(c, n + 1, r);
    if (n + 2 == c.nrows) break;
    phase1<RANK, 0, false>(c, n + 2, r);
  }
  finish_strip<RANK>(c, r, (c.nrows - 1) & 1);
}

constexpr int NCL = 66;
struct Strip { int seg, h0, nrows; };
__device__ __forceinline__ bool is_down(int cl) { return cl < 2 || !((cl - 2) & 4); }
__device__ __forceinline__ Strip get_strip(int cl, int wg) {
  const int k = cl - 2, i = k >> 2;
  const int q = (i & 1) ? (wg ? 16 + 15 * i : 16 * i + 16) : (wg ? 30 + 15 * i : 16 * i - 1);
  return cl < 2 ? Strip{2 * cl + wg, -1, 16} : Strip{k & 3, 2 * q + wg, 16 - wg};
}

__device__ __forceinline__ void load_rows(const CUtensorMap* xmap, const char* x, uint32_t sbase, int rank, int wg, Strip sp, int hstep) {
  const uint32_t full = sbase + OFF_BAR + 8 * (BAR_FULL + 2 * wg), empty = full + 8 * (BAR_EMPTY - BAR_FULL);
  const uint32_t in_base = sbase + OFF_IN + wg * WG_IN_BYTES;
  const char* xseg = x + (sp.seg * 128 + rank * 64) * (CH * 2);
#pragma unroll 1
  for (int m = 3; m <= sp.nrows + 2; m++) {
    const int s = m & 1, h = sp.h0 + m * hstep;
    mbar_wait(empty + 8 * s, ((m - 3) >> 1) & 1);
    if (m == 3) {
      asm volatile("mbarrier.arrive.shared::cluster.b64 _, [%0];" ::"r"((sbase + OFF_BAR + 8 * (BAR_READY + wg)) ^ 0x01000000u) : "memory");
      mbar_wait(full, 0);
    }
    if (m <= 4) mbar_arrive(full + 8 * s);
    if (m < sp.nrows + 2) {
      mbar_expect_tx(full + 8 * s, 2 * BOX_BYTES);
      tma_load5(in_base + s * STAGE_BYTES, xmap, full + 8 * s, rank * 48, 0, sp.seg * 16, 0, h);
      tma_load5(in_base + s * STAGE_BYTES + OFF_BOXB, xmap, full + 8 * s, rank * 48, 2, sp.seg * 16 - 1, 0, h);
      const int hp = h + PF_DIST * hstep;
      if (PF_DIST > 0 && m >= 4 + PF_START && m + PF_DIST < sp.nrows + 2 && (unsigned)hp < (unsigned)IMG_H)
        asm volatile("cp.async.bulk.prefetch.L2.global [%0], %1;" ::"l"(xseg + (size_t)hp * (IMG_W * CH * 2)), "r"(64 * CH * 2) : "memory");
    } else {
      mbar_arrive(full + 8 * s);
    }
  }
}
__device__ __forceinline__ void store_rows(const CUtensorMap* omap, uint32_t sbase, int rank, int wg, Strip sp, int hstep) {
  const uint32_t full = sbase + OFF_BAR + 8 * (BAR_FULL + 2 * wg), staged = full + 8 * (BAR_STAGED - BAR_FULL);
  const uint32_t xfull = sbase + OFF_BAR + 8 * (BAR_XFULL + 4 * wg);
#pragma unroll 1
  for (int n = 0; n < sp.nrows - 1; n++) {
    const int b = n & 1;
    mbar_wait(staged + 8 * b, ((n + 1) >> 1) & 1);
    tma_store5(omap, sbase + OFF_X + (2 * wg + b) * XBUF_BYTES, 0, sp.seg * 16, 0, rank, sp.h0 + (n + 1) * hstep);
#pragma unroll
    for (int q = 0; q < 4; q++) mbar_expect_tx(xfull + 64 * b + 8 * q, X_BYTES);
    asm volatile("cp.async.bulk.wait_group.read 0;" ::: "memory");
    if (n == 0) mbar_wait(xfull + 64, 0);
    if (n + 2 < sp.nrows) asm volatile("mbarrier.arrive.shared::cluster.b64 _, [%0];" ::"r"((full + 8 * (b ^ 1)) ^ 0x01000000u) : "memory");
  }
}

__global__ void __cluster_dims__(2, 1, 1) __launch_bounds__(384, 1)
dilated_conv_wino_kernel(const __grid_constant__ CUtensorMap xmap, const __grid_constant__ CUtensorMap omap,
                         const __nv_bfloat16* __restrict__ x, const __nv_bfloat16* __restrict__ w, __nv_bfloat16* __restrict__ out) {
  extern __shared__ uint8_t smem_raw[];
  const int tid = threadIdx.x;
  const int w12 = __shfl_sync(0xffffffff, tid >> 5, 0);
  const int wg = w12 >> 2, warp = w12 & 3;
  const int lane = tid & 31;
  const int rank = blockIdx.x & 1;
  const int cl = blockIdx.x >> 1;
  const bool down = is_down(cl);
  const uint32_t sbase = SMEM_BASE + (rank << 24);
  const uint32_t b0 = sbase + OFF_BAR;
  const uint32_t bar_w = b0 + 8 * BAR_W;

  if (w12 >= 9) {
    if (elect_one()) {
      const int a = w12 - 9, i = down ? a : 2 - a;
      const char* src = reinterpret_cast<const char*>(w) + (uint32_t)((i * 6 + rank) * (3 * BT_BYTES));
      const uint32_t dst = sbase + OFF_W + a * 3 * BT_BYTES;
      mbar_init(bar_w + 8 * a, 1);
      mbar_expect_tx(bar_w + 8 * a, 9 * BT_BYTES);
      bulk_load(dst + (rank ? 2 : 3) * 9 * BT_BYTES, src, 3 * BT_BYTES, bar_w + 8 * a);
      bulk_load(dst, src + 6 * BT_BYTES, 3 * BT_BYTES, bar_w + 8 * a);
      bulk_load(dst + (rank ? 3 : 2) * 9 * BT_BYTES, src + 12 * BT_BYTES, 3 * BT_BYTES, bar_w + 8 * a);
    }
  } else if (elect_one()) {
    if (w12 < 8) {
      const uint32_t xf = b0 + 8 * (BAR_XFULL + w12);
      mbar_init(xf, 1);
      mbar_init(xf + 64, 1);
      if (w12 < 4) {
        mbar_init(b0 + 8 * (BAR_FULL + w12), 2);
        mbar_expect_tx(b0 + 8 * (BAR_FULL + w12), 2 * BOX_BYTES);
        mbar_arrive(b0 + 8 * (BAR_FULL + w12));
      } else {
        mbar_init(b0 + 8 * (BAR_EMPTY + warp), 4);
        mbar_init(b0 + 8 * (BAR_STAGED + warp), 4);
      }
      mbar_expect_tx(xf, X_BYTES);
      mbar_expect_tx(xf + 64, X_BYTES);
    } else {
      asm volatile("prefetch.tensormap [%0];" ::"l"(&xmap) : "memory");
#pragma unroll
      for (int q = 0; q < 2; q++) {
        mbar_init(b0 + 8 * (BAR_ROW0 + q), 1);
        mbar_init(b0 + 8 * (BAR_READY + q), 1);
      }
      mbar_init(bar_w + 24, 12);
#pragma unroll
      for (int q = 0; q < 2; q++) mbar_expect_tx(b0 + 8 * (BAR_ROW0 + q), 2 * BOX_BYTES);
    }
    asm volatile("fence.mbarrier_init.release.cluster;" ::: "memory");
  }
  __syncthreads();
  asm volatile("barrier.cluster.arrive.relaxed.aligned;" ::: "memory");
  const Strip s0 = get_strip(cl, 0), s1 = get_strip(cl, 1);
  const int hstep = down ? 2 : -2;
  if (w12 == 8 || w12 == 9) {
    if (elect_one()) {
#pragma unroll 1
      for (uint32_t order = cl < 2 ? RORDS : RORD; order; order >>= 4) {
        const int g = (order >> 2) & 1, m = order & 3;
        const uint32_t dst = m == 0 ? sbase + (g ? OFF_ROW0_1 : OFF_ROW0_0) : sbase + OFF_IN + g * WG_IN_BYTES + (m & 1) * STAGE_BYTES;
        const uint32_t bar = b0 + 8 * (m == 0 ? BAR_ROW0 + g : BAR_FULL + 2 * g + (m & 1));
        tma_load5(dst + warp * OFF_BOXB, &xmap, bar, rank * 48, 2 * warp, (g ? s1.seg : s0.seg) * 16 - warp, 0, (g ? s1.h0 : s0.h0) + m * hstep);
      }
      asm volatile("prefetch.tensormap [%0];" ::"l"(&omap) : "memory");
    }
    __syncwarp();
  }
  if ((uint32_t)__cvta_generic_to_shared(smem_raw) != sbase || mapa(sbase, rank ^ 1) != (sbase ^ 0x01000000u)) __trap();
  asm volatile("barrier.cluster.wait.aligned;" ::: "memory");
  transform_weights(sbase, rank, (wg == 0 ? WI0 : wg == 1 ? WI1 : WI2) + warp * 0x010101u, lane);

  if (wg == 2) {
    asm volatile("setmaxnreg.dec.sync.aligned.u32 24;");
    if (elect_one()) {
      if (warp < 2) load_rows(&xmap, reinterpret_cast<const char*>(x), sbase, rank, warp, warp ? s1 : s0, hstep);
      else store_rows(&omap, sbase, rank, warp - 2, warp == 3 ? s1 : s0, hstep);
    }
  } else {
    asm volatile("setmaxnreg.inc.sync.aligned.u32 240;");
    Ctx c;
    c.out = reinterpret_cast<char*>(out);
    c.warp = warp;
    c.bar_full = b0 + 8 * (BAR_FULL + wg * NSTAGE);
    c.bar_ready = b0 + 8 * (BAR_READY + wg);
    c.u0 = (wg ? s1.seg : s0.seg) * 16;
    c.h0 = wg ? s1.h0 : s0.h0;
    c.hstep = hstep;
    c.nrows = wg ? s1.nrows : s0.nrows;
    c.xfull = b0 + 8 * (BAR_XFULL + w12);
    const uint32_t in_base = sbase + OFF_IN + wg * WG_IN_BYTES;
    {
      const int g = lane & 7, mi = lane >> 3;
      const int rU = 8 * warp + g + ((mi & 1) ? 34 : 0);
      const int rE = 8 * warp + g + ((mi & 1) ? 2 : 70 + 34);
      const uint32_t pU = in_base + rU * 128, pE = in_base + rE * 128;
      c.aU = pU + (((mi >> 1) ^ ((pU >> 7) & 7)) << 4);
      c.aE = pE + (((mi >> 1) ^ ((pE >> 7) & 7)) << 4);
    }
    c.xaddr = sbase + OFF_X + wg * 2 * XBUF_BYTES + (warp * 8 + (lane >> 2)) * 192 + (lane & 3) * 16;
    const uint32_t row0_off = sbase + (wg ? OFF_ROW0_1 : OFF_ROW0_0) - in_base;
    const uint32_t bar_row0 = cl < 2 ? bar_w : b0 + 8 * (BAR_ROW0 + wg);
    if (rank == 0) run_strip<0>(c, row0_off, bar_row0); else run_strip<1>(c, row0_off, bar_row0);
  }
}

typedef CUresult (*EncodeTiledFn)(CUtensorMap*, CUtensorMapDataType, cuuint32_t, void*, const cuuint64_t*, const cuuint64_t*,
                                  const cuuint32_t*, const cuuint32_t*, CUtensorMapInterleave, CUtensorMapSwizzle,
                                  CUtensorMapL2promotion, CUtensorMapFloatOOBfill);

}

extern "C" void kernel_launch(void* const* d_in, const int* in_sizes, int n_in, void* d_out, int out_size) {
  (void)in_sizes; (void)n_in; (void)out_size;
  static EncodeTiledFn encode = nullptr;
  if (!encode) {
    void* fn = nullptr;
    cudaDriverEntryPointQueryResult qr;
    cudaGetDriverEntryPoint("cuTensorMapEncodeTiled", &fn, cudaEnableDefault, &qr);
    encode = (EncodeTiledFn)fn;
    cudaFuncSetAttribute(dilated_conv_wino_kernel, cudaFuncAttributeMaxDynamicSharedMemorySize, SMEM_BYTES);
  }
  CUtensorMap xmap;
  const cuuint64_t dims[5] = {CH, 4, IMG_W / 8, 2, IMG_H};
  const cuuint64_t strides[4] = {CH * 2, 8 * CH * 2, 4 * CH * 2, IMG_W * CH * 2};
  const cuuint32_t box[5] = {48, 2, 17, 2, 1};
  const cuuint32_t estr[5] = {1, 1, 1, 1, 1};
#define PROMO CU_TENSOR_MAP_L2_PROMOTION_L2_128B
  encode(&xmap, CU_TENSOR_MAP_DATA_TYPE_BFLOAT16, 5, d_in[0], dims, strides, box, estr, CU_TENSOR_MAP_INTERLEAVE_NONE,
         CU_TENSOR_MAP_SWIZZLE_128B, PROMO, CU_TENSOR_MAP_FLOAT_OOB_FILL_NONE);
  CUtensorMap omap;
  const cuuint64_t odims[5] = {2 * CH, IMG_W / 8, 2, 2, IMG_H};
  const cuuint64_t ostrides[4] = {8 * CH * 2, 4 * CH * 2, 2 * CH * 2, IMG_W * CH * 2};
  const cuuint32_t obox[5] = {2 * CH, 16, 2, 1, 1};
  encode(&omap, CU_TENSOR_MAP_DATA_TYPE_BFLOAT16, 5, d_out, odims, ostrides, obox, estr, CU_TENSOR_MAP_INTERLEAVE_NONE,
         CU_TENSOR_MAP_SWIZZLE_NONE, CU_TENSOR_MAP_L2_PROMOTION_NONE, CU_TENSOR_MAP_FLOAT_OOB_FILL_NONE);
  dilated_conv_wino_kernel<<<2 * NCL, 384, SMEM_BYTES>>>(xmap, omap, (const __nv_bfloat16*)d_in[0], (const __nv_bfloat16*)d_in[1], (__nv_bfloat16*)d_out);
}
```

```cpp
#include <cuda_runtime.h>
#include <cuda_bf16.h>
#include <cuda.h>
#include <stdint.h>

namespace {

constexpr int IMG_H = 512, IMG_W = 512, CH = 96;
constexpr int NSTAGE = 2;

constexpr int BT_BYTES   = 3072;
constexpr int W_BYTES    = 36 * BT_BYTES;
constexpr int BOX_BYTES  = 68 * 96;
constexpr int OFF_BOXB   = 70 * 128;
constexpr int STAGE_BYTES = 144 * 128;
constexpr int OFF_V      = 72 * 128;
constexpr int WG_IN_BYTES = STAGE_BYTES + 138 * 128;
constexpr int OFF_W      = 0;
constexpr int OFF_IN     = OFF_W + W_BYTES;
constexpr int OFF_X      = OFF_IN + 2 * WG_IN_BYTES;
constexpr int X_BYTES    = 3072;
constexpr int XBUF_BYTES = 4 * X_BYTES;
constexpr int SMEM_BYTES = OFF_X + 4 * XBUF_BYTES;
constexpr int OFF_ROW0_0 = OFF_X + ((OFF_IN - OFF_X) & 1023);
constexpr int OFF_ROW0_1 = OFF_X + 2 * XBUF_BYTES + ((OFF_IN + WG_IN_BYTES - OFF_X) & 1023);
constexpr int OFF_BAR    = OFF_IN + 138 * 128;
constexpr int BAR_FULL = 0, BAR_EMPTY = 4, BAR_STAGED = 8, BAR_XFULL = 12, BAR_W = 28, BAR_ROW0 = 32, BAR_READY = 34;
static_assert(SMEM_BYTES <= 232448, "shared memory");
constexpr uint32_t SMEM_BASE = 1024;
constexpr uint64_t BDESC = (uint64_t)((SMEM_BASE + OFF_W) >> 4) | ((uint64_t)(1536 >> 4) << 16) | ((uint64_t)(128 >> 4) << 32);

__device__ __forceinline__ void wg_fence()  { asm volatile("wgmma.fence.sync.aligned;" ::: "memory"); }
__device__ __forceinline__ void wg_commit() { asm volatile("wgmma.commit_group.sync.aligned;" ::: "memory"); }
template <int N> __device__ __forceinline__ void wg_wait() { asm volatile("wgmma.wait_group.sync.aligned %0;" ::"n"(N) : "memory"); }

template <int SCALE_D>
__device__ __forceinline__ void wgmma96(float (&d)[48], const uint32_t (&a)[4], uint64_t DESC) {
  asm volatile(
      "{\n.reg .pred p;\nsetp.ne.b32 p, %53, 0;\n"
      "wgmma.mma_async.sync.aligned.m64n96k16.f32.bf16.bf16 "
      "{%0,%1,%2,%3,%4,%5,%6,%7,%8,%9,%10,%11,%12,%13,%14,%15,%16,%17,%18,%19,%20,%21,%22,%23,"
      "%24,%25,%26,%27,%28,%29,%30,%31,%32,%33,%34,%35,%36,%37,%38,%39,%40,%41,%42,%43,%44,%45,%46,%47}, "
      "{%48,%49,%50,%51}, %52, p, 1, 1, 1;\n}\n"
      : "+f"(d[0]), "+f"(d[1]), "+f"(d[2]), "+f"(d[3]), "+f"(d[4]), "+f"(d[5]), "+f"(d[6]), "+f"(d[7]),
        "+f"(d[8]), "+f"(d[9]), "+f"(d[10]), "+f"(d[11]), "+f"(d[12]), "+f"(d[13]), "+f"(d[14]), "+f"(d[15]),
        "+f"(d[16]), "+f"(d[17]), "+f"(d[18]), "+f"(d[19]), "+f"(d[20]), "+f"(d[21]), "+f"(d[22]), "+f"(d[23]),
        "+f"(d[24]), "+f"(d[25]), "+f"(d[26]), "+f"(d[27]), "+f"(d[28]), "+f"(d[29]), "+f"(d[30]), "+f"(d[31]),
        "+f"(d[32]), "+f"(d[33]), "+f"(d[34]), "+f"(d[35]), "+f"(d[36]), "+f"(d[37]), "+f"(d[38]), "+f"(d[39]),
        "+f"(d[40]), "+f"(d[41]), "+f"(d[42]), "+f"(d[43]), "+f"(d[44]), "+f"(d[45]), "+f"(d[46]), "+f"(d[47])
      : "r"(a[0]), "r"(a[1]), "r"(a[2]), "r"(a[3]), "l"(DESC), "n"(SCALE_D));
}

__device__ __forceinline__ void ldsm4(uint32_t (&r)[4], uint32_t addr) {
  asm volatile("ldmatrix.sync.aligned.m8n8.x4.shared.b16 {%0,%1,%2,%3}, [%4];"
               : "=r"(r[0]), "=r"(r[1]), "=r"(r[2]), "=r"(r[3]) : "r"(addr) : "memory");
}
__device__ __forceinline__ uint32_t badd(uint32_t a, uint32_t b) {
  uint32_t d; asm volatile("add.rn.bf16x2 %0, %1, %2;" : "=r"(d) : "r"(a), "r"(b)); return d;
}
__device__ __forceinline__ uint32_t bsub(uint32_t a, uint32_t b) {
  uint32_t d; asm volatile("sub.rn.bf16x2 %0, %1, %2;" : "=r"(d) : "r"(a), "r"(b)); return d;
}
__device__ __forceinline__ float bf_lo(uint32_t v) {
  return __uint_as_float(v << 16);
}
__device__ __forceinline__ float bf_hi(uint32_t v) { return __uint_as_float(v & 0xffff0000u); }
__device__ __forceinline__ uint32_t pack2(float lo, float hi) {
  uint32_t d; asm volatile("cvt.rn.bf16x2.f32 %0, %1, %2;" : "=r"(d) : "f"(hi), "f"(lo)); return d;
}

__device__ __forceinline__ void mbar_wait(uint32_t bar, uint32_t parity) {
  asm volatile(
      "{\n.reg .pred p;\n.reg .u32 it;\n"
      "mbarrier.try_wait.parity.shared::cta.b64 p, [%0], %1;\n"
      "@p bra WAIT_DONE;\n"
      "mov.u32 it, 0;\n"
      "WAIT_LOOP:\n"
      ".pragma \"nounroll\";\n"
      "mbarrier.try_wait.parity.shared::cta.b64 p, [%0], %1;\n"
      "@p bra WAIT_DONE;\n"
      "add.u32 it, it, 1;\n"
      "setp.lt.u32 p, it, 4194304;\n"
      "@p bra WAIT_LOOP;\n"
      "trap;\n"
      "WAIT_DONE:\n}\n" ::"r"(bar), "r"(parity) : "memory");
}
__device__ __forceinline__ void mbar_init(uint32_t bar, uint32_t count) {
  asm volatile("mbarrier.init.shared::cta.b64 [%0], %1;" ::"r"(bar), "r"(count) : "memory");
}
__device__ __forceinline__ void mbar_arrive(uint32_t bar) {
  asm volatile("mbarrier.arrive.shared::cta.b64 _, [%0];" ::"r"(bar) : "memory");
}
__device__ __forceinline__ void mbar_expect_tx(uint32_t bar, uint32_t bytes) {
  asm volatile("mbarrier.arrive.expect_tx.shared::cta.b64 _, [%0], %1;" ::"r"(bar), "r"(bytes) : "memory");
}
__device__ __forceinline__ void tma_load5(uint32_t dst, const CUtensorMap* map, uint32_t bar, int c0, int c1, int c2, int c3, int c4) {
  asm volatile("cp.async.bulk.tensor.5d.shared::cluster.global.mbarrier::complete_tx::bytes [%0], [%1, {%3,%4,%5,%6,%7}], [%2];"
               ::"r"(dst), "l"(map), "r"(bar), "r"(c0), "r"(c1), "r"(c2), "r"(c3), "r"(c4) : "memory");
}
__device__ __forceinline__ void bulk_load(uint32_t dst, const void* src, uint32_t bytes, uint32_t bar) {
  asm volatile("cp.async.bulk.shared::cluster.global.mbarrier::complete_tx::bytes [%0], [%1], %2, [%3];"
               ::"r"(dst), "l"(src), "r"(bytes), "r"(bar) : "memory");
}
template <int OFF>
__device__ __forceinline__ void st_async4(uint32_t cluster_addr, uint32_t cluster_bar, uint32_t a, uint32_t b, uint32_t c, uint32_t d) {
  asm volatile("st.async.shared::cluster.mbarrier::complete_tx::bytes.v4.b32 [%0+%6], {%2,%3,%4,%5}, [%1];"
               ::"r"(cluster_addr), "r"(cluster_bar), "r"(a), "r"(b), "r"(c), "r"(d), "n"(OFF) : "memory");
}
__device__ __forceinline__ void stsm4(uint32_t addr, uint32_t a, uint32_t b, uint32_t c, uint32_t d) {
  asm volatile("stmatrix.sync.aligned.m8n8.x4.shared.b16 [%0], {%1,%2,%3,%4};" ::"r"(addr), "r"(a), "r"(b), "r"(c), "r"(d) : "memory");
}
__device__ __forceinline__ void lds4(uint32_t (&r)[4], uint32_t addr) {
  asm volatile("ld.shared.v4.b32 {%0,%1,%2,%3}, [%4];" : "=r"(r[0]), "=r"(r[1]), "=r"(r[2]), "=r"(r[3]) : "r"(addr) : "memory");
}
__device__ __forceinline__ void sts4(uint32_t addr, const uint32_t (&r)[4]) {
  asm volatile("st.shared.v4.b32 [%0], {%1,%2,%3,%4};" ::"r"(addr), "r"(r[0]), "r"(r[1]), "r"(r[2]), "r"(r[3]) : "memory");
}
__device__ __forceinline__ void tma_store5(const CUtensorMap* map, uint32_t src, int c0, int c1, int c2, int c3, int c4) {
  asm volatile("cp.async.bulk.tensor.5d.global.shared::cta.bulk_group [%0, {%2,%3,%4,%5,%6}], [%1];"
               ::"l"(map), "r"(src), "r"(c0), "r"(c1), "r"(c2), "r"(c3), "r"(c4) : "memory");
  asm volatile("cp.async.bulk.commit_group;" ::: "memory");
}
__device__ __forceinline__ bool elect_one() {
  uint32_t p;
  asm volatile("{\n.reg .pred P;\nelect.sync _|P, 0xffffffff;\nselp.u32 %0, 1, 0, P;\n}\n" : "=r"(p));
  return p;
}
__device__ __forceinline__ uint32_t mapa(uint32_t addr, uint32_t rank) {
  uint32_t r; asm("mapa.shared::cluster.u32 %0, %1, %2;" : "=r"(r) : "r"(addr), "r"(rank)); return r;
}

__device__ __forceinline__ void tr_sum(uint32_t (&t)[3][4], const uint32_t (&U)[3][4], const uint32_t (&V)[3][4]) {
#pragma unroll
  for (int k = 0; k < 3; k++)
#pragma unroll
    for (int i = 0; i < 4; i++) t[k][i] = badd(U[k][i], V[k][i]);
}
__device__ __forceinline__ void tr_dif(uint32_t (&t)[3][4], const uint32_t (&U)[3][4], const uint32_t (&V)[3][4]) {
#pragma unroll
  for (int k = 0; k < 3; k++)
#pragma unroll
    for (int i = 0; i < 4; i++) t[k][i] = bsub(V[k][i], U[k][i]);
}
__device__ __forceinline__ void tr_t0(uint32_t (&t)[3][4], const uint32_t (&V)[3][4], const uint32_t (&E)[3][4]) {
#pragma unroll
  for (int k = 0; k < 3; k++) {
    t[k][0] = bsub(E[k][0], V[k][0]); t[k][1] = bsub(V[k][0], V[k][1]);
    t[k][2] = bsub(E[k][2], V[k][2]); t[k][3] = bsub(V[k][2], V[k][3]);
  }
}
__device__ __forceinline__ void tr_t3(uint32_t (&t)[3][4], const uint32_t (&U)[3][4], const uint32_t (&E)[3][4]) {
#pragma unroll
  for (int k = 0; k < 3; k++) {
    t[k][0] = bsub(U[k][1], U[k][0]); t[k][1] = bsub(E[k][1], U[k][1]);
    t[k][2] = bsub(U[k][3], U[k][2]); t[k][3] = bsub(E[k][3], U[k][3]);
  }
}
__device__ __forceinline__ void ld3(uint32_t (&R)[3][4], uint32_t aU, int off) {
#pragma unroll
  for (int k = 0; k < 3; k++) ldsm4(R[k], (aU ^ (32 * k)) + off);
}
template <int COMP, int AGE, int FIRST>
__device__ __forceinline__ void batch_(float (&acc)[48], const uint32_t (&t)[3][4], uint64_t bd) {
  constexpr int base = ((COMP * 3 + AGE) * 3) * BT_BYTES;
  wgmma96<FIRST ? 0 : 1>(acc, t[0], bd + ((base) >> 4));
  wgmma96<1>(acc, t[1], bd + ((base + BT_BYTES) >> 4));
  wgmma96<1>(acc, t[2], bd + ((base + 2 * BT_BYTES) >> 4));
  wg_commit();
}

template <int RANK, int I0, int I1>
__device__ __forceinline__ void butterfly(float (&X)[48], float (&Y)[48]) {
#pragma unroll
  for (int i = I0; i < I1; i++) {
    if (RANK == 0) asm volatile("sub.rn.f32 %0, %0, %1;\nfma.rn.f32 %1, %1, 0f40000000, %0;" : "+f"(X[i]), "+f"(Y[i]));
    else           asm volatile("add.rn.f32 %0, %0, %1;\nfma.rn.f32 %1, %1, 0fC0000000, %0;" : "+f"(X[i]), "+f"(Y[i]));
  }
}

struct Ctx {
  uint32_t aU, aE;
  uint32_t bar_full;
  uint32_t bar_ready;
  uint32_t xaddr, xfull;
  char* out;
  int wg, warp;
  uint32_t sig;
  int u0, h0, hstep;
  int nrows;
};

template <int BUF, int C0, int C1>
__device__ __forceinline__ void load_partner(const Ctx& c, uint32_t (&P)[6][4]) {
#pragma unroll
  for (int ch = C0; ch < C1; ch++) lds4(P[ch], c.xaddr + BUF * XBUF_BYTES + (ch & 1) * 6144 + (ch >> 1) * 64);
}
template <int RANK, int BUF, int CH0>
__device__ __forceinline__ void send_chunk(const Ctx& c, const float (&X)[48]) {
  constexpr uint32_t RDELTA = RANK ? 0xFF000000u : 0x01000000u;
  constexpr int m = CH0 >> 1, s = CH0 & 1;
  uint32_t o[4];
#pragma unroll
  for (int ss = 0; ss < 4; ss++) o[ss] = pack2(X[16 * m + 4 * ss + 2 * s], X[16 * m + 4 * ss + 2 * s + 1]);
  st_async4<BUF * XBUF_BYTES + s * 6144 + m * 64>(c.xaddr + RDELTA, c.xfull + BUF * 64 + RDELTA, o[0], o[1], o[2], o[3]);
}

#define PF_START 2
#define WI0 0x404001u
#define WI1 0x110d05u
#define WI2 0x404009u
#define LOCK 1
#define PF_DIST 1
#define RORD 0x654210
#define RORDS 0x6521

struct Regs {
  float X[48], Y[48];
  uint32_t T[4][2][3][4];
  uint32_t U[3][4], V[3][4], E[3][4];
  uint32_t Z[6][4], P[6][4];
};

__device__ __forceinline__ void warp_done(uint32_t bar) {
  asm volatile("fence.proxy.async.shared::cta;" ::: "memory");
  __syncwarp();
  asm volatile("{\n.reg .pred q;\nelect.sync _|q, 0xffffffff;\n@q mbarrier.arrive.shared::cta.b64 _, [%0];\n}\n" ::"r"(bar) : "memory");
}
__device__ __forceinline__ void warp_release(uint32_t bar, uint32_t a, uint32_t b, uint32_t c, uint32_t d, uint32_t zero) {
  asm volatile("{\n.reg .pred q;\n.reg .b32 t;\nlop3.b32 t, %1, %4, %5, 0x80;\nlop3.b32 t, t, %2, %3, 0x80;\nor.b32 t, t, 1;\n"
               "elect.sync _|q, 0xffffffff;\n@q mbarrier.arrive.shared::cta.b64 _, [%0], t;\n}\n"
               ::"r"(bar), "r"(a), "r"(b), "r"(c), "r"(d), "r"(zero) : "memory");
}
__device__ __forceinline__ void warp_arrive_if(uint32_t bar, int on) {
  asm volatile("{\n.reg .pred p, q;\nelect.sync _|q, 0xffffffff;\nsetp.ne.and.s32 p, %1, 0, q;\n@p mbarrier.arrive.shared::cta.b64 _, [%0];\n}\n"
               ::"r"(bar), "r"(on) : "memory");
}
template <int C0, int C1>
__device__ __forceinline__ void pack_acc(uint32_t (&Z)[6][4], const float (&Y)[48]) {
#pragma unroll
  for (int ch = C0; ch < C1; ch++)
#pragma unroll
    for (int ss = 0; ss < 4; ss++) {
      const int i = 16 * (ch >> 1) + 4 * ss + 2 * (ch & 1);
      Z[ch][ss] = pack2(Y[i], Y[i + 1]);
    }
}
template <int BUF, int C0, int C1>
__device__ __forceinline__ void add_stage(const Ctx& c, uint32_t (&Z)[6][4], const uint32_t (&P)[6][4]) {
#pragma unroll
  for (int ch = C0; ch < C1; ch++)
#pragma unroll
    for (int ss = 0; ss < 4; ss++) Z[ch][ss] = badd(Z[ch][ss], P[ch][ss]);
#pragma unroll
  for (int ch = C0; ch < C1; ch++) sts4(c.xaddr + BUF * XBUF_BYTES + (ch & 1) * 6144 + (ch >> 1) * 64, Z[ch]);
}

__device__ __forceinline__ uint64_t get_bd(const Ctx& c, int n) {
  return BDESC + (uint64_t)(uint32_t)(n >> 8);
}
#define G1  batch_<0, 0, 1>(r.X, r.T[0][OLD], bd);
#define G2  batch_<0, 1, 0>(r.X, r.T[0][MID], bd);
#define G3  batch_<0, 2, 0>(r.X, r.T[0][OLD], bd);
#define G4  batch_<1, 0, 1>(r.Y, r.T[1][OLD], bd);
#define G5  batch_<1, 1, 0>(r.Y, r.T[1][MID], bd);
#define G6  batch_<1, 2, 0>(r.Y, r.T[1][OLD], bd);
#define G7  if (OLD == 1) batch_<2, 0, 0>(r.X, r.T[2][OLD], bd); else { if (!skip) { F batch_<2, 0, 0>(r.X, r.T[2][OLD], bd); } else { F wg_commit(); } F }
#define G8  batch_<2, 1, 0>(r.X, r.T[2][MID], bd);
#define G9  batch_<2, 2, 0>(r.X, r.T[2][OLD], bd);
#define G10 if (OLD == 1) batch_<3, 0, 0>(r.Y, r.T[3][OLD], bd); else { if (!skip) { F batch_<3, 0, 0>(r.Y, r.T[3][OLD], bd); } else { F wg_commit(); } F }
#define G11 batch_<3, 1, 0>(r.Y, r.T[3][MID], bd);
#define G12 batch_<3, 2, 0>(r.Y, r.T[3][OLD], bd);
#define F   wg_fence();
#define W(k) wg_wait<k>();
#define PACK pack_acc<0, 6>(r.Z, r.Y);
#define PK(a, b) pack_acc<a, b>(r.Z, r.Y);
#define XW  mbar_wait(c.xfull + MID * 64, ((n - 1) >> 1) & 1); FIX3
#define LP(a, b) load_partner<MID, a, b>(c, r.P);
#define AS(a, b) add_stage<MID, a, b>(c, r.Z, r.P);
#define LV1 if (RANK == 0) ld3(r.V, c.aU, OLD * STAGE_BYTES + OFF_V); else ld3(r.U, c.aU, OLD * STAGE_BYTES);
#define LU1 if (RANK == 0) ld3(r.U, c.aU, OLD * STAGE_BYTES); else ld3(r.V, c.aU, OLD * STAGE_BYTES + OFF_V);
#define LU2 if (RANK == 0) ld3(r.U, c.aU, MID * STAGE_BYTES); else ld3(r.V, c.aU, MID * STAGE_BYTES + OFF_V);
#define LE  ld3(r.E, c.aE, OLD * STAGE_BYTES);
#define LEk(k)  ldsm4(r.E[k], (c.aE ^ (32 * k)) + OLD * STAGE_BYTES);
#define LV1k(k) if (RANK == 0) ldsm4(r.V[k], (c.aU ^ (32 * k)) + OLD * STAGE_BYTES + OFF_V); else ldsm4(r.U[k], (c.aU ^ (32 * k)) + OLD * STAGE_BYTES);
#define LV2k(k) if (RANK == 0) ldsm4(r.V[k], (c.aU ^ (32 * k)) + MID * STAGE_BYTES + OFF_V); else ldsm4(r.U[k], (c.aU ^ (32 * k)) + MID * STAGE_BYTES);
#define LU1k(k) if (RANK == 0) ldsm4(r.U[k], (c.aU ^ (32 * k)) + OLD * STAGE_BYTES); else ldsm4(r.V[k], (c.aU ^ (32 * k)) + OLD * STAGE_BYTES + OFF_V);
#define LU2k(k) if (RANK == 0) ldsm4(r.U[k], (c.aU ^ (32 * k)) + MID * STAGE_BYTES); else ldsm4(r.V[k], (c.aU ^ (32 * k)) + MID * STAGE_BYTES + OFF_V);
#define TRS tr_sum(r.T[0][OLD], r.U, r.V);
#define TRF tr_dif(r.T[1][OLD], r.U, r.V);
#define TRC if (RANK == 0) tr_t3(r.T[2][OLD], r.U, r.E); else tr_t0(r.T[2][OLD], r.V, r.E);
#define TRD if (RANK == 0) tr_t0(r.T[3][OLD], r.V, r.E); else tr_t3(r.T[3][OLD], r.U, r.E);
#define SIG if (LOCK) warp_arrive_if(c.sig + 64 * (OLD ? c.wg : 1 - c.wg), OLD ? 1 : n | c.wg);
#define DONE warp_done(c.bar_full + 8 * (BAR_STAGED - BAR_FULL + MID));
#define EMP warp_release(c.bar_full + 8 * (BAR_EMPTY - BAR_FULL + OLD), r.E[0][RANK], r.E[1][RANK], r.E[2][RANK], __float_as_uint(r.Y[47]), n >> 8);
#define FW  if (OLD == 1) mbar_wait(c.bar_full, ((n + 2) >> 1) & 1); \
            else mbar_wait(n ? c.bar_full + 8 : c.bar_ready, n ? ((n + 3) >> 1) & 1 : 0);
#define FIX3 if (OLD == 1 && n == 1) { mbar_wait(c.bar_full + 8, 1); SCHED_FIX3 }
#define SND(k) send_chunk<RANK, OLD, k>(c, r.X);
#define SCHED1 F G1 LV1k(0) LU1k(2) XW LP(0,1) LP(1,2) LP(2,3) LP(3,4) W(1) PK(0,1) PK(1,2) LP(4,5) LP(5,6) AS(0,1) AS(1,2) PK(2,3) AS(2,3) LV1k(1) PK(3,4) LV1k(2) PK(4,5) PK(5,6) F G2 AS(3,4) AS(4,5) AS(5,6) W(1) TRS F G4 LEk(0) F G5 SIG W(1) TRF LEk(1) F G3 G6 LEk(2)
#define SCHED1_FIRST SIG LEk(0) LEk(1) LEk(2)
#define SCHED_FIX3 LU1k(0) LU1k(1) LU1k(2) LV1k(0)
#define SCHED2 F G7 G8 EMP W(1) TRC F G9 DONE FW W(0) SND(0) LU2k(0) F G10 SND(1) F G11 SND(2) LU2k(1) SND(3) SND(4) W(1) TRD SND(5) F G12

template <int RANK, int OLD, bool FIRST>
__device__ __forceinline__ void phase1(const Ctx& c, int n, Regs& r) {
  constexpr int MID = 1 - OLD;
  const uint64_t bd = get_bd(c, n);
  if (FIRST) {
    wg_fence();
    batch_<0, 1, 1>(r.X, r.T[0][MID], bd);
    batch_<1, 1, 1>(r.Y, r.T[1][MID], bd);
    if ((unsigned)c.h0 < (unsigned)IMG_H) {
      wg_fence();
      batch_<0, 0, 0>(r.X, r.T[0][OLD], bd);
      batch_<1, 0, 0>(r.Y, r.T[1][OLD], bd);
    }
    mbar_wait(c.bar_full + 8 * OLD, 0);
    LU1 LV1 W(1) TRS F G3 W(1) TRF F G6
    SCHED1_FIRST
  } else {
    SCHED1
  }
}

template <int RANK, int OLD>
__device__ __forceinline__ void phase2(const Ctx& c, int n, Regs& r) {
  constexpr int MID = 1 - OLD;
  const uint64_t bd = get_bd(c, n);
  wg_wait<0>();
  butterfly<RANK, 0, 48>(r.X, r.Y);
  const bool skip = (unsigned)(c.h0 + n * c.hstep) >= (unsigned)IMG_H;
  SCHED2
}

template <int RANK>
__device__ __forceinline__ void finish_strip(const Ctx& c, Regs& r, int buf) {
  if (LOCK) warp_arrive_if(c.sig + 64 * (buf ^ c.wg), 1);
  wg_wait<0>();
  pack_acc<0, 6>(r.Z, r.Y);
  const int lane = threadIdx.x & 31, g = lane >> 2;
  const int px = 8 * (c.u0 + 4 * c.warp + (g >> 1)) + (g & 1) + 2 * RANK;
  char* o = c.out + ((size_t)(c.h0 + c.nrows * c.hstep) * IMG_W + px) * (CH * 2) + (lane & 3) * 16;
  mbar_wait(c.xfull + buf * 64, ((c.nrows - 1) >> 1) & 1);
#pragma unroll
  for (int ch = 0; ch < 6; ch++) lds4(r.P[ch], c.xaddr + buf * XBUF_BYTES + (ch & 1) * 6144 + (ch >> 1) * 64);
#pragma unroll
  for (int ch = 0; ch < 6; ch++)
    asm volatile("st.global.v4.b32 [%0], {%1,%2,%3,%4};" ::"l"(o + (ch & 1) * (4 * CH * 2) + (ch >> 1) * 64), "r"(badd(r.Z[ch][0], r.P[ch][0])),
                 "r"(badd(r.Z[ch][1], r.P[ch][1])), "r"(badd(r.Z[ch][2], r.P[ch][2])), "r"(badd(r.Z[ch][3], r.P[ch][3])) : "memory");
}

__device__ __forceinline__ void transform_weights(uint32_t sbase, int rank, uint32_t items, int lane) {
  const uint32_t bar_w = sbase + OFF_BAR + 8 * BAR_W;
  const uint32_t o_w0 = (rank ? 2 : 3) * 9 * BT_BYTES, o_w2 = (rank ? 3 : 2) * 9 * BT_BYTES;
#pragma unroll 1
  for (; items; items >>= 8) {
    const int item = (items & 255) - 1;
    if (item >= 18) break;
    const uint32_t base = sbase + OFF_W + item * 1536;
    mbar_wait(bar_w + 8 * (item / 6), 0);
    uint32_t wa[3][4], wb[3][4], wd[3][4];
    const uint32_t src = base + (lane >> 2) * 192 + (lane & 3) * 16;
#pragma unroll
    for (int m = 0; m < 3; m++) lds4(wa[m], src + o_w0 + m * 64);
#pragma unroll
    for (int m = 0; m < 3; m++) lds4(wd[m], src + o_w2 + m * 64);
#pragma unroll
    for (int m = 0; m < 3; m++) lds4(wb[m], src + m * 64);
    __syncwarp();
    const uint32_t dst = base + lane * 16;
#pragma unroll
    for (int m = 0; m < 3; m++) stsm4(dst + m * 512 + o_w0, wa[m][0], wa[m][1], wa[m][2], wa[m][3]);
#pragma unroll
    for (int m = 0; m < 3; m++) stsm4(dst + m * 512 + o_w2, wd[m][0], wd[m][1], wd[m][2], wd[m][3]);
#pragma unroll
    for (int m = 0; m < 3; m++) {
      uint32_t g1[4], g2[4];
#pragma unroll
      for (int ss = 0; ss < 4; ss++) {
        const uint32_t a = wa[m][ss], b = wb[m][ss], d = wd[m][ss];
        const float slo = 0.5f * (bf_lo(a) + bf_lo(d)), shi = 0.5f * (bf_hi(a) + bf_hi(d));
        const float blo = bf_lo(b), bhi = bf_hi(b);
        g1[ss] = pack2(fmaf(blo, 0.5f, slo), fmaf(bhi, 0.5f, shi));
        g2[ss] = pack2(fmaf(blo, -0.5f, slo), fmaf(bhi, -0.5f, shi));
      }
      stsm4(dst + m * 512, g1[0], g1[1], g1[2], g1[3]);
      stsm4(dst + m * 512 + 9 * BT_BYTES, g2[0], g2[1], g2[2], g2[3]);
    }
  }
  asm volatile("fence.proxy.async.shared::cta;" ::: "memory");
  __syncwarp();
  if (elect_one()) mbar_arrive(bar_w + 24);
}

template <int RANK>
__device__ __forceinline__ void run_strip(const Ctx& c, uint32_t row0_off, uint32_t bar_row0) {
  Regs r;
#pragma unroll
  for (int m = 0; m < 2; m++) {
    const uint32_t off = m ? STAGE_BYTES : row0_off;
    mbar_wait(m ? c.bar_full + 8 : bar_row0, 0);
    if (m == 0 && (unsigned)c.h0 >= (unsigned)IMG_H) {
#pragma unroll
      for (int i = 0; i < 48; i++) asm volatile("" : "=r"(r.T[i / 12][0][(i / 4) % 3][i % 4]));
      continue;
    }
    ld3(r.U, c.aU, off);
    ld3(r.V, c.aU, off + OFF_V);
    ld3(r.E, c.aE, off);
    tr_sum(r.T[0][m], r.U, r.V);
    tr_dif(r.T[1][m], r.U, r.V);
    tr_t3(r.T[RANK == 0 ? 2 : 3][m], r.U, r.E);
    tr_t0(r.T[RANK == 0 ? 3 : 2][m], r.V, r.E);
  }
  warp_done(c.bar_full + 8 * (BAR_EMPTY - BAR_FULL + 1));
  mbar_wait(SMEM_BASE + (RANK << 24) + OFF_BAR + 8 * BAR_W + 24, 0);
#pragma unroll
  for (int i = 0; i < 48; i++) { r.X[i] = 0.f; r.Y[i] = 0.f; r.Z[i % 6][i / 12] = 0; r.P[i % 6][i / 12] = 0; }
  phase1<RANK, 0, true>(c, 0, r);
#pragma unroll 1
  for (int n = 0;; n += 2) {
    phase2<RANK, 0>(c, n, r);
    if (n + 1 == c.nrows) break;
    phase1<RANK, 1, false>(c, n + 1, r);
    phase2<RANK, 1>(c, n + 1, r);
    if (n + 2 == c.nrows) break;
    phase1<RANK, 0, false>(c, n + 2, r);
  }
  finish_strip<RANK>(c, r, (c.nrows - 1) & 1);
}

constexpr int NCL = 66;
struct Strip { int seg, h0, nrows; };
__device__ __forceinline__ bool is_down(int cl) { return cl < 2 || !((cl - 2) & 4); }
__device__ __forceinline__ Strip get_strip(int cl, int wg) {
  const int k = cl - 2, i = k >> 2;
  const int q = (i & 1) ? (wg ? 16 + 15 * i : 16 * i + 16) : (wg ? 30 + 15 * i : 16 * i - 1);
  return cl < 2 ? Strip{2 * cl + wg, -1, 16} : Strip{k & 3, 2 * q + wg, 16 - wg};
}

__device__ __forceinline__ void load_rows(const CUtensorMap* xmap, const char* x, uint32_t sbase, int rank, int wg, Strip sp, int hstep) {
  const uint32_t full = sbase + OFF_BAR + 8 * (BAR_FULL + 2 * wg), empty = full + 8 * (BAR_EMPTY - BAR_FULL);
  const uint32_t in_base = sbase + OFF_IN + wg * WG_IN_BYTES;
  const int halo = sp.seg != 3 * rank ? 6 : 0;
  const char* xseg = x + (sp.seg * 128 + (rank ? 64 : -halo)) * (CH * 2);
  const int pf_bytes = (64 + halo) * CH * 2;
#pragma unroll 1
  for (int m = 3; m <= sp.nrows + 2; m++) {
    const int s = m & 1, h = sp.h0 + m * hstep;
    mbar_wait(empty + 8 * s, ((m - 3) >> 1) & 1);
    if (m == 3) {
      asm volatile("mbarrier.arrive.shared::cluster.b64 _, [%0];" ::"r"((sbase + OFF_BAR + 8 * (BAR_READY + wg)) ^ 0x01000000u) : "memory");
      mbar_wait(full, 0);
    }
    if (m <= 4) mbar_arrive(full + 8 * s);
    if (m < sp.nrows + 2) {
      const int hp = h + PF_DIST * hstep;
      const bool pf = PF_DIST > 0 && m >= 4 + PF_START && m + PF_DIST < sp.nrows + 2 && (unsigned)hp < (unsigned)IMG_H;
      mbar_expect_tx(full + 8 * s, 2 * BOX_BYTES);
      tma_load5(in_base + s * STAGE_BYTES, xmap, full + 8 * s, rank * 48, 0, sp.seg * 16, 0, h);
      tma_load5(in_base + s * STAGE_BYTES + OFF_BOXB, xmap, full + 8 * s, rank * 48, 2, sp.seg * 16 - 1, 0, h);
      if (pf) asm volatile("cp.async.bulk.prefetch.L2.global [%0], %1;" ::"l"(xseg + (size_t)hp * (IMG_W * CH * 2)), "r"(pf_bytes) : "memory");
    } else {
      mbar_arrive(full + 8 * s);
    }
  }
}
__device__ __forceinline__ void store_rows(const CUtensorMap* omap, uint32_t sbase, int rank, int wg, Strip sp, int hstep) {
  const uint32_t full = sbase + OFF_BAR + 8 * (BAR_FULL + 2 * wg), staged = full + 8 * (BAR_STAGED - BAR_FULL);
  const uint32_t xfull = sbase + OFF_BAR + 8 * (BAR_XFULL + 4 * wg);
#pragma unroll 1
  for (int n = 0; n < sp.nrows - 1; n++) {
    const int b = n & 1;
    mbar_wait(staged + 8 * b, ((n + 1) >> 1) & 1);
    tma_store5(omap, sbase + OFF_X + (2 * wg + b) * XBUF_BYTES, 0, sp.seg * 16, 0, rank, sp.h0 + (n + 1) * hstep);
#pragma unroll
    for (int q = 0; q < 4; q++) mbar_expect_tx(xfull + 64 * b + 8 * q, X_BYTES);
    asm volatile("cp.async.bulk.wait_group.read 0;" ::: "memory");
    if (n == 0) mbar_wait(xfull + 64, 0);
    if (n + 2 < sp.nrows) asm volatile("mbarrier.arrive.shared::cluster.b64 _, [%0];" ::"r"((full + 8 * (b ^ 1)) ^ 0x01000000u) : "memory");
  }
}

__global__ void __cluster_dims__(2, 1, 1) __launch_bounds__(384, 1)
dilated_conv_wino_kernel(const __grid_constant__ CUtensorMap xmap, const __grid_constant__ CUtensorMap omap,
                         const __nv_bfloat16* __restrict__ x, const __nv_bfloat16* __restrict__ w, __nv_bfloat16* __restrict__ out) {
  extern __shared__ uint8_t smem_raw[];
  const int tid = threadIdx.x;
  const int w12 = __shfl_sync(0xffffffff, tid >> 5, 0);
  const int wg = w12 >> 2, warp = w12 & 3;
  const int lane = tid & 31;
  const int rank = blockIdx.x & 1;
  const int cl = blockIdx.x >> 1;
  const bool down = is_down(cl);
  const uint32_t sbase = SMEM_BASE + (rank << 24);
  const uint32_t b0 = sbase + OFF_BAR;
  const uint32_t bar_w = b0 + 8 * BAR_W;

  if (w12 >= 9) {
    if (elect_one()) {
      const int a = w12 - 9, i = down ? a : 2 - a;
      const char* src = reinterpret_cast<const char*>(w) + (uint32_t)((i * 6 + rank) * (3 * BT_BYTES));
      const uint32_t dst = sbase + OFF_W + a * 3 * BT_BYTES;
      mbar_init(bar_w + 8 * a, 1);
      mbar_expect_tx(bar_w + 8 * a, 9 * BT_BYTES);
      bulk_load(dst + (rank ? 2 : 3) * 9 * BT_BYTES, src, 3 * BT_BYTES, bar_w + 8 * a);
      bulk_load(dst, src + 6 * BT_BYTES, 3 * BT_BYTES, bar_w + 8 * a);
      bulk_load(dst + (rank ? 3 : 2) * 9 * BT_BYTES, src + 12 * BT_BYTES, 3 * BT_BYTES, bar_w + 8 * a);
    }
  } else if (elect_one()) {
    if (w12 < 8) {
      const uint32_t xf = b0 + 8 * (BAR_XFULL + w12);
      mbar_init(xf, 1 + LOCK);
      mbar_init(xf + 64, 1 + LOCK);
      if (w12 < 4) {
        mbar_init(b0 + 8 * (BAR_FULL + w12), 2);
        mbar_expect_tx(b0 + 8 * (BAR_FULL + w12), 2 * BOX_BYTES);
        mbar_arrive(b0 + 8 * (BAR_FULL + w12));
      } else {
        mbar_init(b0 + 8 * (BAR_EMPTY + warp), 4);
        mbar_init(b0 + 8 * (BAR_STAGED + warp), 4);
      }
      mbar_expect_tx(xf, X_BYTES);
      mbar_expect_tx(xf + 64, X_BYTES);
    } else {
      asm volatile("prefetch.tensormap [%0];" ::"l"(&xmap) : "memory");
#pragma unroll
      for (int q = 0; q < 2; q++) {
        mbar_init(b0 + 8 * (BAR_ROW0 + q), 1);
        mbar_init(b0 + 8 * (BAR_READY + q), 1);
      }
      mbar_init(bar_w + 24, 12);
#pragma unroll
      for (int q = 0; q < 2; q++) mbar_expect_tx(b0 + 8 * (BAR_ROW0 + q), 2 * BOX_BYTES);
    }
    asm volatile("fence.mbarrier_init.release.cluster;" ::: "memory");
  }
  __syncthreads();
  asm volatile("barrier.cluster.arrive.relaxed.aligned;" ::: "memory");
  const Strip s0 = get_strip(cl, 0), s1 = get_strip(cl, 1);
  const int hstep = down ? 2 : -2;
  if (w12 == 8 || w12 == 9) {
    if (elect_one()) {
#pragma unroll 1
      for (uint32_t order = cl < 2 ? RORDS : RORD; order; order >>= 4) {
        const int g = (order >> 2) & 1, m = order & 3;
        const uint32_t dst = m == 0 ? sbase + (g ? OFF_ROW0_1 : OFF_ROW0_0) : sbase + OFF_IN + g * WG_IN_BYTES + (m & 1) * STAGE_BYTES;
        const uint32_t bar = b0 + 8 * (m == 0 ? BAR_ROW0 + g : BAR_FULL + 2 * g + (m & 1));
        tma_load5(dst + warp * OFF_BOXB, &xmap, bar, rank * 48, 2 * warp, (g ? s1.seg : s0.seg) * 16 - warp, 0, (g ? s1.h0 : s0.h0) + m * hstep);
      }
      asm volatile("prefetch.tensormap [%0];" ::"l"(&omap) : "memory");
    }
    __syncwarp();
  }
  if ((uint32_t)__cvta_generic_to_shared(smem_raw) != sbase || mapa(sbase, rank ^ 1) != (sbase ^ 0x01000000u)) __trap();
  asm volatile("barrier.cluster.wait.aligned;" ::: "memory");
  transform_weights(sbase, rank, (wg == 0 ? WI0 : wg == 1 ? WI1 : WI2) + warp * 0x010101u, lane);

  if (wg == 2) {
    asm volatile("setmaxnreg.dec.sync.aligned.u32 24;");
    if (elect_one()) {
      if (warp < 2) load_rows(&xmap, reinterpret_cast<const char*>(x), sbase, rank, warp, warp ? s1 : s0, hstep);
      else store_rows(&omap, sbase, rank, warp - 2, warp == 3 ? s1 : s0, hstep);
    }
  } else {
    asm volatile("setmaxnreg.inc.sync.aligned.u32 240;");
    Ctx c;
    c.out = reinterpret_cast<char*>(out);
    c.wg = wg;
    c.warp = warp;
    c.sig = b0 + 8 * (BAR_XFULL + (w12 ^ 4));
    c.bar_full = b0 + 8 * (BAR_FULL + wg * NSTAGE);
    c.bar_ready = b0 + 8 * (BAR_READY + wg);
    c.u0 = (wg ? s1.seg : s0.seg) * 16;
    c.h0 = wg ? s1.h0 : s0.h0;
    c.hstep = hstep;
    c.nrows = wg ? s1.nrows : s0.nrows;
    c.xfull = b0 + 8 * (BAR_XFULL + w12);
    const uint32_t in_base = sbase + OFF_IN + wg * WG_IN_BYTES;
    {
      const int g = lane & 7, mi = lane >> 3;
      const int rU = 8 * warp + g + ((mi & 1) ? 34 : 0);
      const int rE = 8 * warp + g + ((mi & 1) ? 2 : 70 + 34);
      const uint32_t pU = in_base + rU * 128, pE = in_base + rE * 128;
      c.aU = pU + (((mi >> 1) ^ ((pU >> 7) & 7)) << 4);
      c.aE = pE + (((mi >> 1) ^ ((pE >> 7) & 7)) << 4);
    }
    c.xaddr = sbase + OFF_X + wg * 2 * XBUF_BYTES + (warp * 8 + (lane >> 2)) * 192 + (lane & 3) * 16;
    const uint32_t row0_off = sbase + (wg ? OFF_ROW0_1 : OFF_ROW0_0) - in_base;
    const uint32_t bar_row0 = cl < 2 ? bar_w : b0 + 8 * (BAR_ROW0 + wg);
    if (rank == 0) run_strip<0>(c, row0_off, bar_row0); else run_strip<1>(c, row0_off, bar_row0);
  }
}

typedef CUresult (*EncodeTiledFn)(CUtensorMap*, CUtensorMapDataType, cuuint32_t, void*, const cuuint64_t*, const cuuint64_t*,
                                  const cuuint32_t*, const cuuint32_t*, CUtensorMapInterleave, CUtensorMapSwizzle,
                                  CUtensorMapL2promotion, CUtensorMapFloatOOBfill);

}

extern "C" void kernel_launch(void* const* d_in, const int* in_sizes, int n_in, void* d_out, int out_size) {
  (void)in_sizes; (void)n_in; (void)out_size;
  static EncodeTiledFn encode = nullptr;
  if (!encode) {
    void* fn = nullptr;
    cudaDriverEntryPointQueryResult qr;
    cudaGetDriverEntryPoint("cuTensorMapEncodeTiled", &fn, cudaEnableDefault, &qr);
    encode = (EncodeTiledFn)fn;
    cudaFuncSetAttribute(dilated_conv_wino_kernel, cudaFuncAttributeMaxDynamicSharedMemorySize, SMEM_BYTES);
  }
  CUtensorMap xmap;
  const cuuint64_t dims[5] = {CH, 4, IMG_W / 8, 2, IMG_H};
  const cuuint64_t strides[4] = {CH * 2, 8 * CH * 2, 4 * CH * 2, IMG_W * CH * 2};
  const cuuint32_t box[5] = {48, 2, 17, 2, 1};
  const cuuint32_t estr[5] = {1, 1, 1, 1, 1};
#define PROMO CU_TENSOR_MAP_L2_PROMOTION_L2_128B
  encode(&xmap, CU_TENSOR_MAP_DATA_TYPE_BFLOAT16, 5, d_in[0], dims, strides, box, estr, CU_TENSOR_MAP_INTERLEAVE_NONE,
         CU_TENSOR_MAP_SWIZZLE_128B, PROMO, CU_TENSOR_MAP_FLOAT_OOB_FILL_NONE);
  CUtensorMap omap;
  const cuuint64_t odims[5] = {2 * CH, IMG_W / 8, 2, 2, IMG_H};
  const cuuint64_t ostrides[4] = {8 * CH * 2, 4 * CH * 2, 2 * CH * 2, IMG_W * CH * 2};
  const cuuint32_t obox[5] = {2 * CH, 16, 2, 1, 1};
  encode(&omap, CU_TENSOR_MAP_DATA_TYPE_BFLOAT16, 5, d_out, odims, ostrides, obox, estr, CU_TENSOR_MAP_INTERLEAVE_NONE,
         CU_TENSOR_MAP_SWIZZLE_NONE, CU_TENSOR_MAP_L2_PROMOTION_NONE, CU_TENSOR_MAP_FLOAT_OOB_FILL_NONE);
  dilated_conv_wino_kernel<<<2 * NCL, 384, SMEM_BYTES>>>(xmap, omap, (const __nv_bfloat16*)d_in[0], (const __nv_bfloat16*)d_in[1], (__nv_bfloat16*)d_out);
}
```

```cpp
#include <cuda_runtime.h>
#include <cuda_bf16.h>
#include <cuda.h>
#include <stdint.h>

namespace {

constexpr int IMG_H = 512, IMG_W = 512, CH = 96;
constexpr int NSTAGE = 2;

constexpr int BT_BYTES   = 3072;
constexpr int W_BYTES    = 36 * BT_BYTES;
constexpr int BOX_BYTES  = 68 * 96;
constexpr int OFF_BOXB   = 70 * 128;
constexpr int STAGE_BYTES = 144 * 128;
constexpr int OFF_V      = 72 * 128;
constexpr int WG_IN_BYTES = STAGE_BYTES + 138 * 128;
constexpr int OFF_W      = 0;
constexpr int OFF_IN     = OFF_W + W_BYTES;
constexpr int OFF_X      = OFF_IN + 2 * WG_IN_BYTES;
constexpr int X_BYTES    = 3072;
constexpr int XBUF_BYTES = 4 * X_BYTES;
constexpr int SMEM_BYTES = OFF_X + 4 * XBUF_BYTES;
constexpr int OFF_ROW0_0 = OFF_X + ((OFF_IN - OFF_X) & 1023);
constexpr int OFF_ROW0_1 = OFF_X + 2 * XBUF_BYTES + ((OFF_IN + WG_IN_BYTES - OFF_X) & 1023);
constexpr int OFF_BAR    = OFF_IN + 138 * 128;
constexpr int BAR_FULL = 0, BAR_EMPTY = 4, BAR_STAGED = 8, BAR_XFULL = 12, BAR_W = 28, BAR_ROW0 = 32, BAR_READY = 34;
static_assert(SMEM_BYTES <= 232448, "shared memory");
constexpr uint32_t SMEM_BASE = 1024;
constexpr uint64_t BDESC = (uint64_t)((SMEM_BASE + OFF_W) >> 4) | ((uint64_t)(1536 >> 4) << 16) | ((uint64_t)(128 >> 4) << 32);

__device__ __forceinline__ void wg_fence()  { asm volatile("wgmma.fence.sync.aligned;" ::: "memory"); }
__device__ __forceinline__ void wg_commit() { asm volatile("wgmma.commit_group.sync.aligned;" ::: "memory"); }
template <int N> __device__ __forceinline__ void wg_wait() { asm volatile("wgmma.wait_group.sync.aligned %0;" ::"n"(N) : "memory"); }

template <int SCALE_D>
__device__ __forceinline__ void wgmma96(float (&d)[48], const uint32_t (&a)[4], uint64_t DESC) {
  asm volatile(
      "{\n.reg .pred p;\nsetp.ne.b32 p, %53, 0;\n"
      "wgmma.mma_async.sync.aligned.m64n96k16.f32.bf16.bf16 "
      "{%0,%1,%2,%3,%4,%5,%6,%7,%8,%9,%10,%11,%12,%13,%14,%15,%16,%17,%18,%19,%20,%21,%22,%23,"
      "%24,%25,%26,%27,%28,%29,%30,%31,%32,%33,%34,%35,%36,%37,%38,%39,%40,%41,%42,%43,%44,%45,%46,%47}, "
      "{%48,%49,%50,%51}, %52, p, 1, 1, 1;\n}\n"
      : "+f"(d[0]), "+f"(d[1]), "+f"(d[2]), "+f"(d[3]), "+f"(d[4]), "+f"(d[5]), "+f"(d[6]), "+f"(d[7]),
        "+f"(d[8]), "+f"(d[9]), "+f"(d[10]), "+f"(d[11]), "+f"(d[12]), "+f"(d[13]), "+f"(d[14]), "+f"(d[15]),
        "+f"(d[16]), "+f"(d[17]), "+f"(d[18]), "+f"(d[19]), "+f"(d[20]), "+f"(d[21]), "+f"(d[22]), "+f"(d[23]),
        "+f"(d[24]), "+f"(d[25]), "+f"(d[26]), "+f"(d[27]), "+f"(d[28]), "+f"(d[29]), "+f"(d[30]), "+f"(d[31]),
        "+f"(d[32]), "+f"(d[33]), "+f"(d[34]), "+f"(d[35]), "+f"(d[36]), "+f"(d[37]), "+f"(d[38]), "+f"(d[39]),
        "+f"(d[40]), "+f"(d[41]), "+f"(d[42]), "+f"(d[43]), "+f"(d[44]), "+f"(d[45]), "+f"(d[46]), "+f"(d[47])
      : "r"(a[0]), "r"(a[1]), "r"(a[2]), "r"(a[3]), "l"(DESC), "n"(SCALE_D));
}

__device__ __forceinline__ void ldsm4(uint32_t (&r)[4], uint32_t addr) {
  asm volatile("ldmatrix.sync.aligned.m8n8.x4.shared.b16 {%0,%1,%2,%3}, [%4];"
               : "=r"(r[0]), "=r"(r[1]), "=r"(r[2]), "=r"(r[3]) : "r"(addr) : "memory");
}
__device__ __forceinline__ uint32_t badd(uint32_t a, uint32_t b) {
  uint32_t d; asm volatile("add.rn.bf16x2 %0, %1, %2;" : "=r"(d) : "r"(a), "r"(b)); return d;
}
__device__ __forceinline__ uint32_t bsub(uint32_t a, uint32_t b) {
  uint32_t d; asm volatile("sub.rn.bf16x2 %0, %1, %2;" : "=r"(d) : "r"(a), "r"(b)); return d;
}
__device__ __forceinline__ float bf_lo(uint32_t v) {
  return __uint_as_float(v << 16);
}
__device__ __forceinline__ float bf_hi(uint32_t v) { return __uint_as_float(v & 0xffff0000u); }
__device__ __forceinline__ uint32_t pack2(float lo, float hi) {
  uint32_t d; asm volatile("cvt.rn.bf16x2.f32 %0, %1, %2;" : "=r"(d) : "f"(hi), "f"(lo)); return d;
}

__device__ __forceinline__ void mbar_wait(uint32_t bar, uint32_t parity) {
  asm volatile(
      "{\n.reg .pred p;\n.reg .u32 it;\n"
      "mbarrier.try_wait.parity.shared::cta.b64 p, [%0], %1;\n"
      "@p bra WAIT_DONE;\n"
      "mov.u32 it, 0;\n"
      "WAIT_LOOP:\n"
      ".pragma \"nounroll\";\n"
      "mbarrier.try_wait.parity.shared::cta.b64 p, [%0], %1;\n"
      "@p bra WAIT_DONE;\n"
      "add.u32 it, it, 1;\n"
      "setp.lt.u32 p, it, 4194304;\n"
      "@p bra WAIT_LOOP;\n"
      "trap;\n"
      "WAIT_DONE:\n}\n" ::"r"(bar), "r"(parity) : "memory");
}
__device__ __forceinline__ void mbar_init(uint32_t bar, uint32_t count) {
  asm volatile("mbarrier.init.shared::cta.b64 [%0], %1;" ::"r"(bar), "r"(count) : "memory");
}
__device__ __forceinline__ void mbar_arrive(uint32_t bar) {
  asm volatile("mbarrier.arrive.shared::cta.b64 _, [%0];" ::"r"(bar) : "memory");
}
__device__ __forceinline__ void mbar_expect_tx(uint32_t bar, uint32_t bytes) {
  asm volatile("mbarrier.arrive.expect_tx.shared::cta.b64 _, [%0], %1;" ::"r"(bar), "r"(bytes) : "memory");
}
__device__ __forceinline__ void tma_load5(uint32_t dst, const CUtensorMap* map, uint32_t bar, int c0, int c1, int c2, int c3, int c4) {
  asm volatile("cp.async.bulk.tensor.5d.shared::cluster.global.mbarrier::complete_tx::bytes [%0], [%1, {%3,%4,%5,%6,%7}], [%2];"
               ::"r"(dst), "l"(map), "r"(bar), "r"(c0), "r"(c1), "r"(c2), "r"(c3), "r"(c4) : "memory");
}
__device__ __forceinline__ void bulk_load(uint32_t dst, const void* src, uint32_t bytes, uint32_t bar) {
  asm volatile("cp.async.bulk.shared::cluster.global.mbarrier::complete_tx::bytes [%0], [%1], %2, [%3];"
               ::"r"(dst), "l"(src), "r"(bytes), "r"(bar) : "memory");
}
template <int OFF>
__device__ __forceinline__ void st_async4(uint32_t cluster_addr, uint32_t cluster_bar, uint32_t a, uint32_t b, uint32_t c, uint32_t d) {
  asm volatile("st.async.shared::cluster.mbarrier::complete_tx::bytes.v4.b32 [%0+%6], {%2,%3,%4,%5}, [%1];"
               ::"r"(cluster_addr), "r"(cluster_bar), "r"(a), "r"(b), "r"(c), "r"(d), "n"(OFF) : "memory");
}
__device__ __forceinline__ void stsm4(uint32_t addr, uint32_t a, uint32_t b, uint32_t c, uint32_t d) {
  asm volatile("stmatrix.sync.aligned.m8n8.x4.shared.b16 [%0], {%1,%2,%3,%4};" ::"r"(addr), "r"(a), "r"(b), "r"(c), "r"(d) : "memory");
}
__device__ __forceinline__ void lds4(uint32_t (&r)[4], uint32_t addr) {
  asm volatile("ld.shared.v4.b32 {%0,%1,%2,%3}, [%4];" : "=r"(r[0]), "=r"(r[1]), "=r"(r[2]), "=r"(r[3]) : "r"(addr) : "memory");
}
__device__ __forceinline__ void sts4(uint32_t addr, const uint32_t (&r)[4]) {
  asm volatile("st.shared.v4.b32 [%0], {%1,%2,%3,%4};" ::"r"(addr), "r"(r[0]), "r"(r[1]), "r"(r[2]), "r"(r[3]) : "memory");
}
__device__ __forceinline__ void tma_store5(const CUtensorMap* map, uint32_t src, int c0, int c1, int c2, int c3, int c4) {
  asm volatile("cp.async.bulk.tensor.5d.global.shared::cta.bulk_group [%0, {%2,%3,%4,%5,%6}], [%1];"
               ::"l"(map), "r"(src), "r"(c0), "r"(c1), "r"(c2), "r"(c3), "r"(c4) : "memory");
  asm volatile("cp.async.bulk.commit_group;" ::: "memory");
}
__device__ __forceinline__ bool elect_one() {
  uint32_t p;
  asm volatile("{\n.reg .pred P;\nelect.sync _|P, 0xffffffff;\nselp.u32 %0, 1, 0, P;\n}\n" : "=r"(p));
  return p;
}
__device__ __forceinline__ uint32_t mapa(uint32_t addr, uint32_t rank) {
  uint32_t r; asm("mapa.shared::cluster.u32 %0, %1, %2;" : "=r"(r) : "r"(addr), "r"(rank)); return r;
}

__device__ __forceinline__ void tr_sum(uint32_t (&t)[3][4], const uint32_t (&U)[3][4], const uint32_t (&V)[3][4]) {
#pragma unroll
  for (int k = 0; k < 3; k++)
#pragma unroll
    for (int i = 0; i < 4; i++) t[k][i] = badd(U[k][i], V[k][i]);
}
__device__ __forceinline__ void tr_dif(uint32_t (&t)[3][4], const uint32_t (&U)[3][4], const uint32_t (&V)[3][4]) {
#pragma unroll
  for (int k = 0; k < 3; k++)
#pragma unroll
    for (int i = 0; i < 4; i++) t[k][i] = bsub(V[k][i], U[k][i]);
}
__device__ __forceinline__ void tr_t0(uint32_t (&t)[3][4], const uint32_t (&V)[3][4], const uint32_t (&E)[3][4]) {
#pragma unroll
  for (int k = 0; k < 3; k++) {
    t[k][0] = bsub(E[k][0], V[k][0]); t[k][1] = bsub(V[k][0], V[k][1]);
    t[k][2] = bsub(E[k][2], V[k][2]); t[k][3] = bsub(V[k][2], V[k][3]);
  }
}
__device__ __forceinline__ void tr_t3(uint32_t (&t)[3][4], const uint32_t (&U)[3][4], const uint32_t (&E)[3][4]) {
#pragma unroll
  for (int k = 0; k < 3; k++) {
    t[k][0] = bsub(U[k][1], U[k][0]); t[k][1] = bsub(E[k][1], U[k][1]);
    t[k][2] = bsub(U[k][3], U[k][2]); t[k][3] = bsub(E[k][3], U[k][3]);
  }
}
__device__ __forceinline__ void ld3(uint32_t (&R)[3][4], uint32_t aU, int off) {
#pragma unroll
  for (int k = 0; k < 3; k++) ldsm4(R[k], (aU ^ (32 * k)) + off);
}
template <int COMP, int AGE, int FIRST>
__device__ __forceinline__ void batch_(float (&acc)[48], const uint32_t (&t)[3][4], uint64_t bd) {
  constexpr int base = ((COMP * 3 + AGE) * 3) * BT_BYTES;
  wgmma96<FIRST ? 0 : 1>(acc, t[0], bd + ((base) >> 4));
  wgmma96<1>(acc, t[1], bd + ((base + BT_BYTES) >> 4));
  wgmma96<1>(acc, t[2], bd + ((base + 2 * BT_BYTES) >> 4));
  wg_commit();
}

template <int RANK, int I0, int I1>
__device__ __forceinline__ void butterfly(float (&X)[48], float (&Y)[48]) {
#pragma unroll
  for (int i = I0; i < I1; i++) {
    if (RANK == 0) asm volatile("sub.rn.f32 %0, %0, %1;\nfma.rn.f32 %1, %1, 0f40000000, %0;" : "+f"(X[i]), "+f"(Y[i]));
    else           asm volatile("add.rn.f32 %0, %0, %1;\nfma.rn.f32 %1, %1, 0fC0000000, %0;" : "+f"(X[i]), "+f"(Y[i]));
  }
}

struct Ctx {
  uint32_t aU, aE;
  uint32_t bar_full;
  uint32_t bar_ready;
  uint32_t xaddr, xfull;
  char* out;
  int wg, warp;
  uint32_t sig;
  int u0, h0, hstep;
  int nrows;
};

template <int BUF, int C0, int C1>
__device__ __forceinline__ void load_partner(const Ctx& c, uint32_t (&P)[6][4]) {
#pragma unroll
  for (int ch = C0; ch < C1; ch++) lds4(P[ch], c.xaddr + BUF * XBUF_BYTES + (ch & 1) * 6144 + (ch >> 1) * 64);
}
template <int RANK, int BUF, int CH0>
__device__ __forceinline__ void send_chunk(const Ctx& c, const float (&X)[48]) {
  constexpr uint32_t RDELTA = RANK ? 0xFF000000u : 0x01000000u;
  constexpr int m = CH0 >> 1, s = CH0 & 1;
  uint32_t o[4];
#pragma unroll
  for (int ss = 0; ss < 4; ss++) o[ss] = pack2(X[16 * m + 4 * ss + 2 * s], X[16 * m + 4 * ss + 2 * s + 1]);
  st_async4<BUF * XBUF_BYTES + s * 6144 + m * 64>(c.xaddr + RDELTA, c.xfull + BUF * 64 + RDELTA, o[0], o[1], o[2], o[3]);
}

#define PF_START 2
#define WI0 0x404001u
#define WI1 0x110d05u
#define WI2 0x404009u
#define LOCK 1
#define PF_DIST 1
#define RORD 0x654210
#define RORDS 0x6521

struct Regs {
  float X[48], Y[48];
  uint32_t T[4][2][3][4];
  uint32_t U[3][4], V[3][4], E[3][4];
  uint32_t Z[6][4], P[6][4];
};

__device__ __forceinline__ void warp_done(uint32_t bar) {
  asm volatile("fence.proxy.async.shared::cta;" ::: "memory");
  __syncwarp();
  asm volatile("{\n.reg .pred q;\nelect.sync _|q, 0xffffffff;\n@q mbarrier.arrive.shared::cta.b64 _, [%0];\n}\n" ::"r"(bar) : "memory");
}
__device__ __forceinline__ void warp_release(uint32_t bar, uint32_t a, uint32_t b, uint32_t c, uint32_t d, uint32_t zero) {
  asm volatile("{\n.reg .pred q;\n.reg .b32 t;\nlop3.b32 t, %1, %4, %5, 0x80;\nlop3.b32 t, t, %2, %3, 0x80;\nor.b32 t, t, 1;\n"
               "elect.sync _|q, 0xffffffff;\n@q mbarrier.arrive.shared::cta.b64 _, [%0], t;\n}\n"
               ::"r"(bar), "r"(a), "r"(b), "r"(c), "r"(d), "r"(zero) : "memory");
}
__device__ __forceinline__ void warp_arrive_if(uint32_t bar, int on) {
  asm volatile("{\n.reg .pred p, q;\nelect.sync _|q, 0xffffffff;\nsetp.ne.and.s32 p, %1, 0, q;\n@p mbarrier.arrive.shared::cta.b64 _, [%0];\n}\n"
               ::"r"(bar), "r"(on) : "memory");
}
template <int C0, int C1>
__device__ __forceinline__ void pack_acc(uint32_t (&Z)[6][4], const float (&Y)[48]) {
#pragma unroll
  for (int ch = C0; ch < C1; ch++)
#pragma unroll
    for (int ss = 0; ss < 4; ss++) {
      const int i = 16 * (ch >> 1) + 4 * ss + 2 * (ch & 1);
      Z[ch][ss] = pack2(Y[i], Y[i + 1]);
    }
}
template <int BUF, int C0, int C1>
__device__ __forceinline__ void add_stage(const Ctx& c, uint32_t (&Z)[6][4], const uint32_t (&P)[6][4]) {
#pragma unroll
  for (int ch = C0; ch < C1; ch++)
#pragma unroll
    for (int ss = 0; ss < 4; ss++) Z[ch][ss] = badd(Z[ch][ss], P[ch][ss]);
#pragma unroll
  for (int ch = C0; ch < C1; ch++) sts4(c.xaddr + BUF * XBUF_BYTES + (ch & 1) * 6144 + (ch >> 1) * 64, Z[ch]);
}

__device__ __forceinline__ uint64_t get_bd(const Ctx& c, int n) {
  return BDESC + (uint64_t)(uint32_t)(n >> 8);
}
#define G1  batch_<0, 0, 1>(r.X, r.T[0][OLD], bd);
#define G2  batch_<0, 1, 0>(r.X, r.T[0][MID], bd);
#define G3  batch_<0, 2, 0>(r.X, r.T[0][OLD], bd);
#define G4  batch_<1, 0, 1>(r.Y, r.T[1][OLD], bd);
#define G5  batch_<1, 1, 0>(r.Y, r.T[1][MID], bd);
#define G6  batch_<1, 2, 0>(r.Y, r.T[1][OLD], bd);
#define G7  if (OLD == 1) batch_<2, 0, 0>(r.X, r.T[2][OLD], bd); else { if (!skip) { F batch_<2, 0, 0>(r.X, r.T[2][OLD], bd); } else { F wg_commit(); } F }
#define G8  batch_<2, 1, 0>(r.X, r.T[2][MID], bd);
#define G9  batch_<2, 2, 0>(r.X, r.T[2][OLD], bd);
#define G10 if (OLD == 1) batch_<3, 0, 0>(r.Y, r.T[3][OLD], bd); else { if (!skip) { F batch_<3, 0, 0>(r.Y, r.T[3][OLD], bd); } else { F wg_commit(); } F }
#define G11 batch_<3, 1, 0>(r.Y, r.T[3][MID], bd);
#define G12 batch_<3, 2, 0>(r.Y, r.T[3][OLD], bd);
#define F   wg_fence();
#define W(k) wg_wait<k>();
#define PACK pack_acc<0, 6>(r.Z, r.Y);
#define PK(a, b) pack_acc<a, b>(r.Z, r.Y);
#define XW  mbar_wait(c.xfull + MID * 64, ((n - 1) >> 1) & 1); FIX3
#define LP(a, b) load_partner<MID, a, b>(c, r.P);
#define AS(a, b) add_stage<MID, a, b>(c, r.Z, r.P);
#define LV1 if (RANK == 0) ld3(r.V, c.aU, OLD * STAGE_BYTES + OFF_V); else ld3(r.U, c.aU, OLD * STAGE_BYTES);
#define LU1 if (RANK == 0) ld3(r.U, c.aU, OLD * STAGE_BYTES); else ld3(r.V, c.aU, OLD * STAGE_BYTES + OFF_V);
#define LU2 if (RANK == 0) ld3(r.U, c.aU, MID * STAGE_BYTES); else ld3(r.V, c.aU, MID * STAGE_BYTES + OFF_V);
#define LE  ld3(r.E, c.aE, OLD * STAGE_BYTES);
#define LEk(k)  ldsm4(r.E[k], (c.aE ^ (32 * k)) + OLD * STAGE_BYTES);
#define LV1k(k) if (RANK == 0) ldsm4(r.V[k], (c.aU ^ (32 * k)) + OLD * STAGE_BYTES + OFF_V); else ldsm4(r.U[k], (c.aU ^ (32 * k)) + OLD * STAGE_BYTES);
#define LV2k(k) if (RANK == 0) ldsm4(r.V[k], (c.aU ^ (32 * k)) + MID * STAGE_BYTES + OFF_V); else ldsm4(r.U[k], (c.aU ^ (32 * k)) + MID * STAGE_BYTES);
#define LU1k(k) if (RANK == 0) ldsm4(r.U[k], (c.aU ^ (32 * k)) + OLD * STAGE_BYTES); else ldsm4(r.V[k], (c.aU ^ (32 * k)) + OLD * STAGE_BYTES + OFF_V);
#define LU2k(k) if (RANK == 0) ldsm4(r.U[k], (c.aU ^ (32 * k)) + MID * STAGE_BYTES); else ldsm4(r.V[k], (c.aU ^ (32 * k)) + MID * STAGE_BYTES + OFF_V);
#define TRS tr_sum(r.T[0][OLD], r.U, r.V);
#define TRF tr_dif(r.T[1][OLD], r.U, r.V);
#define TRC if (RANK == 0) tr_t3(r.T[2][OLD], r.U, r.E); else tr_t0(r.T[2][OLD], r.V, r.E);
#define TRD if (RANK == 0) tr_t0(r.T[3][OLD], r.V, r.E); else tr_t3(r.T[3][OLD], r.U, r.E);
#define SIG if (LOCK) warp_arrive_if(c.sig + 64 * (OLD ? c.wg : 1 - c.wg), OLD ? 1 : n | c.wg);
#define FEN asm volatile("fence.proxy.async.shared::cta;" ::: "memory");
#define DONE __syncwarp(); warp_arrive_if(c.bar_full + 8 * (BAR_STAGED - BAR_FULL + MID), 1);
#define EMP warp_release(c.bar_full + 8 * (BAR_EMPTY - BAR_FULL + OLD), r.E[0][RANK], r.E[1][RANK], r.E[2][RANK], __float_as_uint(r.Y[47]), n >> 8);
#define FW  if (OLD == 1) mbar_wait(c.bar_full, ((n + 2) >> 1) & 1); \
            else mbar_wait(n ? c.bar_full + 8 : c.bar_ready, n ? ((n + 3) >> 1) & 1 : 0);
#define FIX3 if (OLD == 1 && n == 1) { mbar_wait(c.bar_full + 8, 1); SCHED_FIX3 }
#define SND(k) send_chunk<RANK, OLD, k>(c, r.X);
#define SCHED1 LV1k(0) LU1k(2) F G1 XW LP(0,1) LP(1,2) LP(2,3) LP(3,4) W(1) PK(0,1) LP(4,5) AS(0,1) PK(1,2) LP(5,6) PK(2,3) AS(1,2) AS(2,3) F G2 PK(3,4) LV1k(1) PK(4,5) LV1k(2) PK(5,6) AS(3,4) AS(4,5) W(1) TRS AS(5,6) F G4 LEk(0) F G5 W(1) TRF SIG LEk(1) F G3 G6 LEk(2)
#define SCHED1_FIRST SIG LEk(0) LEk(1) LEk(2)
#define SCHED_FIX3 LU1k(0) LU1k(1) LU1k(2) LV1k(0)
#define SCHED2 F G7 EMP F G8 W(1) TRC F G9 FW W(0) SND(0) F G10 SND(1) F G11 SND(2) SND(3) FEN DONE LU2k(0) SND(4) W(1) TRD SND(5) F G12 LU2k(1)

template <int RANK, int OLD, bool FIRST>
__device__ __forceinline__ void phase1(const Ctx& c, int n, Regs& r) {
  constexpr int MID = 1 - OLD;
  const uint64_t bd = get_bd(c, n);
  if (FIRST) {
    wg_fence();
    batch_<0, 1, 1>(r.X, r.T[0][MID], bd);
    batch_<1, 1, 1>(r.Y, r.T[1][MID], bd);
    if ((unsigned)c.h0 < (unsigned)IMG_H) {
      wg_fence();
      batch_<0, 0, 0>(r.X, r.T[0][OLD], bd);
      batch_<1, 0, 0>(r.Y, r.T[1][OLD], bd);
    }
    mbar_wait(c.bar_full + 8 * OLD, 0);
    LU1 LV1 W(1) TRS F G3 W(1) TRF F G6
    SCHED1_FIRST
  } else {
    SCHED1
  }
}

template <int RANK, int OLD>
__device__ __forceinline__ void phase2(const Ctx& c, int n, Regs& r) {
  constexpr int MID = 1 - OLD;
  const uint64_t bd = get_bd(c, n);
  wg_wait<0>();
  butterfly<RANK, 0, 48>(r.X, r.Y);
  const bool skip = (unsigned)(c.h0 + n * c.hstep) >= (unsigned)IMG_H;
  SCHED2
}

template <int RANK>
__device__ __forceinline__ void finish_strip(const Ctx& c, Regs& r, int buf) {
  if (LOCK) warp_arrive_if(c.sig + 64 * (buf ^ c.wg), 1);
  wg_wait<0>();
  pack_acc<0, 6>(r.Z, r.Y);
  const int lane = threadIdx.x & 31, g = lane >> 2;
  const int px = 8 * (c.u0 + 4 * c.warp + (g >> 1)) + (g & 1) + 2 * RANK;
  char* o = c.out + ((size_t)(c.h0 + c.nrows * c.hstep) * IMG_W + px) * (CH * 2) + (lane & 3) * 16;
  mbar_wait(c.xfull + buf * 64, ((c.nrows - 1) >> 1) & 1);
#pragma unroll
  for (int ch = 0; ch < 6; ch++) lds4(r.P[ch], c.xaddr + buf * XBUF_BYTES + (ch & 1) * 6144 + (ch >> 1) * 64);
#pragma unroll
  for (int ch = 0; ch < 6; ch++)
    asm volatile("st.global.v4.b32 [%0], {%1,%2,%3,%4};" ::"l"(o + (ch & 1) * (4 * CH * 2) + (ch >> 1) * 64), "r"(badd(r.Z[ch][0], r.P[ch][0])),
                 "r"(badd(r.Z[ch][1], r.P[ch][1])), "r"(badd(r.Z[ch][2], r.P[ch][2])), "r"(badd(r.Z[ch][3], r.P[ch][3])) : "memory");
}

__device__ __forceinline__ void transform_weights(uint32_t sbase, int rank, uint32_t items, int lane) {
  const uint32_t bar_w = sbase + OFF_BAR + 8 * BAR_W;
  const uint32_t o_w0 = (rank ? 2 : 3) * 9 * BT_BYTES, o_w2 = (rank ? 3 : 2) * 9 * BT_BYTES;
#pragma unroll 1
  for (; items; items >>= 8) {
    const int item = (items & 255) - 1;
    if (item >= 18) break;
    const uint32_t base = sbase + OFF_W + item * 1536;
    mbar_wait(bar_w + 8 * (item / 6), 0);
    uint32_t wa[3][4], wb[3][4], wd[3][4];
    const uint32_t src = base + (lane >> 2) * 192 + (lane & 3) * 16;
#pragma unroll
    for (int m = 0; m < 3; m++) lds4(wa[m], src + o_w0 + m * 64);
#pragma unroll
    for (int m = 0; m < 3; m++) lds4(wd[m], src + o_w2 + m * 64);
#pragma unroll
    for (int m = 0; m < 3; m++) lds4(wb[m], src + m * 64);
    __syncwarp();
    const uint32_t dst = base + lane * 16;
#pragma unroll
    for (int m = 0; m < 3; m++) stsm4(dst + m * 512 + o_w0, wa[m][0], wa[m][1], wa[m][2], wa[m][3]);
#pragma unroll
    for (int m = 0; m < 3; m++) stsm4(dst + m * 512 + o_w2, wd[m][0], wd[m][1], wd[m][2], wd[m][3]);
#pragma unroll
    for (int m = 0; m < 3; m++) {
      uint32_t g1[4], g2[4];
#pragma unroll
      for (int ss = 0; ss < 4; ss++) {
        const uint32_t a = wa[m][ss], b = wb[m][ss], d = wd[m][ss];
        const float slo = 0.5f * (bf_lo(a) + bf_lo(d)), shi = 0.5f * (bf_hi(a) + bf_hi(d));
        const float blo = bf_lo(b), bhi = bf_hi(b);
        g1[ss] = pack2(fmaf(blo, 0.5f, slo), fmaf(bhi, 0.5f, shi));
        g2[ss] = pack2(fmaf(blo, -0.5f, slo), fmaf(bhi, -0.5f, shi));
      }
      stsm4(dst + m * 512, g1[0], g1[1], g1[2], g1[3]);
      stsm4(dst + m * 512 + 9 * BT_BYTES, g2[0], g2[1], g2[2], g2[3]);
    }
  }
  asm volatile("fence.proxy.async.shared::cta;" ::: "memory");
  __syncwarp();
  if (elect_one()) mbar_arrive(bar_w + 24);
}

template <int RANK>
__device__ __forceinline__ void run_strip(const Ctx& c, uint32_t row0_off, uint32_t bar_row0) {
  Regs r;
#pragma unroll
  for (int m = 0; m < 2; m++) {
    const uint32_t off = m ? STAGE_BYTES : row0_off;
    mbar_wait(m ? c.bar_full + 8 : bar_row0, 0);
    if (m == 0 && (unsigned)c.h0 >= (unsigned)IMG_H) {
#pragma unroll
      for (int i = 0; i < 48; i++) asm volatile("" : "=r"(r.T[i / 12][0][(i / 4) % 3][i % 4]));
      continue;
    }
    ld3(r.U, c.aU, off);
    ld3(r.V, c.aU, off + OFF_V);
    ld3(r.E, c.aE, off);
    tr_sum(r.T[0][m], r.U, r.V);
    tr_dif(r.T[1][m], r.U, r.V);
    tr_t3(r.T[RANK == 0 ? 2 : 3][m], r.U, r.E);
    tr_t0(r.T[RANK == 0 ? 3 : 2][m], r.V, r.E);
  }
  warp_done(c.bar_full + 8 * (BAR_EMPTY - BAR_FULL + 1));
  mbar_wait(SMEM_BASE + (RANK << 24) + OFF_BAR + 8 * BAR_W + 24, 0);
#pragma unroll
  for (int i = 0; i < 48; i++) { r.X[i] = 0.f; r.Y[i] = 0.f; r.Z[i % 6][i / 12] = 0; r.P[i % 6][i / 12] = 0; }
  phase1<RANK, 0, true>(c, 0, r);
#pragma unroll 1
  for (int n = 0;; n += 2) {
    phase2<RANK, 0>(c, n, r);
    if (n + 1 == c.nrows) break;
    phase1<RANK, 1, false>(c, n + 1, r);
    phase2<RANK, 1>(c, n + 1, r);
    if (n + 2 == c.nrows) break;
    phase1<RANK, 0, false>(c, n + 2, r);
  }
  finish_strip<RANK>(c, r, (c.nrows - 1) & 1);
}

constexpr int NCL = 66;
struct Strip { int seg, h0, nrows; };
__device__ __forceinline__ bool is_down(int cl) { return cl < 2 || !((cl - 2) & 4); }
__device__ __forceinline__ Strip get_strip(int cl, int wg) {
  const int k = cl - 2, i = k >> 2;
  const int q = (i & 1) ? (wg ? 16 + 15 * i : 16 * i + 16) : (wg ? 30 + 15 * i : 16 * i - 1);
  return cl < 2 ? Strip{2 * cl + wg, -1, 16} : Strip{k & 3, 2 * q + wg, 16 - wg};
}

__device__ __forceinline__ void load_rows(const CUtensorMap* xmap, const char* x, uint32_t sbase, int rank, int wg, Strip sp, int hstep) {
  const uint32_t full = sbase + OFF_BAR + 8 * (BAR_FULL + 2 * wg), empty = full + 8 * (BAR_EMPTY - BAR_FULL);
  const uint32_t in_base = sbase + OFF_IN + wg * WG_IN_BYTES;
  const int halo = sp.seg != 3 * rank ? 6 : 0;
  const char* xseg = x + (sp.seg * 128 + (rank ? 64 : -halo)) * (CH * 2);
  const int pf_bytes = (64 + halo) * CH * 2;
#pragma unroll 1
  for (int m = 3; m <= sp.nrows + 2; m++) {
    const int s = m & 1, h = sp.h0 + m * hstep;
    mbar_wait(empty + 8 * s, ((m - 3) >> 1) & 1);
    if (m == 3) {
      asm volatile("mbarrier.arrive.shared::cluster.b64 _, [%0];" ::"r"((sbase + OFF_BAR + 8 * (BAR_READY + wg)) ^ 0x01000000u) : "memory");
      mbar_wait(full, 0);
    }
    if (m <= 4) mbar_arrive(full + 8 * s);
    if (m < sp.nrows + 2) {
      const int hp = h + PF_DIST * hstep;
      const bool pf = PF_DIST > 0 && m >= 4 + PF_START && m + PF_DIST < sp.nrows + 2 && (unsigned)hp < (unsigned)IMG_H;
      mbar_expect_tx(full + 8 * s, 2 * BOX_BYTES);
      tma_load5(in_base + s * STAGE_BYTES, xmap, full + 8 * s, rank * 48, 0, sp.seg * 16, 0, h);
      tma_load5(in_base + s * STAGE_BYTES + OFF_BOXB, xmap, full + 8 * s, rank * 48, 2, sp.seg * 16 - 1, 0, h);
      if (pf) asm volatile("cp.async.bulk.prefetch.L2.global [%0], %1;" ::"l"(xseg + (size_t)hp * (IMG_W * CH * 2)), "r"(pf_bytes) : "memory");
    } else {
      mbar_arrive(full + 8 * s);
    }
  }
}
__device__ __forceinline__ void store_rows(const CUtensorMap* omap, uint32_t sbase, int rank, int wg, Strip sp, int hstep) {
  const uint32_t full = sbase + OFF_BAR + 8 * (BAR_FULL + 2 * wg), staged = full + 8 * (BAR_STAGED - BAR_FULL);
  const uint32_t xfull = sbase + OFF_BAR + 8 * (BAR_XFULL + 4 * wg);
#pragma unroll 1
  for (int n = 0; n < sp.nrows - 1; n++) {
    const int b = n & 1;
    mbar_wait(staged + 8 * b, ((n + 1) >> 1) & 1);
    tma_store5(omap, sbase + OFF_X + (2 * wg + b) * XBUF_BYTES, 0, sp.seg * 16, 0, rank, sp.h0 + (n + 1) * hstep);
#pragma unroll
    for (int q = 0; q < 4; q++) mbar_expect_tx(xfull + 64 * b + 8 * q, X_BYTES);
    asm volatile("cp.async.bulk.wait_group.read 0;" ::: "memory");
    if (n == 0) mbar_wait(xfull + 64, 0);
    if (n + 2 < sp.nrows) asm volatile("mbarrier.arrive.shared::cluster.b64 _, [%0];" ::"r"((full + 8 * (b ^ 1)) ^ 0x01000000u) : "memory");
  }
}

__global__ void __cluster_dims__(2, 1, 1) __launch_bounds__(384, 1)
dilated_conv_wino_kernel(const __grid_constant__ CUtensorMap xmap, const __grid_constant__ CUtensorMap omap,
                         const __nv_bfloat16* __restrict__ x, const __nv_bfloat16* __restrict__ w, __nv_bfloat16* __restrict__ out) {
  extern __shared__ uint8_t smem_raw[];
  const int tid = threadIdx.x;
  const int w12 = __shfl_sync(0xffffffff, tid >> 5, 0);
  const int wg = w12 >> 2, warp = w12 & 3;
  const int lane = tid & 31;
  const int rank = blockIdx.x & 1;
  const int cl = blockIdx.x >> 1;
  const bool down = is_down(cl);
  const uint32_t sbase = SMEM_BASE + (rank << 24);
  const uint32_t b0 = sbase + OFF_BAR;
  const uint32_t bar_w = b0 + 8 * BAR_W;

  if (w12 >= 9) {
    if (elect_one()) {
      const int a = w12 - 9, i = down ? a : 2 - a;
      const char* src = reinterpret_cast<const char*>(w) + (uint32_t)((i * 6 + rank) * (3 * BT_BYTES));
      const uint32_t dst = sbase + OFF_W + a * 3 * BT_BYTES;
      mbar_init(bar_w + 8 * a, 1);
      mbar_expect_tx(bar_w + 8 * a, 9 * BT_BYTES);
      bulk_load(dst + (rank ? 2 : 3) * 9 * BT_BYTES, src, 3 * BT_BYTES, bar_w + 8 * a);
      bulk_load(dst, src + 6 * BT_BYTES, 3 * BT_BYTES, bar_w + 8 * a);
      bulk_load(dst + (rank ? 3 : 2) * 9 * BT_BYTES, src + 12 * BT_BYTES, 3 * BT_BYTES, bar_w + 8 * a);
    }
  } else if (elect_one()) {
    if (w12 < 8) {
      const uint32_t xf = b0 + 8 * (BAR_XFULL + w12);
      mbar_init(xf, 1 + LOCK);
      mbar_init(xf + 64, 1 + LOCK);
      if (w12 < 4) {
        mbar_init(b0 + 8 * (BAR_FULL + w12), 2);
        mbar_expect_tx(b0 + 8 * (BAR_FULL + w12), 2 * BOX_BYTES);
        mbar_arrive(b0 + 8 * (BAR_FULL + w12));
      } else {
        mbar_init(b0 + 8 * (BAR_EMPTY + warp), 4);
        mbar_init(b0 + 8 * (BAR_STAGED + warp), 4);
      }
      mbar_expect_tx(xf, X_BYTES);
      mbar_expect_tx(xf + 64, X_BYTES);
    } else {
      asm volatile("prefetch.tensormap [%0];" ::"l"(&xmap) : "memory");
#pragma unroll
      for (int q = 0; q < 2; q++) {
        mbar_init(b0 + 8 * (BAR_ROW0 + q), 1);
        mbar_init(b0 + 8 * (BAR_READY + q), 1);
      }
      mbar_init(bar_w + 24, 12);
#pragma unroll
      for (int q = 0; q < 2; q++) mbar_expect_tx(b0 + 8 * (BAR_ROW0 + q), 2 * BOX_BYTES);
    }
    asm volatile("fence.mbarrier_init.release.cluster;" ::: "memory");
  }
  __syncthreads();
  asm volatile("barrier.cluster.arrive.relaxed.aligned;" ::: "memory");
  const Strip s0 = get_strip(cl, 0), s1 = get_strip(cl, 1);
  const int hstep = down ? 2 : -2;
  if (w12 == 8 || w12 == 9) {
    if (elect_one()) {
#pragma unroll 1
      for (uint32_t order = cl < 2 ? RORDS : RORD; order; order >>= 4) {
        const int g = (order >> 2) & 1, m = order & 3;
        const uint32_t dst = m == 0 ? sbase + (g ? OFF_ROW0_1 : OFF_ROW0_0) : sbase + OFF_IN + g * WG_IN_BYTES + (m & 1) * STAGE_BYTES;
        const uint32_t bar = b0 + 8 * (m == 0 ? BAR_ROW0 + g : BAR_FULL + 2 * g + (m & 1));
        tma_load5(dst + warp * OFF_BOXB, &xmap, bar, rank * 48, 2 * warp, (g ? s1.seg : s0.seg) * 16 - warp, 0, (g ? s1.h0 : s0.h0) + m * hstep);
      }
      asm volatile("prefetch.tensormap [%0];" ::"l"(&omap) : "memory");
    }
    __syncwarp();
  }
  if ((uint32_t)__cvta_generic_to_shared(smem_raw) != sbase || mapa(sbase, rank ^ 1) != (sbase ^ 0x01000000u)) __trap();
  asm volatile("barrier.cluster.wait.aligned;" ::: "memory");
  transform_weights(sbase, rank, (wg == 0 ? WI0 : wg == 1 ? WI1 : WI2) + warp * 0x010101u, lane);

  if (wg == 2) {
    asm volatile("setmaxnreg.dec.sync.aligned.u32 24;");
    if (elect_one()) {
      if (warp < 2) load_rows(&xmap, reinterpret_cast<const char*>(x), sbase, rank, warp, warp ? s1 : s0, hstep);
      else store_rows(&omap, sbase, rank, warp - 2, warp == 3 ? s1 : s0, hstep);
    }
  } else {
    asm volatile("setmaxnreg.inc.sync.aligned.u32 240;");
    Ctx c;
    c.out = reinterpret_cast<char*>(out);
    c.wg = wg;
    c.warp = warp;
    c.sig = b0 + 8 * (BAR_XFULL + (w12 ^ 4));
    c.bar_full = b0 + 8 * (BAR_FULL + wg * NSTAGE);
    c.bar_ready = b0 + 8 * (BAR_READY + wg);
    c.u0 = (wg ? s1.seg : s0.seg) * 16;
    c.h0 = wg ? s1.h0 : s0.h0;
    c.hstep = hstep;
    c.nrows = wg ? s1.nrows : s0.nrows;
    c.xfull = b0 + 8 * (BAR_XFULL + w12);
    const uint32_t in_base = sbase + OFF_IN + wg * WG_IN_BYTES;
    {
      const int g = lane & 7, mi = lane >> 3;
      const int rU = 8 * warp + g + ((mi & 1) ? 34 : 0);
      const int rE = 8 * warp + g + ((mi & 1) ? 2 : 70 + 34);
      const uint32_t pU = in_base + rU * 128, pE = in_base + rE * 128;
      c.aU = pU + (((mi >> 1) ^ ((pU >> 7) & 7)) << 4);
      c.aE = pE + (((mi >> 1) ^ ((pE >> 7) & 7)) << 4);
    }
    c.xaddr = sbase + OFF_X + wg * 2 * XBUF_BYTES + (warp * 8 + (lane >> 2)) * 192 + (lane & 3) * 16;
    const uint32_t row0_off = sbase + (wg ? OFF_ROW0_1 : OFF_ROW0_0) - in_base;
    const uint32_t bar_row0 = cl < 2 ? bar_w : b0 + 8 * (BAR_ROW0 + wg);
    if (rank == 0) run_strip<0>(c, row0_off, bar_row0); else run_strip<1>(c, row0_off, bar_row0);
  }
}

typedef CUresult (*EncodeTiledFn)(CUtensorMap*, CUtensorMapDataType, cuuint32_t, void*, const cuuint64_t*, const cuuint64_t*,
                                  const cuuint32_t*, const cuuint32_t*, CUtensorMapInterleave, CUtensorMapSwizzle,
                                  CUtensorMapL2promotion, CUtensorMapFloatOOBfill);

}

extern "C" void kernel_launch(void* const* d_in, const int* in_sizes, int n_in, void* d_out, int out_size) {
  (void)in_sizes; (void)n_in; (void)out_size;
  static EncodeTiledFn encode = nullptr;
  if (!encode) {
    void* fn = nullptr;
    cudaDriverEntryPointQueryResult qr;
    cudaGetDriverEntryPoint("cuTensorMapEncodeTiled", &fn, cudaEnableDefault, &qr);
    encode = (EncodeTiledFn)fn;
    cudaFuncSetAttribute(dilated_conv_wino_kernel, cudaFuncAttributeMaxDynamicSharedMemorySize, SMEM_BYTES);
  }
  CUtensorMap xmap;
  const cuuint64_t dims[5] = {CH, 4, IMG_W / 8, 2, IMG_H};
  const cuuint64_t strides[4] = {CH * 2, 8 * CH * 2, 4 * CH * 2, IMG_W * CH * 2};
  const cuuint32_t box[5] = {48, 2, 17, 2, 1};
  const cuuint32_t estr[5] = {1, 1, 1, 1, 1};
#define PROMO CU_TENSOR_MAP_L2_PROMOTION_L2_128B
  encode(&xmap, CU_TENSOR_MAP_DATA_TYPE_BFLOAT16, 5, d_in[0], dims, strides, box, estr, CU_TENSOR_MAP_INTERLEAVE_NONE,
         CU_TENSOR_MAP_SWIZZLE_128B, PROMO, CU_TENSOR_MAP_FLOAT_OOB_FILL_NONE);
  CUtensorMap omap;
  const cuuint64_t odims[5] = {2 * CH, IMG_W / 8, 2, 2, IMG_H};
  const cuuint64_t ostrides[4] = {8 * CH * 2, 4 * CH * 2, 2 * CH * 2, IMG_W * CH * 2};
  const cuuint32_t obox[5] = {2 * CH, 16, 2, 1, 1};
  encode(&omap, CU_TENSOR_MAP_DATA_TYPE_BFLOAT16, 5, d_out, odims, ostrides, obox, estr, CU_TENSOR_MAP_INTERLEAVE_NONE,
         CU_TENSOR_MAP_SWIZZLE_NONE, CU_TENSOR_MAP_L2_PROMOTION_NONE, CU_TENSOR_MAP_FLOAT_OOB_FILL_NONE);
  dilated_conv_wino_kernel<<<2 * NCL, 384, SMEM_BYTES>>>(xmap, omap, (const __nv_bfloat16*)d_in[0], (const __nv_bfloat16*)d_in[1], (__nv_bfloat16*)d_out);
}
```

```cpp
#include <cuda_runtime.h>
#include <cuda_bf16.h>
#include <cuda.h>
#include <stdint.h>

namespace {

constexpr int IMG_H = 512, IMG_W = 512, CH = 96;
constexpr int NSTAGE = 2;

constexpr int BT_BYTES   = 3072;
constexpr int W_BYTES    = 36 * BT_BYTES;
constexpr int BOX_BYTES  = 68 * 96;
constexpr int OFF_BOXB   = 70 * 128;
constexpr int STAGE_BYTES = 144 * 128;
constexpr int OFF_V      = 72 * 128;
constexpr int WG_IN_BYTES = STAGE_BYTES + 138 * 128;
constexpr int OFF_W      = 0;
constexpr int OFF_IN     = OFF_W + W_BYTES;
constexpr int OFF_X      = OFF_IN + 2 * WG_IN_BYTES;
constexpr int X_BYTES    = 3072;
constexpr int XBUF_BYTES = 4 * X_BYTES;
constexpr int SMEM_BYTES = OFF_X + 4 * XBUF_BYTES;
constexpr int OFF_ROW0_0 = OFF_X + ((OFF_IN - OFF_X) & 1023);
constexpr int OFF_ROW0_1 = OFF_X + 2 * XBUF_BYTES + ((OFF_IN + WG_IN_BYTES - OFF_X) & 1023);
constexpr int OFF_BAR    = OFF_IN + 138 * 128;
constexpr int BAR_FULL = 0, BAR_EMPTY = 4, BAR_STAGED = 8, BAR_XFULL = 12, BAR_W = 28, BAR_ROW0 = 32, BAR_READY = 34;
static_assert(SMEM_BYTES <= 232448, "shared memory");
constexpr uint32_t SMEM_BASE = 1024;
constexpr uint64_t BDESC = (uint64_t)((SMEM_BASE + OFF_W) >> 4) | ((uint64_t)(1536 >> 4) << 16) | ((uint64_t)(128 >> 4) << 32);

__device__ __forceinline__ void wg_fence()  { asm volatile("wgmma.fence.sync.aligned;" ::: "memory"); }
__device__ __forceinline__ void wg_commit() { asm volatile("wgmma.commit_group.sync.aligned;" ::: "memory"); }
template <int N> __device__ __forceinline__ void wg_wait() { asm volatile("wgmma.wait_group.sync.aligned %0;" ::"n"(N) : "memory"); }

template <int SCALE_D>
__device__ __forceinline__ void wgmma96(float (&d)[48], const uint32_t (&a)[4], uint64_t DESC) {
  asm volatile(
      "{\n.reg .pred p;\nsetp.ne.b32 p, %53, 0;\n"
      "wgmma.mma_async.sync.aligned.m64n96k16.f32.bf16.bf16 "
      "{%0,%1,%2,%3,%4,%5,%6,%7,%8,%9,%10,%11,%12,%13,%14,%15,%16,%17,%18,%19,%20,%21,%22,%23,"
      "%24,%25,%26,%27,%28,%29,%30,%31,%32,%33,%34,%35,%36,%37,%38,%39,%40,%41,%42,%43,%44,%45,%46,%47}, "
      "{%48,%49,%50,%51}, %52, p, 1, 1, 1;\n}\n"
      : "+f"(d[0]), "+f"(d[1]), "+f"(d[2]), "+f"(d[3]), "+f"(d[4]), "+f"(d[5]), "+f"(d[6]), "+f"(d[7]),
        "+f"(d[8]), "+f"(d[9]), "+f"(d[10]), "+f"(d[11]), "+f"(d[12]), "+f"(d[13]), "+f"(d[14]), "+f"(d[15]),
        "+f"(d[16]), "+f"(d[17]), "+f"(d[18]), "+f"(d[19]), "+f"(d[20]), "+f"(d[21]), "+f"(d[22]), "+f"(d[23]),
        "+f"(d[24]), "+f"(d[25]), "+f"(d[26]), "+f"(d[27]), "+f"(d[28]), "+f"(d[29]), "+f"(d[30]), "+f"(d[31]),
        "+f"(d[32]), "+f"(d[33]), "+f"(d[34]), "+f"(d[35]), "+f"(d[36]), "+f"(d[37]), "+f"(d[38]), "+f"(d[39]),
        "+f"(d[40]), "+f"(d[41]), "+f"(d[42]), "+f"(d[43]), "+f"(d[44]), "+f"(d[45]), "+f"(d[46]), "+f"(d[47])
      : "r"(a[0]), "r"(a[1]), "r"(a[2]), "r"(a[3]), "l"(DESC), "n"(SCALE_D));
}

__device__ __forceinline__ void ldsm4(uint32_t (&r)[4], uint32_t addr) {
  asm volatile("ldmatrix.sync.aligned.m8n8.x4.shared.b16 {%0,%1,%2,%3}, [%4];"
               : "=r"(r[0]), "=r"(r[1]), "=r"(r[2]), "=r"(r[3]) : "r"(addr) : "memory");
}
__device__ __forceinline__ uint32_t badd(uint32_t a, uint32_t b) {
  uint32_t d; asm volatile("add.rn.bf16x2 %0, %1, %2;" : "=r"(d) : "r"(a), "r"(b)); return d;
}
__device__ __forceinline__ uint32_t bsub(uint32_t a, uint32_t b) {
  uint32_t d; asm volatile("sub.rn.bf16x2 %0, %1, %2;" : "=r"(d) : "r"(a), "r"(b)); return d;
}
__device__ __forceinline__ float bf_lo(uint32_t v) {
  return __uint_as_float(v << 16);
}
__device__ __forceinline__ float bf_hi(uint32_t v) { return __uint_as_float(v & 0xffff0000u); }
__device__ __forceinline__ uint32_t pack2(float lo, float hi) {
  uint32_t d; asm volatile("cvt.rn.bf16x2.f32 %0, %1, %2;" : "=r"(d) : "f"(hi), "f"(lo)); return d;
}

__device__ __forceinline__ void mbar_wait(uint32_t bar, uint32_t parity) {
  asm volatile(
      "{\n.reg .pred p;\n.reg .u32 it;\n"
      "mbarrier.try_wait.parity.shared::cta.b64 p, [%0], %1;\n"
      "@p bra WAIT_DONE;\n"
      "mov.u32 it, 0;\n"
      "WAIT_LOOP:\n"
      ".pragma \"nounroll\";\n"
      "mbarrier.try_wait.parity.shared::cta.b64 p, [%0], %1;\n"
      "@p bra WAIT_DONE;\n"
      "add.u32 it, it, 1;\n"
      "setp.lt.u32 p, it, 4194304;\n"
      "@p bra WAIT_LOOP;\n"
      "trap;\n"
      "WAIT_DONE:\n}\n" ::"r"(bar), "r"(parity) : "memory");
}
__device__ __forceinline__ void mbar_init(uint32_t bar, uint32_t count) {
  asm volatile("mbarrier.init.shared::cta.b64 [%0], %1;" ::"r"(bar), "r"(count) : "memory");
}
__device__ __forceinline__ void mbar_arrive(uint32_t bar) {
  asm volatile("mbarrier.arrive.shared::cta.b64 _, [%0];" ::"r"(bar) : "memory");
}
__device__ __forceinline__ void mbar_expect_tx(uint32_t bar, uint32_t bytes) {
  asm volatile("mbarrier.arrive.expect_tx.shared::cta.b64 _, [%0], %1;" ::"r"(bar), "r"(bytes) : "memory");
}
__device__ __forceinline__ void tma_load5(uint32_t dst, const CUtensorMap* map, uint32_t bar, int c0, int c1, int c2, int c3, int c4) {
  asm volatile("cp.async.bulk.tensor.5d.shared::cluster.global.mbarrier::complete_tx::bytes [%0], [%1, {%3,%4,%5,%6,%7}], [%2];"
               ::"r"(dst), "l"(map), "r"(bar), "r"(c0), "r"(c1), "r"(c2), "r"(c3), "r"(c4) : "memory");
}
__device__ __forceinline__ void bulk_load(uint32_t dst, const void* src, uint32_t bytes, uint32_t bar) {
  asm volatile("cp.async.bulk.shared::cluster.global.mbarrier::complete_tx::bytes [%0], [%1], %2, [%3];"
               ::"r"(dst), "l"(src), "r"(bytes), "r"(bar) : "memory");
}
template <int OFF>
__device__ __forceinline__ void st_async4(uint32_t cluster_addr, uint32_t cluster_bar, uint32_t a, uint32_t b, uint32_t c, uint32_t d) {
  asm volatile("st.async.shared::cluster.mbarrier::complete_tx::bytes.v4.b32 [%0+%6], {%2,%3,%4,%5}, [%1];"
               ::"r"(cluster_addr), "r"(cluster_bar), "r"(a), "r"(b), "r"(c), "r"(d), "n"(OFF) : "memory");
}
__device__ __forceinline__ void stsm4(uint32_t addr, uint32_t a, uint32_t b, uint32_t c, uint32_t d) {
  asm volatile("stmatrix.sync.aligned.m8n8.x4.shared.b16 [%0], {%1,%2,%3,%4};" ::"r"(addr), "r"(a), "r"(b), "r"(c), "r"(d) : "memory");
}
__device__ __forceinline__ void lds4(uint32_t (&r)[4], uint32_t addr) {
  asm volatile("ld.shared.v4.b32 {%0,%1,%2,%3}, [%4];" : "=r"(r[0]), "=r"(r[1]), "=r"(r[2]), "=r"(r[3]) : "r"(addr) : "memory");
}
__device__ __forceinline__ void sts4(uint32_t addr, const uint32_t (&r)[4]) {
  asm volatile("st.shared.v4.b32 [%0], {%1,%2,%3,%4};" ::"r"(addr), "r"(r[0]), "r"(r[1]), "r"(r[2]), "r"(r[3]) : "memory");
}
__device__ __forceinline__ void tma_store5(const CUtensorMap* map, uint32_t src, int c0, int c1, int c2, int c3, int c4) {
  asm volatile("cp.async.bulk.tensor.5d.global.shared::cta.bulk_group [%0, {%2,%3,%4,%5,%6}], [%1];"
               ::"l"(map), "r"(src), "r"(c0), "r"(c1), "r"(c2), "r"(c3), "r"(c4) : "memory");
  asm volatile("cp.async.bulk.commit_group;" ::: "memory");
}
__device__ __forceinline__ bool elect_one() {
  uint32_t p;
  asm volatile("{\n.reg .pred P;\nelect.sync _|P, 0xffffffff;\nselp.u32 %0, 1, 0, P;\n}\n" : "=r"(p));
  return p;
}
__device__ __forceinline__ uint32_t mapa(uint32_t addr, uint32_t rank) {
  uint32_t r; asm("mapa.shared::cluster.u32 %0, %1, %2;" : "=r"(r) : "r"(addr), "r"(rank)); return r;
}

__device__ __forceinline__ void tr_sum(uint32_t (&t)[3][4], const uint32_t (&U)[3][4], const uint32_t (&V)[3][4]) {
#pragma unroll
  for (int k = 0; k < 3; k++)
#pragma unroll
    for (int i = 0; i < 4; i++) t[k][i] = badd(U[k][i], V[k][i]);
}
__device__ __forceinline__ void tr_dif(uint32_t (&t)[3][4], const uint32_t (&U)[3][4], const uint32_t (&V)[3][4]) {
#pragma unroll
  for (int k = 0; k < 3; k++)
#pragma unroll
    for (int i = 0; i < 4; i++) t[k][i] = bsub(V[k][i], U[k][i]);
}
__device__ __forceinline__ void tr_t0(uint32_t (&t)[3][4], const uint32_t (&V)[3][4], const uint32_t (&E)[3][4]) {
#pragma unroll
  for (int k = 0; k < 3; k++) {
    t[k][0] = bsub(E[k][0], V[k][0]); t[k][1] = bsub(V[k][0], V[k][1]);
    t[k][2] = bsub(E[k][2], V[k][2]); t[k][3] = bsub(V[k][2], V[k][3]);
  }
}
__device__ __forceinline__ void tr_t3(uint32_t (&t)[3][4], const uint32_t (&U)[3][4], const uint32_t (&E)[3][4]) {
#pragma unroll
  for (int k = 0; k < 3; k++) {
    t[k][0] = bsub(U[k][1], U[k][0]); t[k][1] = bsub(E[k][1], U[k][1]);
    t[k][2] = bsub(U[k][3], U[k][2]); t[k][3] = bsub(E[k][3], U[k][3]);
  }
}
__device__ __forceinline__ void ld3(uint32_t (&R)[3][4], uint32_t aU, int off) {
#pragma unroll
  for (int k = 0; k < 3; k++) ldsm4(R[k], (aU ^ (32 * k)) + off);
}
template <int COMP, int AGE, int FIRST>
__device__ __forceinline__ void batch_(float (&acc)[48], const uint32_t (&t)[3][4], uint64_t bd) {
  constexpr int base = ((COMP * 3 + AGE) * 3) * BT_BYTES;
  wgmma96<FIRST ? 0 : 1>(acc, t[0], bd + ((base) >> 4));
  wgmma96<1>(acc, t[1], bd + ((base + BT_BYTES) >> 4));
  wgmma96<1>(acc, t[2], bd + ((base + 2 * BT_BYTES) >> 4));
  wg_commit();
}

template <int RANK, int I0, int I1>
__device__ __forceinline__ void butterfly(float (&X)[48], float (&Y)[48]) {
#pragma unroll
  for (int i = I0; i < I1; i++) {
    if (RANK == 0) asm volatile("sub.rn.f32 %0, %0, %1;\nfma.rn.f32 %1, %1, 0f40000000, %0;" : "+f"(X[i]), "+f"(Y[i]));
    else           asm volatile("add.rn.f32 %0, %0, %1;\nfma.rn.f32 %1, %1, 0fC0000000, %0;" : "+f"(X[i]), "+f"(Y[i]));
  }
}

struct Ctx {
  uint32_t aU, aE;
  uint32_t bar_full;
  uint32_t bar_ready;
  uint32_t xaddr, xfull;
  char* out;
  int wg, warp;
  uint32_t sig;
  int u0, h0, hstep;
  int nrows;
};

template <int BUF, int C0, int C1>
__device__ __forceinline__ void load_partner(const Ctx& c, uint32_t (&P)[6][4]) {
#pragma unroll
  for (int ch = C0; ch < C1; ch++) lds4(P[ch], c.xaddr + BUF * XBUF_BYTES + (ch & 1) * 6144 + (ch >> 1) * 64);
}
template <int RANK, int BUF, int CH0>
__device__ __forceinline__ void send_chunk(const Ctx& c, const float (&X)[48]) {
  constexpr uint32_t RDELTA = RANK ? 0xFF000000u : 0x01000000u;
  constexpr int m = CH0 >> 1, s = CH0 & 1;
  uint32_t o[4];
#pragma unroll
  for (int ss = 0; ss < 4; ss++) o[ss] = pack2(X[16 * m + 4 * ss + 2 * s], X[16 * m + 4 * ss + 2 * s + 1]);
  st_async4<BUF * XBUF_BYTES + s * 6144 + m * 64>(c.xaddr + RDELTA, c.xfull + BUF * 64 + RDELTA, o[0], o[1], o[2], o[3]);
}

#define PF_START 1
#define WI0 0x404001u
#define WI1 0x110d05u
#define WI2 0x404009u
#define LOCK 1
#define R3G 0
#define PF_START1 PF_START
#define INC 1
#define PF_DIST 1
#define RORD 0x642501
#define RORDS 0x6521

struct Regs {
  float X[48], Y[48];
  uint32_t T[4][2][3][4];
  uint32_t U[3][4], V[3][4], E[3][4];
  uint32_t Z[6][4], P[6][4];
};

__device__ __forceinline__ void warp_done(uint32_t bar) {
  asm volatile("fence.proxy.async.shared::cta;" ::: "memory");
  __syncwarp();
  asm volatile("{\n.reg .pred q;\nelect.sync _|q, 0xffffffff;\n@q mbarrier.arrive.shared::cta.b64 _, [%0];\n}\n" ::"r"(bar) : "memory");
}
__device__ __forceinline__ void warp_release(uint32_t bar, uint32_t a, uint32_t b, uint32_t c, uint32_t d, uint32_t zero) {
  asm volatile("{\n.reg .pred q;\n.reg .b32 t;\nlop3.b32 t, %1, %4, %5, 0x80;\nlop3.b32 t, t, %2, %3, 0x80;\nor.b32 t, t, 1;\n"
               "elect.sync _|q, 0xffffffff;\n@q mbarrier.arrive.shared::cta.b64 _, [%0], t;\n}\n"
               ::"r"(bar), "r"(a), "r"(b), "r"(c), "r"(d), "r"(zero) : "memory");
}
__device__ __forceinline__ void warp_arrive_if(uint32_t bar, int on) {
  asm volatile("{\n.reg .pred p, q;\nelect.sync _|q, 0xffffffff;\nsetp.ne.and.s32 p, %1, 0, q;\n@p mbarrier.arrive.shared::cta.b64 _, [%0];\n}\n"
               ::"r"(bar), "r"(on) : "memory");
}
template <int C0, int C1>
__device__ __forceinline__ void pack_acc(uint32_t (&Z)[6][4], const float (&Y)[48]) {
#pragma unroll
  for (int ch = C0; ch < C1; ch++)
#pragma unroll
    for (int ss = 0; ss < 4; ss++) {
      const int i = 16 * (ch >> 1) + 4 * ss + 2 * (ch & 1);
      Z[ch][ss] = pack2(Y[i], Y[i + 1]);
    }
}
template <int BUF, int C0, int C1>
__device__ __forceinline__ void add_stage(const Ctx& c, uint32_t (&Z)[6][4], const uint32_t (&P)[6][4]) {
#pragma unroll
  for (int ch = C0; ch < C1; ch++)
#pragma unroll
    for (int ss = 0; ss < 4; ss++) Z[ch][ss] = badd(Z[ch][ss], P[ch][ss]);
#pragma unroll
  for (int ch = C0; ch < C1; ch++) sts4(c.xaddr + BUF * XBUF_BYTES + (ch & 1) * 6144 + (ch >> 1) * 64, Z[ch]);
}

__device__ __forceinline__ uint64_t get_bd(const Ctx& c, int n) {
  return BDESC + (uint64_t)(uint32_t)(n >> 8);
}
#define G1  batch_<0, 0, 1>(r.X, r.T[0][OLD], bd);
#define G2  batch_<0, 1, 0>(r.X, r.T[0][MID], bd);
#define G3  batch_<0, 2, 0>(r.X, r.T[0][OLD], bd);
#define G4  batch_<1, 0, 1>(r.Y, r.T[1][OLD], bd);
#define G5  batch_<1, 1, 0>(r.Y, r.T[1][MID], bd);
#define G6  batch_<1, 2, 0>(r.Y, r.T[1][OLD], bd);
#define G7  if (OLD == 1) batch_<2, 0, 0>(r.X, r.T[2][OLD], bd); else { if (!skip) { F batch_<2, 0, 0>(r.X, r.T[2][OLD], bd); } else { F wg_commit(); } F }
#define G8  batch_<2, 1, 0>(r.X, r.T[2][MID], bd);
#define G9  batch_<2, 2, 0>(r.X, r.T[2][OLD], bd);
#define G10 if (OLD == 1) batch_<3, 0, 0>(r.Y, r.T[3][OLD], bd); else { if (!skip) { F batch_<3, 0, 0>(r.Y, r.T[3][OLD], bd); } else { F wg_commit(); } F }
#define G11 batch_<3, 1, 0>(r.Y, r.T[3][MID], bd);
#define G12 batch_<3, 2, 0>(r.Y, r.T[3][OLD], bd);
#define F   wg_fence();
#define W(k) wg_wait<k>();
#define PACK pack_acc<0, 6>(r.Z, r.Y);
#define PK(a, b) pack_acc<a, b>(r.Z, r.Y);
#define XW  mbar_wait(c.xfull + MID * 64, ((n - 1) >> 1) & 1); FIX3
#define LP(a, b) load_partner<MID, a, b>(c, r.P);
#define AS(a, b) add_stage<MID, a, b>(c, r.Z, r.P);
#define LV1 if (RANK == 0) ld3(r.V, c.aU, OLD * STAGE_BYTES + OFF_V); else ld3(r.U, c.aU, OLD * STAGE_BYTES);
#define LU1 if (RANK == 0) ld3(r.U, c.aU, OLD * STAGE_BYTES); else ld3(r.V, c.aU, OLD * STAGE_BYTES + OFF_V);
#define LU2 if (RANK == 0) ld3(r.U, c.aU, MID * STAGE_BYTES); else ld3(r.V, c.aU, MID * STAGE_BYTES + OFF_V);
#define LE  ld3(r.E, c.aE, OLD * STAGE_BYTES);
#define LEk(k)  ldsm4(r.E[k], (c.aE ^ (32 * k)) + OLD * STAGE_BYTES);
#define LV1k(k) if (RANK == 0) ldsm4(r.V[k], (c.aU ^ (32 * k)) + OLD * STAGE_BYTES + OFF_V); else ldsm4(r.U[k], (c.aU ^ (32 * k)) + OLD * STAGE_BYTES);
#define LV2k(k) if (RANK == 0) ldsm4(r.V[k], (c.aU ^ (32 * k)) + MID * STAGE_BYTES + OFF_V); else ldsm4(r.U[k], (c.aU ^ (32 * k)) + MID * STAGE_BYTES);
#define LU1k(k) if (RANK == 0) ldsm4(r.U[k], (c.aU ^ (32 * k)) + OLD * STAGE_BYTES); else ldsm4(r.V[k], (c.aU ^ (32 * k)) + OLD * STAGE_BYTES + OFF_V);
#define LU2k(k) if (RANK == 0) ldsm4(r.U[k], (c.aU ^ (32 * k)) + MID * STAGE_BYTES); else ldsm4(r.V[k], (c.aU ^ (32 * k)) + MID * STAGE_BYTES + OFF_V);
#define TRS tr_sum(r.T[0][OLD], r.U, r.V);
#define TRF tr_dif(r.T[1][OLD], r.U, r.V);
#define TRC if (RANK == 0) tr_t3(r.T[2][OLD], r.U, r.E); else tr_t0(r.T[2][OLD], r.V, r.E);
#define TRD if (RANK == 0) tr_t0(r.T[3][OLD], r.V, r.E); else tr_t3(r.T[3][OLD], r.U, r.E);
#define SIG if (LOCK) warp_arrive_if(c.sig + 64 * (OLD ? c.wg : 1 - c.wg), OLD ? 1 : n | c.wg);
#define FEN asm volatile("fence.proxy.async.shared::cta;" ::: "memory");
#define DONE __syncwarp(); warp_arrive_if(c.bar_full + 8 * (BAR_STAGED - BAR_FULL + MID), 1);
#define EMP warp_release(c.bar_full + 8 * (BAR_EMPTY - BAR_FULL + OLD), r.E[0][RANK], r.E[1][RANK], r.E[2][RANK], __float_as_uint(r.Y[47]), n >> 8);
#define FW  if (OLD == 1) mbar_wait(c.bar_full, ((n + 2) >> 1) & 1); \
            else mbar_wait(n ? c.bar_full + 8 : c.bar_ready, n ? ((n + 3) >> 1) & 1 : 0);
#define FIX3 if (OLD == 1 && n == 1) { mbar_wait(c.bar_full + 8, 1); SCHED_FIX3 }
#define SND(k) send_chunk<RANK, OLD, k>(c, r.X);
#define SCHED1 LV1k(0) LU1k(2) F G1 XW LP(0,1) LP(1,2) LP(2,3) LP(3,4) W(1) PK(0,1) LP(4,5) AS(0,1) PK(1,2) LP(5,6) PK(2,3) AS(1,2) AS(2,3) F G2 PK(3,4) LV1k(1) PK(4,5) LV1k(2) PK(5,6) AS(3,4) AS(4,5) W(1) TRS AS(5,6) F G4 LEk(0) F G5 W(1) TRF SIG LEk(1) F G3 G6 LEk(2)
#define SCHED1_FIRST SIG LEk(0) LEk(1) LEk(2)
#define SCHED_FIX3 LU1k(0) LU1k(1) LU1k(2) LV1k(0)
#define SCHED2 F G7 EMP F G8 W(1) TRC F G9 FW W(0) SND(0) F G10 SND(1) F G11 SND(2) SND(3) FEN DONE LU2k(0) SND(4) W(1) TRD SND(5) F G12 LU2k(1)

template <int RANK, int OLD, bool FIRST>
__device__ __forceinline__ void phase1(const Ctx& c, int n, Regs& r) {
  constexpr int MID = 1 - OLD;
  const uint64_t bd = get_bd(c, n);
  if (FIRST) {
    mbar_wait(c.bar_full + 8 * OLD, 0);
    LU1 LV1 W(1) TRS F G3 W(1) TRF F G6
    SCHED1_FIRST
  } else {
    SCHED1
  }
}

template <int RANK, int OLD>
__device__ __forceinline__ void phase2(const Ctx& c, int n, Regs& r) {
  constexpr int MID = 1 - OLD;
  const uint64_t bd = get_bd(c, n);
  wg_wait<0>();
  butterfly<RANK, 0, 48>(r.X, r.Y);
  const bool skip = (unsigned)(c.h0 + n * c.hstep) >= (unsigned)IMG_H;
  SCHED2
}

template <int RANK>
__device__ __forceinline__ void finish_strip(const Ctx& c, Regs& r, int buf) {
  if (LOCK) warp_arrive_if(c.sig + 64 * (buf ^ c.wg), 1);
  wg_wait<0>();
  pack_acc<0, 6>(r.Z, r.Y);
  const int lane = threadIdx.x & 31, g = lane >> 2;
  const int px = 8 * (c.u0 + 4 * c.warp + (g >> 1)) + (g & 1) + 2 * RANK;
  char* o = c.out + ((size_t)(c.h0 + c.nrows * c.hstep) * IMG_W + px) * (CH * 2) + (lane & 3) * 16;
  mbar_wait(c.xfull + buf * 64, ((c.nrows - 1) >> 1) & 1);
#pragma unroll
  for (int ch = 0; ch < 6; ch++) lds4(r.P[ch], c.xaddr + buf * XBUF_BYTES + (ch & 1) * 6144 + (ch >> 1) * 64);
#pragma unroll
  for (int ch = 0; ch < 6; ch++)
    asm volatile("st.global.v4.b32 [%0], {%1,%2,%3,%4};" ::"l"(o + (ch & 1) * (4 * CH * 2) + (ch >> 1) * 64), "r"(badd(r.Z[ch][0], r.P[ch][0])),
                 "r"(badd(r.Z[ch][1], r.P[ch][1])), "r"(badd(r.Z[ch][2], r.P[ch][2])), "r"(badd(r.Z[ch][3], r.P[ch][3])) : "memory");
}

__device__ __forceinline__ void transform_weights(uint32_t sbase, int rank, uint32_t items, int lane) {
  const uint32_t bar_w = sbase + OFF_BAR + 8 * BAR_W;
  const uint32_t o_w0 = (rank ? 2 : 3) * 9 * BT_BYTES, o_w2 = (rank ? 3 : 2) * 9 * BT_BYTES;
#pragma unroll 1
  for (; items; items >>= 8) {
    const int item = (items & 255) - 1;
    if (item >= 18) break;
    const uint32_t base = sbase + OFF_W + item * 1536;
    mbar_wait(bar_w + 8 * (item / 6), 0);
    uint32_t wa[3][4], wb[3][4], wd[3][4];
    const uint32_t src = base + (lane >> 2) * 192 + (lane & 3) * 16;
#pragma unroll
    for (int m = 0; m < 3; m++) lds4(wa[m], src + o_w0 + m * 64);
#pragma unroll
    for (int m = 0; m < 3; m++) lds4(wd[m], src + o_w2 + m * 64);
#pragma unroll
    for (int m = 0; m < 3; m++) lds4(wb[m], src + m * 64);
    __syncwarp();
    const uint32_t dst = base + lane * 16;
#pragma unroll
    for (int m = 0; m < 3; m++) stsm4(dst + m * 512 + o_w0, wa[m][0], wa[m][1], wa[m][2], wa[m][3]);
#pragma unroll
    for (int m = 0; m < 3; m++) stsm4(dst + m * 512 + o_w2, wd[m][0], wd[m][1], wd[m][2], wd[m][3]);
#pragma unroll
    for (int m = 0; m < 3; m++) {
      uint32_t g1[4], g2[4];
#pragma unroll
      for (int ss = 0; ss < 4; ss++) {
        const uint32_t a = wa[m][ss], b = wb[m][ss], d = wd[m][ss];
        const float slo = 0.5f * (bf_lo(a) + bf_lo(d)), shi = 0.5f * (bf_hi(a) + bf_hi(d));
        const float blo = bf_lo(b), bhi = bf_hi(b);
        g1[ss] = pack2(fmaf(blo, 0.5f, slo), fmaf(bhi, 0.5f, shi));
        g2[ss] = pack2(fmaf(blo, -0.5f, slo), fmaf(bhi, -0.5f, shi));
      }
      stsm4(dst + m * 512, g1[0], g1[1], g1[2], g1[3]);
      stsm4(dst + m * 512 + 9 * BT_BYTES, g2[0], g2[1], g2[2], g2[3]);
    }
  }
  asm volatile("fence.proxy.async.shared::cta;" ::: "memory");
  __syncwarp();
  if (elect_one()) mbar_arrive(bar_w + 24);
}

template <int RANK>
__device__ __forceinline__ void run_strip(const Ctx& c, uint32_t row0_off, uint32_t bar_row0) {
  Regs r;
#pragma unroll
  for (int i = 0; i < 48; i++) { r.X[i] = 0.f; r.Y[i] = 0.f; r.Z[i % 6][i / 12] = 0; r.P[i % 6][i / 12] = 0; }
#pragma unroll
  for (int m = 1; m >= 0; m--) {
    const uint32_t off = m ? STAGE_BYTES : row0_off;
    mbar_wait(m ? c.bar_full + 8 : bar_row0, 0);
    if (m == 0 && (unsigned)c.h0 >= (unsigned)IMG_H) {
#pragma unroll
      for (int i = 0; i < 48; i++) asm volatile("" : "=r"(r.T[i / 12][0][(i / 4) % 3][i % 4]));
      continue;
    }
    ld3(r.U, c.aU, off);
    ld3(r.V, c.aU, off + OFF_V);
    ld3(r.E, c.aE, off);
    tr_sum(r.T[0][m], r.U, r.V);
    tr_dif(r.T[1][m], r.U, r.V);
    if (m && INC == 2) { tr_t3(r.T[RANK == 0 ? 2 : 3][m], r.U, r.E); tr_t0(r.T[RANK == 0 ? 3 : 2][m], r.V, r.E); }
    if (m) mbar_wait(SMEM_BASE + (RANK << 24) + OFF_BAR + 8 * BAR_W + 24, 0);
    wg_fence();
    if (m) { batch_<0, 1, 1>(r.X, r.T[0][1], BDESC); batch_<1, 1, 1>(r.Y, r.T[1][1], BDESC); }
    else   { batch_<0, 0, 0>(r.X, r.T[0][0], BDESC); batch_<1, 0, 0>(r.Y, r.T[1][0], BDESC); }
    if (!(m && INC == 2)) { tr_t3(r.T[RANK == 0 ? 2 : 3][m], r.U, r.E); tr_t0(r.T[RANK == 0 ? 3 : 2][m], r.V, r.E); }
  }
  warp_done(c.bar_full + 8 * (BAR_EMPTY - BAR_FULL + 1));
  phase1<RANK, 0, true>(c, 0, r);
#pragma unroll 1
  for (int n = 0;; n += 2) {
    phase2<RANK, 0>(c, n, r);
    if (n + 1 == c.nrows) break;
    phase1<RANK, 1, false>(c, n + 1, r);
    phase2<RANK, 1>(c, n + 1, r);
    if (n + 2 == c.nrows) break;
    phase1<RANK, 0, false>(c, n + 2, r);
  }
  finish_strip<RANK>(c, r, (c.nrows - 1) & 1);
}

constexpr int NCL = 66;
struct Strip { int seg, h0, nrows; };
__device__ __forceinline__ bool is_down(int cl) { return cl < 2 || !((cl - 2) & 4); }
__device__ __forceinline__ Strip get_strip(int cl, int wg) {
  const int k = cl - 2, i = k >> 2;
  const int q = (i & 1) ? (wg ? 16 + 15 * i : 16 * i + 16) : (wg ? 30 + 15 * i : 16 * i - 1);
  return cl < 2 ? Strip{2 * cl + wg, -1, 16} : Strip{k & 3, 2 * q + wg, 16 - wg};
}

__device__ __forceinline__ void load_rows(const CUtensorMap* xmap, const char* x, uint32_t sbase, int rank, int wg, Strip sp, int hstep) {
  const uint32_t full = sbase + OFF_BAR + 8 * (BAR_FULL + 2 * wg), empty = full + 8 * (BAR_EMPTY - BAR_FULL);
  const uint32_t in_base = sbase + OFF_IN + wg * WG_IN_BYTES;
  const int halo = sp.seg != 3 * rank ? 6 : 0;
  const char* xseg = x + (sp.seg * 128 + (rank ? 64 : -halo)) * (CH * 2);
  const int pf_bytes = (64 + halo) * CH * 2;
#pragma unroll 1
  for (int m = 3; m <= sp.nrows + 2; m++) {
    const int s = m & 1, h = sp.h0 + m * hstep;
    mbar_wait(empty + 8 * s, ((m - 3) >> 1) & 1);
    if (m == 3) {
      asm volatile("mbarrier.arrive.shared::cluster.b64 _, [%0];" ::"r"((sbase + OFF_BAR + 8 * (BAR_READY + wg)) ^ 0x01000000u) : "memory");
      if (R3G & (1 << wg)) mbar_wait(full, 0);
    }
    if (m <= 4) mbar_arrive(full + 8 * s);
    if (m < sp.nrows + 2) {
      const int hp = h + PF_DIST * hstep;
      const bool pf = PF_DIST > 0 && m >= 4 + (wg ? PF_START1 : PF_START) && m + PF_DIST < sp.nrows + 2 && (unsigned)hp < (unsigned)IMG_H;
      mbar_expect_tx(full + 8 * s, 2 * BOX_BYTES);
      tma_load5(in_base + s * STAGE_BYTES, xmap, full + 8 * s, rank * 48, 0, sp.seg * 16, 0, h);
      tma_load5(in_base + s * STAGE_BYTES + OFF_BOXB, xmap, full + 8 * s, rank * 48, 2, sp.seg * 16 - 1, 0, h);
      if (pf) asm volatile("cp.async.bulk.prefetch.L2.global [%0], %1;" ::"l"(xseg + (size_t)hp * (IMG_W * CH * 2)), "r"(pf_bytes) : "memory");
    } else {
      mbar_arrive(full + 8 * s);
    }
  }
}
__device__ __forceinline__ void store_rows(const CUtensorMap* omap, uint32_t sbase, int rank, int wg, Strip sp, int hstep) {
  const uint32_t full = sbase + OFF_BAR + 8 * (BAR_FULL + 2 * wg), staged = full + 8 * (BAR_STAGED - BAR_FULL);
  const uint32_t xfull = sbase + OFF_BAR + 8 * (BAR_XFULL + 4 * wg);
#pragma unroll 1
  for (int n = 0; n < sp.nrows - 1; n++) {
    const int b = n & 1;
    mbar_wait(staged + 8 * b, ((n + 1) >> 1) & 1);
    tma_store5(omap, sbase + OFF_X + (2 * wg + b) * XBUF_BYTES, 0, sp.seg * 16, 0, rank, sp.h0 + (n + 1) * hstep);
#pragma unroll
    for (int q = 0; q < 4; q++) mbar_expect_tx(xfull + 64 * b + 8 * q, X_BYTES);
    asm volatile("cp.async.bulk.wait_group.read 0;" ::: "memory");
    if (n == 0) mbar_wait(xfull + 64, 0);
    if (n + 2 < sp.nrows) asm volatile("mbarrier.arrive.shared::cluster.b64 _, [%0];" ::"r"((full + 8 * (b ^ 1)) ^ 0x01000000u) : "memory");
  }
}

__global__ void __cluster_dims__(2, 1, 1) __launch_bounds__(384, 1)
dilated_conv_wino_kernel(const __grid_constant__ CUtensorMap xmap, const __grid_constant__ CUtensorMap omap,
                         const __nv_bfloat16* __restrict__ x, const __nv_bfloat16* __restrict__ w, __nv_bfloat16* __restrict__ out) {
  extern __shared__ uint8_t smem_raw[];
  const int tid = threadIdx.x;
  const int w12 = __shfl_sync(0xffffffff, tid >> 5, 0);
  const int wg = w12 >> 2, warp = w12 & 3;
  const int lane = tid & 31;
  const int rank = blockIdx.x & 1;
  const int cl = blockIdx.x >> 1;
  const bool down = is_down(cl);
  const uint32_t sbase = SMEM_BASE + (rank << 24);
  const uint32_t b0 = sbase + OFF_BAR;
  const uint32_t bar_w = b0 + 8 * BAR_W;

  if (w12 >= 9) {
    if (elect_one()) {
      const int a = w12 - 9, i = down ? a : 2 - a;
      const char* src = reinterpret_cast<const char*>(w) + (uint32_t)((i * 6 + rank) * (3 * BT_BYTES));
      const uint32_t dst = sbase + OFF_W + a * 3 * BT_BYTES;
      mbar_init(bar_w + 8 * a, 1);
      mbar_expect_tx(bar_w + 8 * a, 9 * BT_BYTES);
      bulk_load(dst + (rank ? 2 : 3) * 9 * BT_BYTES, src, 3 * BT_BYTES, bar_w + 8 * a);
      bulk_load(dst, src + 6 * BT_BYTES, 3 * BT_BYTES, bar_w + 8 * a);
      bulk_load(dst + (rank ? 3 : 2) * 9 * BT_BYTES, src + 12 * BT_BYTES, 3 * BT_BYTES, bar_w + 8 * a);
    }
  } else if (elect_one()) {
    if (w12 < 8) {
      const uint32_t xf = b0 + 8 * (BAR_XFULL + w12);
      mbar_init(xf, 1 + LOCK);
      mbar_init(xf + 64, 1 + LOCK);
      if (w12 < 4) {
        mbar_init(b0 + 8 * (BAR_FULL + w12), 2);
        mbar_expect_tx(b0 + 8 * (BAR_FULL + w12), 2 * BOX_BYTES);
        mbar_arrive(b0 + 8 * (BAR_FULL + w12));
      } else {
        mbar_init(b0 + 8 * (BAR_EMPTY + warp), 4);
        mbar_init(b0 + 8 * (BAR_STAGED + warp), 4);
      }
      mbar_expect_tx(xf, X_BYTES);
      mbar_expect_tx(xf + 64, X_BYTES);
    } else {
      asm volatile("prefetch.tensormap [%0];" ::"l"(&xmap) : "memory");
#pragma unroll
      for (int q = 0; q < 2; q++) {
        mbar_init(b0 + 8 * (BAR_ROW0 + q), 1);
        mbar_init(b0 + 8 * (BAR_READY + q), 1);
      }
      mbar_init(bar_w + 24, 12);
#pragma unroll
      for (int q = 0; q < 2; q++) mbar_expect_tx(b0 + 8 * (BAR_ROW0 + q), 2 * BOX_BYTES);
    }
    asm volatile("fence.mbarrier_init.release.cluster;" ::: "memory");
  }
  __syncthreads();
  asm volatile("barrier.cluster.arrive.relaxed.aligned;" ::: "memory");
  const Strip s0 = get_strip(cl, 0), s1 = get_strip(cl, 1);
  const int hstep = down ? 2 : -2;
  if (w12 == 8 || w12 == 9) {
    if (elect_one()) {
#pragma unroll 1
      for (uint32_t order = cl < 2 ? RORDS : RORD; order; order >>= 4) {
        const int g = (order >> 2) & 1, m = order & 3;
        const uint32_t dst = m == 0 ? sbase + (g ? OFF_ROW0_1 : OFF_ROW0_0) : sbase + OFF_IN + g * WG_IN_BYTES + (m & 1) * STAGE_BYTES;
        const uint32_t bar = b0 + 8 * (m == 0 ? BAR_ROW0 + g : BAR_FULL + 2 * g + (m & 1));
        tma_load5(dst + warp * OFF_BOXB, &xmap, bar, rank * 48, 2 * warp, (g ? s1.seg : s0.seg) * 16 - warp, 0, (g ? s1.h0 : s0.h0) + m * hstep);
      }
      asm volatile("prefetch.tensormap [%0];" ::"l"(&omap) : "memory");
    }
    __syncwarp();
  }
  if ((uint32_t)__cvta_generic_to_shared(smem_raw) != sbase || mapa(sbase, rank ^ 1) != (sbase ^ 0x01000000u)) __trap();
  asm volatile("barrier.cluster.wait.aligned;" ::: "memory");
  transform_weights(sbase, rank, (wg == 0 ? WI0 : wg == 1 ? WI1 : WI2) + warp * 0x010101u, lane);

  if (wg == 2) {
    asm volatile("setmaxnreg.dec.sync.aligned.u32 24;");
    if (elect_one()) {
      if (warp < 2) load_rows(&xmap, reinterpret_cast<const char*>(x), sbase, rank, warp, warp ? s1 : s0, hstep);
      else store_rows(&omap, sbase, rank, warp - 2, warp == 3 ? s1 : s0, hstep);
    }
  } else {
    asm volatile("setmaxnreg.inc.sync.aligned.u32 240;");
    Ctx c;
    c.out = reinterpret_cast<char*>(out);
    c.wg = wg;
    c.warp = warp;
    c.sig = b0 + 8 * (BAR_XFULL + (w12 ^ 4));
    c.bar_full = b0 + 8 * (BAR_FULL + wg * NSTAGE);
    c.bar_ready = b0 + 8 * (BAR_READY + wg);
    c.u0 = (wg ? s1.seg : s0.seg) * 16;
    c.h0 = wg ? s1.h0 : s0.h0;
    c.hstep = hstep;
    c.nrows = wg ? s1.nrows : s0.nrows;
    c.xfull = b0 + 8 * (BAR_XFULL + w12);
    const uint32_t in_base = sbase + OFF_IN + wg * WG_IN_BYTES;
    {
      const int g = lane & 7, mi = lane >> 3;
      const int rU = 8 * warp + g + ((mi & 1) ? 34 : 0);
      const int rE = 8 * warp + g + ((mi & 1) ? 2 : 70 + 34);
      const uint32_t pU = in_base + rU * 128, pE = in_base + rE * 128;
      c.aU = pU + (((mi >> 1) ^ ((pU >> 7) & 7)) << 4);
      c.aE = pE + (((mi >> 1) ^ ((pE >> 7) & 7)) << 4);
    }
    c.xaddr = sbase + OFF_X + wg * 2 * XBUF_BYTES + (warp * 8 + (lane >> 2)) * 192 + (lane & 3) * 16;
    const uint32_t row0_off = sbase + (wg ? OFF_ROW0_1 : OFF_ROW0_0) - in_base;
    const uint32_t bar_row0 = cl < 2 ? bar_w : b0 + 8 * (BAR_ROW0 + wg);
    if (rank == 0) run_strip<0>(c, row0_off, bar_row0); else run_strip<1>(c, row0_off, bar_row0);
  }
}

typedef CUresult (*EncodeTiledFn)(CUtensorMap*, CUtensorMapDataType, cuuint32_t, void*, const cuuint64_t*, const cuuint64_t*,
                                  const cuuint32_t*, const cuuint32_t*, CUtensorMapInterleave, CUtensorMapSwizzle,
                                  CUtensorMapL2promotion, CUtensorMapFloatOOBfill);

}

extern "C" void kernel_launch(void* const* d_in, const int* in_sizes, int n_in, void* d_out, int out_size) {
  (void)in_sizes; (void)n_in; (void)out_size;
  static EncodeTiledFn encode = nullptr;
  if (!encode) {
    void* fn = nullptr;
    cudaDriverEntryPointQueryResult qr;
    cudaGetDriverEntryPoint("cuTensorMapEncodeTiled", &fn, cudaEnableDefault, &qr);
    encode = (EncodeTiledFn)fn;
    cudaFuncSetAttribute(dilated_conv_wino_kernel, cudaFuncAttributeMaxDynamicSharedMemorySize, SMEM_BYTES);
  }
  CUtensorMap xmap;
  const cuuint64_t dims[5] = {CH, 4, IMG_W / 8, 2, IMG_H};
  const cuuint64_t strides[4] = {CH * 2, 8 * CH * 2, 4 * CH * 2, IMG_W * CH * 2};
  const cuuint32_t box[5] = {48, 2, 17, 2, 1};
  const cuuint32_t estr[5] = {1, 1, 1, 1, 1};
#define PROMO CU_TENSOR_MAP_L2_PROMOTION_L2_128B
  encode(&xmap, CU_TENSOR_MAP_DATA_TYPE_BFLOAT16, 5, d_in[0], dims, strides, box, estr, CU_TENSOR_MAP_INTERLEAVE_NONE,
         CU_TENSOR_MAP_SWIZZLE_128B, PROMO, CU_TENSOR_MAP_FLOAT_OOB_FILL_NONE);
  CUtensorMap omap;
  const cuuint64_t odims[5] = {2 * CH, IMG_W / 8, 2, 2, IMG_H};
  const cuuint64_t ostrides[4] = {8 * CH * 2, 4 * CH * 2, 2 * CH * 2, IMG_W * CH * 2};
  const cuuint32_t obox[5] = {2 * CH, 16, 2, 1, 1};
  encode(&omap, CU_TENSOR_MAP_DATA_TYPE_BFLOAT16, 5, d_out, odims, ostrides, obox, estr, CU_TENSOR_MAP_INTERLEAVE_NONE,
         CU_TENSOR_MAP_SWIZZLE_NONE, CU_TENSOR_MAP_L2_PROMOTION_NONE, CU_TENSOR_MAP_FLOAT_OOB_FILL_NONE);
  dilated_conv_wino_kernel<<<2 * NCL, 384, SMEM_BYTES>>>(xmap, omap, (const __nv_bfloat16*)d_in[0], (const __nv_bfloat16*)d_in[1], (__nv_bfloat16*)d_out);
}
```

```cpp
#include <cuda_runtime.h>
#include <cuda_bf16.h>
#include <cuda.h>
#include <stdint.h>

namespace {

constexpr int IMG_H = 512, IMG_W = 512, CH = 96;
constexpr int NSTAGE = 2;

constexpr int BT_BYTES   = 3072;
constexpr int W_BYTES    = 36 * BT_BYTES;
constexpr int BOX_BYTES  = 68 * 96;
constexpr int OFF_BOXB   = 70 * 128;
constexpr int STAGE_BYTES = 144 * 128;
constexpr int OFF_V      = 72 * 128;
constexpr int WG_IN_BYTES = STAGE_BYTES + 138 * 128;
constexpr int OFF_W      = 0;
constexpr int OFF_IN     = OFF_W + W_BYTES;
constexpr int OFF_X      = OFF_IN + 2 * WG_IN_BYTES;
constexpr int X_BYTES    = 3072;
constexpr int XBUF_BYTES = 4 * X_BYTES;
constexpr int SMEM_BYTES = OFF_X + 4 * XBUF_BYTES;
constexpr int OFF_ROW0_0 = OFF_X + ((OFF_IN - OFF_X) & 1023);
constexpr int OFF_ROW0_1 = OFF_X + 2 * XBUF_BYTES + ((OFF_IN + WG_IN_BYTES - OFF_X) & 1023);
constexpr int OFF_BAR    = OFF_IN + 138 * 128;
constexpr int BAR_FULL = 0, BAR_EMPTY = 4, BAR_STAGED = 8, BAR_XFULL = 12, BAR_W = 28, BAR_ROW0 = 32, BAR_READY = 34;
static_assert(SMEM_BYTES <= 232448, "shared memory");
constexpr uint32_t SMEM_BASE = 1024;
constexpr uint64_t BDESC = (uint64_t)((SMEM_BASE + OFF_W) >> 4) | ((uint64_t)(1536 >> 4) << 16) | ((uint64_t)(128 >> 4) << 32);

__device__ __forceinline__ void wg_fence()  { asm volatile("wgmma.fence.sync.aligned;" ::: "memory"); }
__device__ __forceinline__ void wg_commit() { asm volatile("wgmma.commit_group.sync.aligned;" ::: "memory"); }
template <int N> __device__ __forceinline__ void wg_wait() { asm volatile("wgmma.wait_group.sync.aligned %0;" ::"n"(N) : "memory"); }

template <int SCALE_D>
__device__ __forceinline__ void wgmma96(float (&d)[48], const uint32_t (&a)[4], uint64_t DESC) {
  asm volatile(
      "{\n.reg .pred p;\nsetp.ne.b32 p, %53, 0;\n"
      "wgmma.mma_async.sync.aligned.m64n96k16.f32.bf16.bf16 "
      "{%0,%1,%2,%3,%4,%5,%6,%7,%8,%9,%10,%11,%12,%13,%14,%15,%16,%17,%18,%19,%20,%21,%22,%23,"
      "%24,%25,%26,%27,%28,%29,%30,%31,%32,%33,%34,%35,%36,%37,%38,%39,%40,%41,%42,%43,%44,%45,%46,%47}, "
      "{%48,%49,%50,%51}, %52, p, 1, 1, 1;\n}\n"
      : "+f"(d[0]), "+f"(d[1]), "+f"(d[2]), "+f"(d[3]), "+f"(d[4]), "+f"(d[5]), "+f"(d[6]), "+f"(d[7]),
        "+f"(d[8]), "+f"(d[9]), "+f"(d[10]), "+f"(d[11]), "+f"(d[12]), "+f"(d[13]), "+f"(d[14]), "+f"(d[15]),
        "+f"(d[16]), "+f"(d[17]), "+f"(d[18]), "+f"(d[19]), "+f"(d[20]), "+f"(d[21]), "+f"(d[22]), "+f"(d[23]),
        "+f"(d[24]), "+f"(d[25]), "+f"(d[26]), "+f"(d[27]), "+f"(d[28]), "+f"(d[29]), "+f"(d[30]), "+f"(d[31]),
        "+f"(d[32]), "+f"(d[33]), "+f"(d[34]), "+f"(d[35]), "+f"(d[36]), "+f"(d[37]), "+f"(d[38]), "+f"(d[39]),
        "+f"(d[40]), "+f"(d[41]), "+f"(d[42]), "+f"(d[43]), "+f"(d[44]), "+f"(d[45]), "+f"(d[46]), "+f"(d[47])
      : "r"(a[0]), "r"(a[1]), "r"(a[2]), "r"(a[3]), "l"(DESC), "n"(SCALE_D));
}

__device__ __forceinline__ void ldsm4(uint32_t (&r)[4], uint32_t addr) {
  asm volatile("ldmatrix.sync.aligned.m8n8.x4.shared.b16 {%0,%1,%2,%3}, [%4];"
               : "=r"(r[0]), "=r"(r[1]), "=r"(r[2]), "=r"(r[3]) : "r"(addr) : "memory");
}
__device__ __forceinline__ uint32_t badd(uint32_t a, uint32_t b) {
  uint32_t d; asm volatile("add.rn.bf16x2 %0, %1, %2;" : "=r"(d) : "r"(a), "r"(b)); return d;
}
__device__ __forceinline__ uint32_t bsub(uint32_t a, uint32_t b) {
  uint32_t d; asm volatile("sub.rn.bf16x2 %0, %1, %2;" : "=r"(d) : "r"(a), "r"(b)); return d;
}
__device__ __forceinline__ float bf_lo(uint32_t v) {
  return __uint_as_float(v << 16);
}
__device__ __forceinline__ float bf_hi(uint32_t v) { return __uint_as_float(v & 0xffff0000u); }
__device__ __forceinline__ uint32_t pack2(float lo, float hi) {
  uint32_t d; asm volatile("cvt.rn.bf16x2.f32 %0, %1, %2;" : "=r"(d) : "f"(hi), "f"(lo)); return d;
}

__device__ __forceinline__ void mbar_wait(uint32_t bar, uint32_t parity) {
  asm volatile(
      "{\n.reg .pred p;\n.reg .u32 it;\n"
      "mbarrier.try_wait.parity.shared::cta.b64 p, [%0], %1;\n"
      "@p bra WAIT_DONE;\n"
      "mov.u32 it, 0;\n"
      "WAIT_LOOP:\n"
      ".pragma \"nounroll\";\n"
      "mbarrier.try_wait.parity.shared::cta.b64 p, [%0], %1;\n"
      "@p bra WAIT_DONE;\n"
      "add.u32 it, it, 1;\n"
      "setp.lt.u32 p, it, 4194304;\n"
      "@p bra WAIT_LOOP;\n"
      "trap;\n"
      "WAIT_DONE:\n}\n" ::"r"(bar), "r"(parity) : "memory");
}
__device__ __forceinline__ void mbar_init(uint32_t bar, uint32_t count) {
  asm volatile("mbarrier.init.shared::cta.b64 [%0], %1;" ::"r"(bar), "r"(count) : "memory");
}
__device__ __forceinline__ void mbar_arrive(uint32_t bar) {
  asm volatile("mbarrier.arrive.shared::cta.b64 _, [%0];" ::"r"(bar) : "memory");
}
__device__ __forceinline__ void mbar_expect_tx(uint32_t bar, uint32_t bytes) {
  asm volatile("mbarrier.arrive.expect_tx.shared::cta.b64 _, [%0], %1;" ::"r"(bar), "r"(bytes) : "memory");
}
__device__ __forceinline__ void tma_load5(uint32_t dst, const CUtensorMap* map, uint32_t bar, int c0, int c1, int c2, int c3, int c4) {
  asm volatile("cp.async.bulk.tensor.5d.shared::cluster.global.mbarrier::complete_tx::bytes [%0], [%1, {%3,%4,%5,%6,%7}], [%2];"
               ::"r"(dst), "l"(map), "r"(bar), "r"(c0), "r"(c1), "r"(c2), "r"(c3), "r"(c4) : "memory");
}
__device__ __forceinline__ void bulk_load(uint32_t dst, const void* src, uint32_t bytes, uint32_t bar) {
  asm volatile("cp.async.bulk.shared::cluster.global.mbarrier::complete_tx::bytes [%0], [%1], %2, [%3];"
               ::"r"(dst), "l"(src), "r"(bytes), "r"(bar) : "memory");
}
template <int OFF>
__device__ __forceinline__ void st_async4(uint32_t cluster_addr, uint32_t cluster_bar, uint32_t a, uint32_t b, uint32_t c, uint32_t d) {
  asm volatile("st.async.shared::cluster.mbarrier::complete_tx::bytes.v4.b32 [%0+%6], {%2,%3,%4,%5}, [%1];"
               ::"r"(cluster_addr), "r"(cluster_bar), "r"(a), "r"(b), "r"(c), "r"(d), "n"(OFF) : "memory");
}
__device__ __forceinline__ void stsm4(uint32_t addr, uint32_t a, uint32_t b, uint32_t c, uint32_t d) {
  asm volatile("stmatrix.sync.aligned.m8n8.x4.shared.b16 [%0], {%1,%2,%3,%4};" ::"r"(addr), "r"(a), "r"(b), "r"(c), "r"(d) : "memory");
}
__device__ __forceinline__ void lds4(uint32_t (&r)[4], uint32_t addr) {
  asm volatile("ld.shared.v4.b32 {%0,%1,%2,%3}, [%4];" : "=r"(r[0]), "=r"(r[1]), "=r"(r[2]), "=r"(r[3]) : "r"(addr) : "memory");
}
__device__ __forceinline__ void sts4(uint32_t addr, const uint32_t (&r)[4]) {
  asm volatile("st.shared.v4.b32 [%0], {%1,%2,%3,%4};" ::"r"(addr), "r"(r[0]), "r"(r[1]), "r"(r[2]), "r"(r[3]) : "memory");
}
__device__ __forceinline__ void tma_store5(const CUtensorMap* map, uint32_t src, int c0, int c1, int c2, int c3, int c4) {
  asm volatile("cp.async.bulk.tensor.5d.global.shared::cta.bulk_group [%0, {%2,%3,%4,%5,%6}], [%1];"
               ::"l"(map), "r"(src), "r"(c0), "r"(c1), "r"(c2), "r"(c3), "r"(c4) : "memory");
  asm volatile("cp.async.bulk.commit_group;" ::: "memory");
}
__device__ __forceinline__ bool elect_one() {
  uint32_t p;
  asm volatile("{\n.reg .pred P;\nelect.sync _|P, 0xffffffff;\nselp.u32 %0, 1, 0, P;\n}\n" : "=r"(p));
  return p;
}
__device__ __forceinline__ uint32_t mapa(uint32_t addr, uint32_t rank) {
  uint32_t r; asm("mapa.shared::cluster.u32 %0, %1, %2;" : "=r"(r) : "r"(addr), "r"(rank)); return r;
}

__device__ __forceinline__ void tr_sum(uint32_t (&t)[3][4], const uint32_t (&U)[3][4], const uint32_t (&V)[3][4]) {
#pragma unroll
  for (int k = 0; k < 3; k++)
#pragma unroll
    for (int i = 0; i < 4; i++) t[k][i] = badd(U[k][i], V[k][i]);
}
__device__ __forceinline__ void tr_dif(uint32_t (&t)[3][4], const uint32_t (&U)[3][4], const uint32_t (&V)[3][4]) {
#pragma unroll
  for (int k = 0; k < 3; k++)
#pragma unroll
    for (int i = 0; i < 4; i++) t[k][i] = bsub(V[k][i], U[k][i]);
}
__device__ __forceinline__ void tr_t0(uint32_t (&t)[3][4], const uint32_t (&V)[3][4], const uint32_t (&E)[3][4]) {
#pragma unroll
  for (int k = 0; k < 3; k++) {
    t[k][0] = bsub(E[k][0], V[k][0]); t[k][1] = bsub(V[k][0], V[k][1]);
    t[k][2] = bsub(E[k][2], V[k][2]); t[k][3] = bsub(V[k][2], V[k][3]);
  }
}
__device__ __forceinline__ void tr_t3(uint32_t (&t)[3][4], const uint32_t (&U)[3][4], const uint32_t (&E)[3][4]) {
#pragma unroll
  for (int k = 0; k < 3; k++) {
    t[k][0] = bsub(U[k][1], U[k][0]); t[k][1] = bsub(E[k][1], U[k][1]);
    t[k][2] = bsub(U[k][3], U[k][2]); t[k][3] = bsub(E[k][3], U[k][3]);
  }
}
__device__ __forceinline__ void ld3(uint32_t (&R)[3][4], uint32_t aU, int off) {
#pragma unroll
  for (int k = 0; k < 3; k++) ldsm4(R[k], (aU ^ (32 * k)) + off);
}
template <int COMP, int AGE, int FIRST>
__device__ __forceinline__ void batch_(float (&acc)[48], const uint32_t (&t)[3][4], uint64_t bd) {
  constexpr int base = ((COMP * 3 + AGE) * 3) * BT_BYTES;
  wgmma96<FIRST ? 0 : 1>(acc, t[0], bd + ((base) >> 4));
  wgmma96<1>(acc, t[1], bd + ((base + BT_BYTES) >> 4));
  wgmma96<1>(acc, t[2], bd + ((base + 2 * BT_BYTES) >> 4));
  wg_commit();
}

template <int RANK, int I0, int I1>
__device__ __forceinline__ void butterfly(float (&X)[48], float (&Y)[48]) {
#pragma unroll
  for (int i = I0; i < I1; i++) {
    if (RANK == 0) asm volatile("sub.rn.f32 %0, %0, %1;\nfma.rn.f32 %1, %1, 0f40000000, %0;" : "+f"(X[i]), "+f"(Y[i]));
    else           asm volatile("add.rn.f32 %0, %0, %1;\nfma.rn.f32 %1, %1, 0fC0000000, %0;" : "+f"(X[i]), "+f"(Y[i]));
  }
}

struct Ctx {
  uint32_t aU, aE;
  uint32_t bar_full;
  uint32_t bar_ready;
  uint32_t xaddr, xfull;
  char* out;
  int wg, warp;
  uint32_t sig;
  int u0, h0, hstep;
  int nrows;
};

template <int BUF, int C0, int C1>
__device__ __forceinline__ void load_partner(const Ctx& c, uint32_t (&P)[6][4]) {
#pragma unroll
  for (int ch = C0; ch < C1; ch++) lds4(P[ch], c.xaddr + BUF * XBUF_BYTES + (ch & 1) * 6144 + (ch >> 1) * 64);
}
template <int RANK, int BUF, int CH0>
__device__ __forceinline__ void send_chunk(const Ctx& c, const float (&X)[48]) {
  constexpr uint32_t RDELTA = RANK ? 0xFF000000u : 0x01000000u;
  constexpr int m = CH0 >> 1, s = CH0 & 1;
  uint32_t o[4];
#pragma unroll
  for (int ss = 0; ss < 4; ss++) o[ss] = pack2(X[16 * m + 4 * ss + 2 * s], X[16 * m + 4 * ss + 2 * s + 1]);
  st_async4<BUF * XBUF_BYTES + s * 6144 + m * 64>(c.xaddr + RDELTA, c.xfull + BUF * 64 + RDELTA, o[0], o[1], o[2], o[3]);
}

#define PF_START 1
#define WI0 0x404001u
#define WI1 0x110d05u
#define WI2 0x404009u
#define PF_DIST 1
#define RORD 0x642501
#define RORDS 0x6521

struct Regs {
  float X[48], Y[48];
  uint32_t T[4][2][3][4];
  uint32_t U[3][4], V[3][4], E[3][4];
  uint32_t Z[6][4], P[6][4];
};

__device__ __forceinline__ void warp_done(uint32_t bar) {
  asm volatile("fence.proxy.async.shared::cta;" ::: "memory");
  __syncwarp();
  asm volatile("{\n.reg .pred q;\nelect.sync _|q, 0xffffffff;\n@q mbarrier.arrive.shared::cta.b64 _, [%0];\n}\n" ::"r"(bar) : "memory");
}
__device__ __forceinline__ void warp_release(uint32_t bar, uint32_t a, uint32_t b, uint32_t c, uint32_t d, uint32_t zero) {
  asm volatile("{\n.reg .pred q;\n.reg .b32 t;\nlop3.b32 t, %1, %4, %5, 0x80;\nlop3.b32 t, t, %2, %3, 0x80;\nor.b32 t, t, 1;\n"
               "elect.sync _|q, 0xffffffff;\n@q mbarrier.arrive.shared::cta.b64 _, [%0], t;\n}\n"
               ::"r"(bar), "r"(a), "r"(b), "r"(c), "r"(d), "r"(zero) : "memory");
}
__device__ __forceinline__ void warp_arrive_if(uint32_t bar, int on) {
  asm volatile("{\n.reg .pred p, q;\nelect.sync _|q, 0xffffffff;\nsetp.ne.and.s32 p, %1, 0, q;\n@p mbarrier.arrive.shared::cta.b64 _, [%0];\n}\n"
               ::"r"(bar), "r"(on) : "memory");
}
template <int C0, int C1>
__device__ __forceinline__ void pack_acc(uint32_t (&Z)[6][4], const float (&Y)[48]) {
#pragma unroll
  for (int ch = C0; ch < C1; ch++)
#pragma unroll
    for (int ss = 0; ss < 4; ss++) {
      const int i = 16 * (ch >> 1) + 4 * ss + 2 * (ch & 1);
      Z[ch][ss] = pack2(Y[i], Y[i + 1]);
    }
}
template <int BUF, int C0, int C1>
__device__ __forceinline__ void add_stage(const Ctx& c, uint32_t (&Z)[6][4], const uint32_t (&P)[6][4]) {
#pragma unroll
  for (int ch = C0; ch < C1; ch++)
#pragma unroll
    for (int ss = 0; ss < 4; ss++) Z[ch][ss] = badd(Z[ch][ss], P[ch][ss]);
#pragma unroll
  for (int ch = C0; ch < C1; ch++) sts4(c.xaddr + BUF * XBUF_BYTES + (ch & 1) * 6144 + (ch >> 1) * 64, Z[ch]);
}

__device__ __forceinline__ uint64_t get_bd(const Ctx& c, int n) {
  return BDESC + (uint64_t)(uint32_t)(n >> 8);
}
#define G1  batch_<0, 0, 1>(r.X, r.T[0][OLD], bd);
#define G2  batch_<0, 1, 0>(r.X, r.T[0][MID], bd);
#define G3  batch_<0, 2, 0>(r.X, r.T[0][OLD], bd);
#define G4  batch_<1, 0, 1>(r.Y, r.T[1][OLD], bd);
#define G5  batch_<1, 1, 0>(r.Y, r.T[1][MID], bd);
#define G6  batch_<1, 2, 0>(r.Y, r.T[1][OLD], bd);
#define G7  if (OLD == 1) batch_<2, 0, 0>(r.X, r.T[2][OLD], bd); else { if (!skip) { F batch_<2, 0, 0>(r.X, r.T[2][OLD], bd); } else { F wg_commit(); } F }
#define G8  batch_<2, 1, 0>(r.X, r.T[2][MID], bd);
#define G9  batch_<2, 2, 0>(r.X, r.T[2][OLD], bd);
#define G10 if (OLD == 1) batch_<3, 0, 0>(r.Y, r.T[3][OLD], bd); else { if (!skip) { F batch_<3, 0, 0>(r.Y, r.T[3][OLD], bd); } else { F wg_commit(); } F }
#define G11 batch_<3, 1, 0>(r.Y, r.T[3][MID], bd);
#define G12 batch_<3, 2, 0>(r.Y, r.T[3][OLD], bd);
#define F   wg_fence();
#define W(k) wg_wait<k>();
#define PACK pack_acc<0, 6>(r.Z, r.Y);
#define PK(a, b) pack_acc<a, b>(r.Z, r.Y);
#define XW  mbar_wait(c.xfull + MID * 64, ((n - 1) >> 1) & 1); FIX3
#define LP(a, b) load_partner<MID, a, b>(c, r.P);
#define AS(a, b) add_stage<MID, a, b>(c, r.Z, r.P);
#define LV1 if (RANK == 0) ld3(r.V, c.aU, OLD * STAGE_BYTES + OFF_V); else ld3(r.U, c.aU, OLD * STAGE_BYTES);
#define LU1 if (RANK == 0) ld3(r.U, c.aU, OLD * STAGE_BYTES); else ld3(r.V, c.aU, OLD * STAGE_BYTES + OFF_V);
#define LU2 if (RANK == 0) ld3(r.U, c.aU, MID * STAGE_BYTES); else ld3(r.V, c.aU, MID * STAGE_BYTES + OFF_V);
#define LE  ld3(r.E, c.aE, OLD * STAGE_BYTES);
#define LEk(k)  ldsm4(r.E[k], (c.aE ^ (32 * k)) + OLD * STAGE_BYTES);
#define LV1k(k) if (RANK == 0) ldsm4(r.V[k], (c.aU ^ (32 * k)) + OLD * STAGE_BYTES + OFF_V); else ldsm4(r.U[k], (c.aU ^ (32 * k)) + OLD * STAGE_BYTES);
#define LV2k(k) if (RANK == 0) ldsm4(r.V[k], (c.aU ^ (32 * k)) + MID * STAGE_BYTES + OFF_V); else ldsm4(r.U[k], (c.aU ^ (32 * k)) + MID * STAGE_BYTES);
#define LU1k(k) if (RANK == 0) ldsm4(r.U[k], (c.aU ^ (32 * k)) + OLD * STAGE_BYTES); else ldsm4(r.V[k], (c.aU ^ (32 * k)) + OLD * STAGE_BYTES + OFF_V);
#define LU2k(k) if (RANK == 0) ldsm4(r.U[k], (c.aU ^ (32 * k)) + MID * STAGE_BYTES); else ldsm4(r.V[k], (c.aU ^ (32 * k)) + MID * STAGE_BYTES + OFF_V);
#define TRS tr_sum(r.T[0][OLD], r.U, r.V);
#define TRF tr_dif(r.T[1][OLD], r.U, r.V);
#define TRC if (RANK == 0) tr_t3(r.T[2][OLD], r.U, r.E); else tr_t0(r.T[2][OLD], r.V, r.E);
#define TRD if (RANK == 0) tr_t0(r.T[3][OLD], r.V, r.E); else tr_t3(r.T[3][OLD], r.U, r.E);
#define SIG warp_arrive_if(c.sig + 64 * (OLD ? c.wg : 1 - c.wg), OLD ? 1 : n | c.wg);
#define FEN asm volatile("fence.proxy.async.shared::cta;" ::: "memory");
#define DONE __syncwarp(); warp_arrive_if(c.bar_full + 8 * (BAR_STAGED - BAR_FULL + MID), 1);
#define EMP warp_release(c.bar_full + 8 * (BAR_EMPTY - BAR_FULL + OLD), r.E[0][RANK], r.E[1][RANK], r.E[2][RANK], __float_as_uint(r.Y[47]), n >> 8);
#define FW  if (OLD == 1) mbar_wait(c.bar_full, ((n + 2) >> 1) & 1); \
            else mbar_wait(n ? c.bar_full + 8 : c.bar_ready, n ? ((n + 3) >> 1) & 1 : 0);
#define FIX3 if (OLD == 1 && n == 1) { mbar_wait(c.bar_full + 8, 1); SCHED_FIX3 }
#define SND(k) send_chunk<RANK, OLD, k>(c, r.X);
#define SCHED1 LV1k(0) LU1k(2) F G1 XW LP(0,1) LP(1,2) LP(2,3) W(1) PK(0,1) LP(3,4) LP(4,5) PK(1,2) LP(5,6) AS(0,1) PK(2,3) AS(1,2) AS(2,3) PK(3,4) F G2 LV1k(1) PK(4,5) LV1k(2) AS(3,4) PK(5,6) AS(4,5) W(1) TRS AS(5,6) F G4 LEk(0) F G5 W(1) TRF SIG F G3 LEk(1) F G6 LEk(2)
#define SCHED1_FIRST SIG LEk(0) LEk(1) LEk(2)
#define SCHED_FIX3 LU1k(0) LU1k(1) LU1k(2) LV1k(0)
#define SCHED2 F G7 EMP F G8 W(1) TRC F G9 FW W(0) SND(0) F G10 SND(1) F G11 SND(2) SND(3) FEN LU2k(0) DONE SND(4) W(1) TRD LU2k(1) SND(5) F G12

template <int RANK, int OLD, bool FIRST>
__device__ __forceinline__ void phase1(const Ctx& c, int n, Regs& r) {
  constexpr int MID = 1 - OLD;
  const uint64_t bd = get_bd(c, n);
  if (FIRST) {
    mbar_wait(c.bar_full + 8 * OLD, 0);
    LU1 LV1 W(1) TRS F G3 W(1) TRF F G6
    SCHED1_FIRST
  } else {
    SCHED1
  }
}

template <int RANK, int OLD>
__device__ __forceinline__ void phase2(const Ctx& c, int n, Regs& r) {
  constexpr int MID = 1 - OLD;
  const uint64_t bd = get_bd(c, n);
  wg_wait<0>();
  butterfly<RANK, 0, 48>(r.X, r.Y);
  const bool skip = (unsigned)(c.h0 + n * c.hstep) >= (unsigned)IMG_H;
  SCHED2
}

template <int RANK>
__device__ __forceinline__ void finish_strip(const Ctx& c, Regs& r, int buf) {
  warp_arrive_if(c.sig + 64 * (buf ^ c.wg), 1);
  wg_wait<0>();
  pack_acc<0, 6>(r.Z, r.Y);
  const int lane = threadIdx.x & 31, g = lane >> 2;
  const int px = 8 * (c.u0 + 4 * c.warp + (g >> 1)) + (g & 1) + 2 * RANK;
  char* o = c.out + ((size_t)(c.h0 + c.nrows * c.hstep) * IMG_W + px) * (CH * 2) + (lane & 3) * 16;
  mbar_wait(c.xfull + buf * 64, ((c.nrows - 1) >> 1) & 1);
#pragma unroll
  for (int ch = 0; ch < 6; ch++) lds4(r.P[ch], c.xaddr + buf * XBUF_BYTES + (ch & 1) * 6144 + (ch >> 1) * 64);
#pragma unroll
  for (int ch = 0; ch < 6; ch++)
    asm volatile("st.global.v4.b32 [%0], {%1,%2,%3,%4};" ::"l"(o + (ch & 1) * (4 * CH * 2) + (ch >> 1) * 64), "r"(badd(r.Z[ch][0], r.P[ch][0])),
                 "r"(badd(r.Z[ch][1], r.P[ch][1])), "r"(badd(r.Z[ch][2], r.P[ch][2])), "r"(badd(r.Z[ch][3], r.P[ch][3])) : "memory");
}

__device__ __forceinline__ void transform_weights(uint32_t sbase, int rank, uint32_t items, int lane) {
  const uint32_t bar_w = sbase + OFF_BAR + 8 * BAR_W;
  const uint32_t o_w0 = (rank ? 2 : 3) * 9 * BT_BYTES, o_w2 = (rank ? 3 : 2) * 9 * BT_BYTES;
#pragma unroll 1
  for (; items; items >>= 8) {
    const int item = (items & 255) - 1;
    if (item >= 18) break;
    const uint32_t base = sbase + OFF_W + item * 1536;
    mbar_wait(bar_w + 8 * (item / 6), 0);
    uint32_t wa[3][4], wb[3][4], wd[3][4];
    const uint32_t src = base + (lane >> 2) * 192 + (lane & 3) * 16;
#pragma unroll
    for (int m = 0; m < 3; m++) lds4(wa[m], src + o_w0 + m * 64);
#pragma unroll
    for (int m = 0; m < 3; m++) lds4(wd[m], src + o_w2 + m * 64);
#pragma unroll
    for (int m = 0; m < 3; m++) lds4(wb[m], src + m * 64);
    __syncwarp();
    const uint32_t dst = base + lane * 16;
#pragma unroll
    for (int m = 0; m < 3; m++) stsm4(dst + m * 512 + o_w0, wa[m][0], wa[m][1], wa[m][2], wa[m][3]);
#pragma unroll
    for (int m = 0; m < 3; m++) stsm4(dst + m * 512 + o_w2, wd[m][0], wd[m][1], wd[m][2], wd[m][3]);
#pragma unroll
    for (int m = 0; m < 3; m++) {
      uint32_t g1[4], g2[4];
#pragma unroll
      for (int ss = 0; ss < 4; ss++) {
        const uint32_t a = wa[m][ss], b = wb[m][ss], d = wd[m][ss];
        const float slo = 0.5f * (bf_lo(a) + bf_lo(d)), shi = 0.5f * (bf_hi(a) + bf_hi(d));
        const float blo = bf_lo(b), bhi = bf_hi(b);
        g1[ss] = pack2(fmaf(blo, 0.5f, slo), fmaf(bhi, 0.5f, shi));
        g2[ss] = pack2(fmaf(blo, -0.5f, slo), fmaf(bhi, -0.5f, shi));
      }
      stsm4(dst + m * 512, g1[0], g1[1], g1[2], g1[3]);
      stsm4(dst + m * 512 + 9 * BT_BYTES, g2[0], g2[1], g2[2], g2[3]);
    }
  }
  asm volatile("fence.proxy.async.shared::cta;" ::: "memory");
  __syncwarp();
  if (elect_one()) mbar_arrive(bar_w + 24);
}

template <int RANK>
__device__ __forceinline__ void run_strip(const Ctx& c, uint32_t row0_off, uint32_t bar_row0) {
  Regs r;
#pragma unroll
  for (int i = 0; i < 48; i++) { r.X[i] = 0.f; r.Y[i] = 0.f; r.Z[i % 6][i / 12] = 0; r.P[i % 6][i / 12] = 0; }
#pragma unroll
  for (int m = 1; m >= 0; m--) {
    const uint32_t off = m ? STAGE_BYTES : row0_off;
    mbar_wait(m ? c.bar_full + 8 : bar_row0, 0);
    if (m == 0 && (unsigned)c.h0 >= (unsigned)IMG_H) {
#pragma unroll
      for (int i = 0; i < 48; i++) asm volatile("" : "=r"(r.T[i / 12][0][(i / 4) % 3][i % 4]));
      continue;
    }
    ld3(r.U, c.aU, off);
    ld3(r.V, c.aU, off + OFF_V);
    ld3(r.E, c.aE, off);
    tr_sum(r.T[0][m], r.U, r.V);
    tr_dif(r.T[1][m], r.U, r.V);
    if (m) mbar_wait(SMEM_BASE + (RANK << 24) + OFF_BAR + 8 * BAR_W + 24, 0);
    wg_fence();
    if (m) { batch_<0, 1, 1>(r.X, r.T[0][1], BDESC); batch_<1, 1, 1>(r.Y, r.T[1][1], BDESC); }
    else   { batch_<0, 0, 0>(r.X, r.T[0][0], BDESC); batch_<1, 0, 0>(r.Y, r.T[1][0], BDESC); }
    tr_t3(r.T[RANK == 0 ? 2 : 3][m], r.U, r.E);
    tr_t0(r.T[RANK == 0 ? 3 : 2][m], r.V, r.E);
  }
  warp_done(c.bar_full + 8 * (BAR_EMPTY - BAR_FULL + 1));
  phase1<RANK, 0, true>(c, 0, r);
#pragma unroll 1
  for (int n = 0;; n += 2) {
    phase2<RANK, 0>(c, n, r);
    if (n + 1 == c.nrows) break;
    phase1<RANK, 1, false>(c, n + 1, r);
    phase2<RANK, 1>(c, n + 1, r);
    if (n + 2 == c.nrows) break;
    phase1<RANK, 0, false>(c, n + 2, r);
  }
  finish_strip<RANK>(c, r, (c.nrows - 1) & 1);
}

constexpr int NCL = 66;
struct Strip { int seg, h0, nrows; };
__device__ __forceinline__ bool is_down(int cl) { return cl < 2 || !((cl - 2) & 4); }
__device__ __forceinline__ Strip get_strip(int cl, int wg) {
  const int k = cl - 2, i = k >> 2;
  const int q = (i & 1) ? (wg ? 16 + 15 * i : 16 * i + 16) : (wg ? 30 + 15 * i : 16 * i - 1);
  return cl < 2 ? Strip{2 * cl + wg, -1, 16} : Strip{k & 3, 2 * q + wg, 16 - wg};
}

__device__ __forceinline__ void load_rows(const CUtensorMap* xmap, const char* x, uint32_t sbase, int rank, int wg, Strip sp, int hstep) {
  const uint32_t full = sbase + OFF_BAR + 8 * (BAR_FULL + 2 * wg), empty = full + 8 * (BAR_EMPTY - BAR_FULL);
  const uint32_t in_base = sbase + OFF_IN + wg * WG_IN_BYTES;
  const int halo = sp.seg != 3 * rank ? 6 : 0;
  const char* xseg = x + (sp.seg * 128 + (rank ? 64 : -halo)) * (CH * 2);
  const int pf_bytes = (64 + halo) * CH * 2;
#pragma unroll 1
  for (int m = 3; m <= sp.nrows + 2; m++) {
    const int s = m & 1, h = sp.h0 + m * hstep;
    mbar_wait(empty + 8 * s, ((m - 3) >> 1) & 1);
    if (m == 3) {
      asm volatile("mbarrier.arrive.shared::cluster.b64 _, [%0];" ::"r"((sbase + OFF_BAR + 8 * (BAR_READY + wg)) ^ 0x01000000u) : "memory");
    }
    if (m <= 4) mbar_arrive(full + 8 * s);
    if (m < sp.nrows + 2) {
      const int hp = h + PF_DIST * hstep;
      const bool pf = PF_DIST > 0 && m >= 4 + PF_START && m + PF_DIST < sp.nrows + 2 && (unsigned)hp < (unsigned)IMG_H;
      mbar_expect_tx(full + 8 * s, 2 * BOX_BYTES);
      tma_load5(in_base + s * STAGE_BYTES, xmap, full + 8 * s, rank * 48, 0, sp.seg * 16, 0, h);
      tma_load5(in_base + s * STAGE_BYTES + OFF_BOXB, xmap, full + 8 * s, rank * 48, 2, sp.seg * 16 - 1, 0, h);
      if (pf) asm volatile("cp.async.bulk.prefetch.L2.global [%0], %1;" ::"l"(xseg + (size_t)hp * (IMG_W * CH * 2)), "r"(pf_bytes) : "memory");
    } else {
      mbar_arrive(full + 8 * s);
    }
  }
}
__device__ __forceinline__ void store_rows(const CUtensorMap* omap, uint32_t sbase, int rank, int wg, Strip sp, int hstep) {
  const uint32_t full = sbase + OFF_BAR + 8 * (BAR_FULL + 2 * wg), staged = full + 8 * (BAR_STAGED - BAR_FULL);
  const uint32_t xfull = sbase + OFF_BAR + 8 * (BAR_XFULL + 4 * wg);
#pragma unroll 1
  for (int n = 0; n < sp.nrows - 1; n++) {
    const int b = n & 1;
    mbar_wait(staged + 8 * b, ((n + 1) >> 1) & 1);
    tma_store5(omap, sbase + OFF_X + (2 * wg + b) * XBUF_BYTES, 0, sp.seg * 16, 0, rank, sp.h0 + (n + 1) * hstep);
#pragma unroll
    for (int q = 0; q < 4; q++) mbar_expect_tx(xfull + 64 * b + 8 * q, X_BYTES);
    asm volatile("cp.async.bulk.wait_group.read 0;" ::: "memory");
    if (n == 0) mbar_wait(xfull + 64, 0);
    if (n + 2 < sp.nrows) asm volatile("mbarrier.arrive.shared::cluster.b64 _, [%0];" ::"r"((full + 8 * (b ^ 1)) ^ 0x01000000u) : "memory");
  }
}

__global__ void __cluster_dims__(2, 1, 1) __launch_bounds__(384, 1)
dilated_conv_wino_kernel(const __grid_constant__ CUtensorMap xmap, const __grid_constant__ CUtensorMap omap,
                         const __nv_bfloat16* __restrict__ x, const __nv_bfloat16* __restrict__ w, __nv_bfloat16* __restrict__ out) {
  extern __shared__ uint8_t smem_raw[];
  const int tid = threadIdx.x;
  const int w12 = __shfl_sync(0xffffffff, tid >> 5, 0);
  const int wg = w12 >> 2, warp = w12 & 3;
  const int lane = tid & 31;
  const int rank = blockIdx.x & 1;
  const int cl = blockIdx.x >> 1;
  const bool down = is_down(cl);
  const uint32_t sbase = SMEM_BASE + (rank << 24);
  const uint32_t b0 = sbase + OFF_BAR;
  const uint32_t bar_w = b0 + 8 * BAR_W;

  if (w12 >= 9) {
    if (elect_one()) {
      const int a = w12 - 9, i = down ? a : 2 - a;
      const char* src = reinterpret_cast<const char*>(w) + (uint32_t)((i * 6 + rank) * (3 * BT_BYTES));
      const uint32_t dst = sbase + OFF_W + a * 3 * BT_BYTES;
      mbar_init(bar_w + 8 * a, 1);
      mbar_expect_tx(bar_w + 8 * a, 9 * BT_BYTES);
      bulk_load(dst + (rank ? 2 : 3) * 9 * BT_BYTES, src, 3 * BT_BYTES, bar_w + 8 * a);
      bulk_load(dst, src + 6 * BT_BYTES, 3 * BT_BYTES, bar_w + 8 * a);
      bulk_load(dst + (rank ? 3 : 2) * 9 * BT_BYTES, src + 12 * BT_BYTES, 3 * BT_BYTES, bar_w + 8 * a);
    }
  } else if (elect_one()) {
    if (w12 < 8) {
      const uint32_t xf = b0 + 8 * (BAR_XFULL + w12);
      mbar_init(xf, 2);
      mbar_init(xf + 64, 2);
      if (w12 < 4) {
        mbar_init(b0 + 8 * (BAR_FULL + w12), 2);
        mbar_expect_tx(b0 + 8 * (BAR_FULL + w12), 2 * BOX_BYTES);
        mbar_arrive(b0 + 8 * (BAR_FULL + w12));
      } else {
        mbar_init(b0 + 8 * (BAR_EMPTY + warp), 4);
        mbar_init(b0 + 8 * (BAR_STAGED + warp), 4);
      }
      mbar_expect_tx(xf, X_BYTES);
      mbar_expect_tx(xf + 64, X_BYTES);
    } else {
      asm volatile("prefetch.tensormap [%0];" ::"l"(&xmap) : "memory");
#pragma unroll
      for (int q = 0; q < 2; q++) {
        mbar_init(b0 + 8 * (BAR_ROW0 + q), 1);
        mbar_init(b0 + 8 * (BAR_READY + q), 1);
      }
      mbar_init(bar_w + 24, 12);
#pragma unroll
      for (int q = 0; q < 2; q++) mbar_expect_tx(b0 + 8 * (BAR_ROW0 + q), 2 * BOX_BYTES);
    }
    asm volatile("fence.mbarrier_init.release.cluster;" ::: "memory");
  }
  __syncthreads();
  asm volatile("barrier.cluster.arrive.relaxed.aligned;" ::: "memory");
  const Strip s0 = get_strip(cl, 0), s1 = get_strip(cl, 1);
  const int hstep = down ? 2 : -2;
  if (w12 == 8 || w12 == 9) {
    if (elect_one()) {
#pragma unroll 1
      for (uint32_t order = cl < 2 ? RORDS : RORD; order; order >>= 4) {
        const int g = (order >> 2) & 1, m = order & 3;
        const uint32_t dst = m == 0 ? sbase + (g ? OFF_ROW0_1 : OFF_ROW0_0) : sbase + OFF_IN + g * WG_IN_BYTES + (m & 1) * STAGE_BYTES;
        const uint32_t bar = b0 + 8 * (m == 0 ? BAR_ROW0 + g : BAR_FULL + 2 * g + (m & 1));
        tma_load5(dst + warp * OFF_BOXB, &xmap, bar, rank * 48, 2 * warp, (g ? s1.seg : s0.seg) * 16 - warp, 0, (g ? s1.h0 : s0.h0) + m * hstep);
      }
      asm volatile("prefetch.tensormap [%0];" ::"l"(&omap) : "memory");
    }
    __syncwarp();
  }
  if ((uint32_t)__cvta_generic_to_shared(smem_raw) != sbase || mapa(sbase, rank ^ 1) != (sbase ^ 0x01000000u)) __trap();
  asm volatile("barrier.cluster.wait.aligned;" ::: "memory");
  transform_weights(sbase, rank, (wg == 0 ? WI0 : wg == 1 ? WI1 : WI2) + warp * 0x010101u, lane);

  if (wg == 2) {
    asm volatile("setmaxnreg.dec.sync.aligned.u32 24;");
    if (elect_one()) {
      if (warp < 2) load_rows(&xmap, reinterpret_cast<const char*>(x), sbase, rank, warp, warp ? s1 : s0, hstep);
      else store_rows(&omap, sbase, rank, warp - 2, warp == 3 ? s1 : s0, hstep);
    }
  } else {
    asm volatile("setmaxnreg.inc.sync.aligned.u32 240;");
    Ctx c;
    c.out = reinterpret_cast<char*>(out);
    c.wg = wg;
    c.warp = warp;
    c.sig = b0 + 8 * (BAR_XFULL + (w12 ^ 4));
    c.bar_full = b0 + 8 * (BAR_FULL + wg * NSTAGE);
    c.bar_ready = b0 + 8 * (BAR_READY + wg);
    c.u0 = (wg ? s1.seg : s0.seg) * 16;
    c.h0 = wg ? s1.h0 : s0.h0;
    c.hstep = hstep;
    c.nrows = wg ? s1.nrows : s0.nrows;
    c.xfull = b0 + 8 * (BAR_XFULL + w12);
    const uint32_t in_base = sbase + OFF_IN + wg * WG_IN_BYTES;
    {
      const int g = lane & 7, mi = lane >> 3;
      const int rU = 8 * warp + g + ((mi & 1) ? 34 : 0);
      const int rE = 8 * warp + g + ((mi & 1) ? 2 : 70 + 34);
      const uint32_t pU = in_base + rU * 128, pE = in_base + rE * 128;
      c.aU = pU + (((mi >> 1) ^ ((pU >> 7) & 7)) << 4);
      c.aE = pE + (((mi >> 1) ^ ((pE >> 7) & 7)) << 4);
    }
    c.xaddr = sbase + OFF_X + wg * 2 * XBUF_BYTES + (warp * 8 + (lane >> 2)) * 192 + (lane & 3) * 16;
    const uint32_t row0_off = sbase + (wg ? OFF_ROW0_1 : OFF_ROW0_0) - in_base;
    const uint32_t bar_row0 = cl < 2 ? bar_w : b0 + 8 * (BAR_ROW0 + wg);
    if (rank == 0) run_strip<0>(c, row0_off, bar_row0); else run_strip<1>(c, row0_off, bar_row0);
  }
}

typedef CUresult (*EncodeTiledFn)(CUtensorMap*, CUtensorMapDataType, cuuint32_t, void*, const cuuint64_t*, const cuuint64_t*,
                                  const cuuint32_t*, const cuuint32_t*, CUtensorMapInterleave, CUtensorMapSwizzle,
                                  CUtensorMapL2promotion, CUtensorMapFloatOOBfill);

}

extern "C" void kernel_launch(void* const* d_in, const int* in_sizes, int n_in, void* d_out, int out_size) {
  (void)in_sizes; (void)n_in; (void)out_size;
  static EncodeTiledFn encode = nullptr;
  if (!encode) {
    void* fn = nullptr;
    cudaDriverEntryPointQueryResult qr;
    cudaGetDriverEntryPoint("cuTensorMapEncodeTiled", &fn, cudaEnableDefault, &qr);
    encode = (EncodeTiledFn)fn;
    cudaFuncSetAttribute(dilated_conv_wino_kernel, cudaFuncAttributeMaxDynamicSharedMemorySize, SMEM_BYTES);
  }
  CUtensorMap xmap;
  const cuuint64_t dims[5] = {CH, 4, IMG_W / 8, 2, IMG_H};
  const cuuint64_t strides[4] = {CH * 2, 8 * CH * 2, 4 * CH * 2, IMG_W * CH * 2};
  const cuuint32_t box[5] = {48, 2, 17, 2, 1};
  const cuuint32_t estr[5] = {1, 1, 1, 1, 1};
#define PROMO CU_TENSOR_MAP_L2_PROMOTION_L2_128B
  encode(&xmap, CU_TENSOR_MAP_DATA_TYPE_BFLOAT16, 5, d_in[0], dims, strides, box, estr, CU_TENSOR_MAP_INTERLEAVE_NONE,
         CU_TENSOR_MAP_SWIZZLE_128B, PROMO, CU_TENSOR_MAP_FLOAT_OOB_FILL_NONE);
  CUtensorMap omap;
  const cuuint64_t odims[5] = {2 * CH, IMG_W / 8, 2, 2, IMG_H};
  const cuuint64_t ostrides[4] = {8 * CH * 2, 4 * CH * 2, 2 * CH * 2, IMG_W * CH * 2};
  const cuuint32_t obox[5] = {2 * CH, 16, 2, 1, 1};
  encode(&omap, CU_TENSOR_MAP_DATA_TYPE_BFLOAT16, 5, d_out, odims, ostrides, obox, estr, CU_TENSOR_MAP_INTERLEAVE_NONE,
         CU_TENSOR_MAP_SWIZZLE_NONE, CU_TENSOR_MAP_L2_PROMOTION_NONE, CU_TENSOR_MAP_FLOAT_OOB_FILL_NONE);
  dilated_conv_wino_kernel<<<2 * NCL, 384, SMEM_BYTES>>>(xmap, omap, (const __nv_bfloat16*)d_in[0], (const __nv_bfloat16*)d_in[1], (__nv_bfloat16*)d_out);
}
```

```cpp
#include <cuda_runtime.h>
#include <cuda_bf16.h>
#include <cuda.h>
#include <stdint.h>

namespace {

constexpr int IMG_H = 512, IMG_W = 512, CH = 96;
constexpr int NSTAGE = 2;

constexpr int BT_BYTES   = 3072;
constexpr int W_BYTES    = 36 * BT_BYTES;
constexpr int BOX_BYTES  = 68 * 96;
constexpr int OFF_BOXB   = 70 * 128;
constexpr int STAGE_BYTES = 144 * 128;
constexpr int OFF_V      = 72 * 128;
constexpr int WG_IN_BYTES = STAGE_BYTES + 138 * 128;
constexpr int OFF_W      = 0;
constexpr int OFF_IN     = OFF_W + W_BYTES;
constexpr int OFF_X      = OFF_IN + 2 * WG_IN_BYTES;
constexpr int X_BYTES    = 3072;
constexpr int XBUF_BYTES = 4 * X_BYTES;
constexpr int SMEM_BYTES = OFF_X + 4 * XBUF_BYTES;
constexpr int OFF_ROW0_0 = OFF_X + ((OFF_IN - OFF_X) & 1023);
constexpr int OFF_ROW0_1 = OFF_X + 2 * XBUF_BYTES + ((OFF_IN + WG_IN_BYTES - OFF_X) & 1023);
constexpr int OFF_BAR    = OFF_IN + 138 * 128;
constexpr int BAR_FULL = 0, BAR_EMPTY = 4, BAR_STAGED = 8, BAR_XFULL = 12, BAR_W = 28, BAR_ROW0 = 32, BAR_READY = 34;
static_assert(SMEM_BYTES <= 232448, "shared memory");
constexpr uint32_t SMEM_BASE = 1024;
constexpr uint64_t BDESC = (uint64_t)((SMEM_BASE + OFF_W) >> 4) | ((uint64_t)(1536 >> 4) << 16) | ((uint64_t)(128 >> 4) << 32);

__device__ __forceinline__ void wg_fence()  { asm volatile("wgmma.fence.sync.aligned;" ::: "memory"); }
__device__ __forceinline__ void wg_commit() { asm volatile("wgmma.commit_group.sync.aligned;" ::: "memory"); }
template <int N> __device__ __forceinline__ void wg_wait() { asm volatile("wgmma.wait_group.sync.aligned %0;" ::"n"(N) : "memory"); }

template <int SCALE_D>
__device__ __forceinline__ void wgmma96(float (&d)[48], const uint32_t (&a)[4], uint64_t DESC) {
  asm volatile(
      "{\n.reg .pred p;\nsetp.ne.b32 p, %53, 0;\n"
      "wgmma.mma_async.sync.aligned.m64n96k16.f32.bf16.bf16 "
      "{%0,%1,%2,%3,%4,%5,%6,%7,%8,%9,%10,%11,%12,%13,%14,%15,%16,%17,%18,%19,%20,%21,%22,%23,"
      "%24,%25,%26,%27,%28,%29,%30,%31,%32,%33,%34,%35,%36,%37,%38,%39,%40,%41,%42,%43,%44,%45,%46,%47}, "
      "{%48,%49,%50,%51}, %52, p, 1, 1, 1;\n}\n"
      : "+f"(d[0]), "+f"(d[1]), "+f"(d[2]), "+f"(d[3]), "+f"(d[4]), "+f"(d[5]), "+f"(d[6]), "+f"(d[7]),
        "+f"(d[8]), "+f"(d[9]), "+f"(d[10]), "+f"(d[11]), "+f"(d[12]), "+f"(d[13]), "+f"(d[14]), "+f"(d[15]),
        "+f"(d[16]), "+f"(d[17]), "+f"(d[18]), "+f"(d[19]), "+f"(d[20]), "+f"(d[21]), "+f"(d[22]), "+f"(d[23]),
        "+f"(d[24]), "+f"(d[25]), "+f"(d[26]), "+f"(d[27]), "+f"(d[28]), "+f"(d[29]), "+f"(d[30]), "+f"(d[31]),
        "+f"(d[32]), "+f"(d[33]), "+f"(d[34]), "+f"(d[35]), "+f"(d[36]), "+f"(d[37]), "+f"(d[38]), "+f"(d[39]),
        "+f"(d[40]), "+f"(d[41]), "+f"(d[42]), "+f"(d[43]), "+f"(d[44]), "+f"(d[45]), "+f"(d[46]), "+f"(d[47])
      : "r"(a[0]), "r"(a[1]), "r"(a[2]), "r"(a[3]), "l"(DESC), "n"(SCALE_D));
}

__device__ __forceinline__ void ldsm4(uint32_t (&r)[4], uint32_t addr) {
  asm volatile("ldmatrix.sync.aligned.m8n8.x4.shared.b16 {%0,%1,%2,%3}, [%4];"
               : "=r"(r[0]), "=r"(r[1]), "=r"(r[2]), "=r"(r[3]) : "r"(addr) : "memory");
}
__device__ __forceinline__ uint32_t badd(uint32_t a, uint32_t b) {
  uint32_t d; asm volatile("add.rn.bf16x2 %0, %1, %2;" : "=r"(d) : "r"(a), "r"(b)); return d;
}
__device__ __forceinline__ uint32_t bsub(uint32_t a, uint32_t b) {
  uint32_t d; asm volatile("sub.rn.bf16x2 %0, %1, %2;" : "=r"(d) : "r"(a), "r"(b)); return d;
}
__device__ __forceinline__ float bf_lo(uint32_t v) {
  return __uint_as_float(v << 16);
}
__device__ __forceinline__ float bf_hi(uint32_t v) { return __uint_as_float(v & 0xffff0000u); }
__device__ __forceinline__ uint32_t pack2(float lo, float hi) {
  uint32_t d; asm volatile("cvt.rn.bf16x2.f32 %0, %1, %2;" : "=r"(d) : "f"(hi), "f"(lo)); return d;
}

__device__ __forceinline__ void mbar_wait(uint32_t bar, uint32_t parity) {
  asm volatile(
      "{\n.reg .pred p;\n.reg .u32 it;\n"
      "mbarrier.try_wait.parity.shared::cta.b64 p, [%0], %1;\n"
      "@p bra WAIT_DONE;\n"
      "mov.u32 it, 0;\n"
      "WAIT_LOOP:\n"
      ".pragma \"nounroll\";\n"
      "mbarrier.try_wait.parity.shared::cta.b64 p, [%0], %1;\n"
      "@p bra WAIT_DONE;\n"
      "add.u32 it, it, 1;\n"
      "setp.lt.u32 p, it, 4194304;\n"
      "@p bra WAIT_LOOP;\n"
      "trap;\n"
      "WAIT_DONE:\n}\n" ::"r"(bar), "r"(parity) : "memory");
}
__device__ __forceinline__ void mbar_init(uint32_t bar, uint32_t count) {
  asm volatile("mbarrier.init.shared::cta.b64 [%0], %1;" ::"r"(bar), "r"(count) : "memory");
}
__device__ __forceinline__ void mbar_arrive(uint32_t bar) {
  asm volatile("mbarrier.arrive.shared::cta.b64 _, [%0];" ::"r"(bar) : "memory");
}
__device__ __forceinline__ void mbar_expect_tx(uint32_t bar, uint32_t bytes) {
  asm volatile("mbarrier.arrive.expect_tx.shared::cta.b64 _, [%0], %1;" ::"r"(bar), "r"(bytes) : "memory");
}
__device__ __forceinline__ void tma_load5(uint32_t dst, const CUtensorMap* map, uint32_t bar, int c0, int c1, int c2, int c3, int c4) {
  asm volatile("cp.async.bulk.tensor.5d.shared::cluster.global.mbarrier::complete_tx::bytes [%0], [%1, {%3,%4,%5,%6,%7}], [%2];"
               ::"r"(dst), "l"(map), "r"(bar), "r"(c0), "r"(c1), "r"(c2), "r"(c3), "r"(c4) : "memory");
}
__device__ __forceinline__ void bulk_load(uint32_t dst, const void* src, uint32_t bytes, uint32_t bar) {
  asm volatile("cp.async.bulk.shared::cluster.global.mbarrier::complete_tx::bytes [%0], [%1], %2, [%3];"
               ::"r"(dst), "l"(src), "r"(bytes), "r"(bar) : "memory");
}
template <int OFF>
__device__ __forceinline__ void st_async4(uint32_t cluster_addr, uint32_t cluster_bar, uint32_t a, uint32_t b, uint32_t c, uint32_t d) {
  asm volatile("st.async.shared::cluster.mbarrier::complete_tx::bytes.v4.b32 [%0+%6], {%2,%3,%4,%5}, [%1];"
               ::"r"(cluster_addr), "r"(cluster_bar), "r"(a), "r"(b), "r"(c), "r"(d), "n"(OFF) : "memory");
}
__device__ __forceinline__ void stsm4(uint32_t addr, uint32_t a, uint32_t b, uint32_t c, uint32_t d) {
  asm volatile("stmatrix.sync.aligned.m8n8.x4.shared.b16 [%0], {%1,%2,%3,%4};" ::"r"(addr), "r"(a), "r"(b), "r"(c), "r"(d) : "memory");
}
__device__ __forceinline__ void lds4(uint32_t (&r)[4], uint32_t addr) {
  asm volatile("ld.shared.v4.b32 {%0,%1,%2,%3}, [%4];" : "=r"(r[0]), "=r"(r[1]), "=r"(r[2]), "=r"(r[3]) : "r"(addr) : "memory");
}
__device__ __forceinline__ void sts4(uint32_t addr, const uint32_t (&r)[4]) {
  asm volatile("st.shared.v4.b32 [%0], {%1,%2,%3,%4};" ::"r"(addr), "r"(r[0]), "r"(r[1]), "r"(r[2]), "r"(r[3]) : "memory");
}
__device__ __forceinline__ void tma_store5(const CUtensorMap* map, uint32_t src, int c0, int c1, int c2, int c3, int c4) {
  asm volatile("cp.async.bulk.tensor.5d.global.shared::cta.bulk_group [%0, {%2,%3,%4,%5,%6}], [%1];"
               ::"l"(map), "r"(src), "r"(c0), "r"(c1), "r"(c2), "r"(c3), "r"(c4) : "memory");
  asm volatile("cp.async.bulk.commit_group;" ::: "memory");
}
__device__ __forceinline__ bool elect_one() {
  uint32_t p;
  asm volatile("{\n.reg .pred P;\nelect.sync _|P, 0xffffffff;\nselp.u32 %0, 1, 0, P;\n}\n" : "=r"(p));
  return p;
}
__device__ __forceinline__ uint32_t mapa(uint32_t addr, uint32_t rank) {
  uint32_t r; asm("mapa.shared::cluster.u32 %0, %1, %2;" : "=r"(r) : "r"(addr), "r"(rank)); return r;
}

__device__ __forceinline__ void tr_sum(uint32_t (&t)[3][4], const uint32_t (&U)[3][4], const uint32_t (&V)[3][4]) {
#pragma unroll
  for (int k = 0; k < 3; k++)
#pragma unroll
    for (int i = 0; i < 4; i++) t[k][i] = badd(U[k][i], V[k][i]);
}
__device__ __forceinline__ void tr_dif(uint32_t (&t)[3][4], const uint32_t (&U)[3][4], const uint32_t (&V)[3][4]) {
#pragma unroll
  for (int k = 0; k < 3; k++)
#pragma unroll
    for (int i = 0; i < 4; i++) t[k][i] = bsub(V[k][i], U[k][i]);
}
__device__ __forceinline__ void tr_t0(uint32_t (&t)[3][4], const uint32_t (&V)[3][4], const uint32_t (&E)[3][4]) {
#pragma unroll
  for (int k = 0; k < 3; k++) {
    t[k][0] = bsub(E[k][0], V[k][0]); t[k][1] = bsub(V[k][0], V[k][1]);
    t[k][2] = bsub(E[k][2], V[k][2]); t[k][3] = bsub(V[k][2], V[k][3]);
  }
}
__device__ __forceinline__ void tr_t3(uint32_t (&t)[3][4], const uint32_t (&U)[3][4], const uint32_t (&E)[3][4]) {
#pragma unroll
  for (int k = 0; k < 3; k++) {
    t[k][0] = bsub(U[k][1], U[k][0]); t[k][1] = bsub(E[k][1], U[k][1]);
    t[k][2] = bsub(U[k][3], U[k][2]); t[k][3] = bsub(E[k][3], U[k][3]);
  }
}
__device__ __forceinline__ void ld3(uint32_t (&R)[3][4], uint32_t aU, int off) {
#pragma unroll
  for (int k = 0; k < 3; k++) ldsm4(R[k], (aU ^ (32 * k)) + off);
}
template <int COMP, int AGE, int FIRST>
__device__ __forceinline__ void batch_(float (&acc)[48], const uint32_t (&t)[3][4], uint64_t bd) {
  constexpr int base = ((COMP * 3 + AGE) * 3) * BT_BYTES;
  wgmma96<FIRST ? 0 : 1>(acc, t[0], bd + ((base) >> 4));
  wgmma96<1>(acc, t[1], bd + ((base + BT_BYTES) >> 4));
  wgmma96<1>(acc, t[2], bd + ((base + 2 * BT_BYTES) >> 4));
  wg_commit();
}

template <int RANK, int I0, int I1>
__device__ __forceinline__ void butterfly(float (&X)[48], float (&Y)[48]) {
#pragma unroll
  for (int i = I0; i < I1; i++) {
    if (RANK == 0) asm volatile("sub.rn.f32 %0, %0, %1;\nfma.rn.f32 %1, %1, 0f40000000, %0;" : "+f"(X[i]), "+f"(Y[i]));
    else           asm volatile("add.rn.f32 %0, %0, %1;\nfma.rn.f32 %1, %1, 0fC0000000, %0;" : "+f"(X[i]), "+f"(Y[i]));
  }
}

struct Ctx {
  uint32_t aU, aE;
  uint32_t bar_full;
  uint32_t bar_ready;
  uint32_t xaddr, xfull;
  char* out;
  int wg, warp;
  uint32_t sig;
  int u0, h0, hstep;
  int nrows;
  uint32_t zero;
};

template <int BUF, int C0, int C1>
__device__ __forceinline__ void load_partner(const Ctx& c, uint32_t (&P)[6][4]) {
#pragma unroll
  for (int ch = C0; ch < C1; ch++) lds4(P[ch], c.xaddr + BUF * XBUF_BYTES + (ch & 1) * 6144 + (ch >> 1) * 64);
}
template <int RANK, int BUF, int CH0>
__device__ __forceinline__ void send_chunk(const Ctx& c, const float (&X)[48]) {
  constexpr uint32_t RDELTA = RANK ? 0xFF000000u : 0x01000000u;
  constexpr int m = CH0 >> 1, s = CH0 & 1;
  uint32_t o[4];
#pragma unroll
  for (int ss = 0; ss < 4; ss++) o[ss] = pack2(X[16 * m + 4 * ss + 2 * s], X[16 * m + 4 * ss + 2 * s + 1]);
  st_async4<BUF * XBUF_BYTES + s * 6144 + m * 64>(c.xaddr + RDELTA, c.xfull + BUF * 64 + RDELTA, o[0], o[1], o[2], o[3]);
}

constexpr int PF_START = 1;
constexpr uint32_t WITEMS0 = 0x404001u, WITEMS1 = 0x110d05u, WITEMS2 = 0x404009u;
constexpr uint32_t FIRST_ROWS = 0x642501u, FIRST_ROWS_BORDER = 0x6521u;

struct Regs {
  float X[48], Y[48];
  uint32_t T[4][2][3][4];
  uint32_t U[3][4], V[3][4], E[3][4];
  uint32_t Z[6][4], P[6][4];
};

__device__ __forceinline__ void warp_done(uint32_t bar) {
  asm volatile("fence.proxy.async.shared::cta;" ::: "memory");
  __syncwarp();
  asm volatile("{\n.reg .pred q;\nelect.sync _|q, 0xffffffff;\n@q mbarrier.arrive.shared::cta.b64 _, [%0];\n}\n" ::"r"(bar) : "memory");
}
__device__ __forceinline__ void warp_release(uint32_t bar, uint32_t a, uint32_t b, uint32_t c, uint32_t d, uint32_t zero) {
  asm volatile("{\n.reg .pred q;\n.reg .b32 t;\nlop3.b32 t, %1, %4, %5, 0x80;\nlop3.b32 t, t, %2, %3, 0x80;\nor.b32 t, t, 1;\n"
               "elect.sync _|q, 0xffffffff;\n@q mbarrier.arrive.shared::cta.b64 _, [%0], t;\n}\n"
               ::"r"(bar), "r"(a), "r"(b), "r"(c), "r"(d), "r"(zero) : "memory");
}
__device__ __forceinline__ void warp_arrive_if(uint32_t bar, int on) {
  asm volatile("{\n.reg .pred p, q;\nelect.sync _|q, 0xffffffff;\nsetp.ne.and.s32 p, %1, 0, q;\n@p mbarrier.arrive.shared::cta.b64 _, [%0];\n}\n"
               ::"r"(bar), "r"(on) : "memory");
}
template <int C0, int C1>
__device__ __forceinline__ void pack_acc(uint32_t (&Z)[6][4], const float (&Y)[48]) {
#pragma unroll
  for (int ch = C0; ch < C1; ch++)
#pragma unroll
    for (int ss = 0; ss < 4; ss++) {
      const int i = 16 * (ch >> 1) + 4 * ss + 2 * (ch & 1);
      Z[ch][ss] = pack2(Y[i], Y[i + 1]);
    }
}
template <int BUF, int C0, int C1>
__device__ __forceinline__ void add_stage(const Ctx& c, uint32_t (&Z)[6][4], const uint32_t (&P)[6][4]) {
#pragma unroll
  for (int ch = C0; ch < C1; ch++)
#pragma unroll
    for (int ss = 0; ss < 4; ss++) Z[ch][ss] = badd(Z[ch][ss], P[ch][ss]);
#pragma unroll
  for (int ch = C0; ch < C1; ch++) sts4(c.xaddr + BUF * XBUF_BYTES + (ch & 1) * 6144 + (ch >> 1) * 64, Z[ch]);
}

__device__ __forceinline__ uint64_t get_bd(int n) { return BDESC + (uint64_t)(uint32_t)(n >> 8); }

#define G1  batch_<0, 0, 1>(r.X, r.T[0][OLD], bd);
#define G2  batch_<0, 1, 0>(r.X, r.T[0][MID], bd);
#define G3  batch_<0, 2, 0>(r.X, r.T[0][OLD], bd);
#define G4  batch_<1, 0, 1>(r.Y, r.T[1][OLD], bd);
#define G5  batch_<1, 1, 0>(r.Y, r.T[1][MID], bd);
#define G6  batch_<1, 2, 0>(r.Y, r.T[1][OLD], bd);
#define G7  if (OLD == 1) batch_<2, 0, 0>(r.X, r.T[2][OLD], bd); else { if (!skip) { F batch_<2, 0, 0>(r.X, r.T[2][OLD], bd); } else { F wg_commit(); } F }
#define G8  batch_<2, 1, 0>(r.X, r.T[2][MID], bd);
#define G9  batch_<2, 2, 0>(r.X, r.T[2][OLD], bd);
#define G10 if (OLD == 1) batch_<3, 0, 0>(r.Y, r.T[3][OLD], bd); else { if (!skip) { F batch_<3, 0, 0>(r.Y, r.T[3][OLD], bd); } else { F wg_commit(); } F }
#define G11 batch_<3, 1, 0>(r.Y, r.T[3][MID], bd);
#define G12 batch_<3, 2, 0>(r.Y, r.T[3][OLD], bd);
#define F   wg_fence();
#define W(k) wg_wait<k>();
#define PK(a, b) pack_acc<a, b>(r.Z, r.Y);
#define XW  mbar_wait(c.xfull + MID * 64, ((n - 1) >> 1) & 1); FIX3
#define LP(a, b) load_partner<MID, a, b>(c, r.P);
#define AS(a, b) add_stage<MID, a, b>(c, r.Z, r.P);
#define LV1 if (RANK == 0) ld3(r.V, c.aU, OLD * STAGE_BYTES + OFF_V); else ld3(r.U, c.aU, OLD * STAGE_BYTES);
#define LU1 if (RANK == 0) ld3(r.U, c.aU, OLD * STAGE_BYTES); else ld3(r.V, c.aU, OLD * STAGE_BYTES + OFF_V);
#define LEk(k)  ldsm4(r.E[k], (c.aE ^ (32 * k)) + OLD * STAGE_BYTES);
#define LV1k(k) if (RANK == 0) ldsm4(r.V[k], (c.aU ^ (32 * k)) + OLD * STAGE_BYTES + OFF_V); else ldsm4(r.U[k], (c.aU ^ (32 * k)) + OLD * STAGE_BYTES);
#define LV2k(k) if (RANK == 0) ldsm4(r.V[k], (c.aU ^ (32 * k)) + MID * STAGE_BYTES + OFF_V); else ldsm4(r.U[k], (c.aU ^ (32 * k)) + MID * STAGE_BYTES);
#define LU1k(k) if (RANK == 0) ldsm4(r.U[k], (c.aU ^ (32 * k)) + OLD * STAGE_BYTES); else ldsm4(r.V[k], (c.aU ^ (32 * k)) + OLD * STAGE_BYTES + OFF_V);
#define LU2k(k) if (RANK == 0) ldsm4(r.U[k], (c.aU ^ (32 * k)) + MID * STAGE_BYTES); else ldsm4(r.V[k], (c.aU ^ (32 * k)) + MID * STAGE_BYTES + OFF_V);
#define TRS tr_sum(r.T[0][OLD], r.U, r.V);
#define TRF tr_dif(r.T[1][OLD], r.U, r.V);
#define TRC if (RANK == 0) tr_t3(r.T[2][OLD], r.U, r.E); else tr_t0(r.T[2][OLD], r.V, r.E);
#define TRD if (RANK == 0) tr_t0(r.T[3][OLD], r.V, r.E); else tr_t3(r.T[3][OLD], r.U, r.E);
#define SIG warp_arrive_if(c.sig + 64 * (OLD ? c.wg : 1 - c.wg), OLD ? 1 : n | c.wg);
#define FEN asm volatile("fence.proxy.async.shared::cta;" ::: "memory");
#define DONE __syncwarp(); warp_arrive_if(c.bar_full + 8 * (BAR_STAGED - BAR_FULL + MID), 1);
#define EMP warp_release(c.bar_full + 8 * (BAR_EMPTY - BAR_FULL + OLD), r.E[0][RANK], r.E[1][RANK], r.E[2][RANK], __float_as_uint(r.Y[47]), c.zero);
#define FW  if (OLD == 1) mbar_wait(c.bar_full, ((n + 2) >> 1) & 1); \
            else mbar_wait(n ? c.bar_full + 8 : c.bar_ready, n ? ((n + 3) >> 1) & 1 : 0);
#define FIX3 if (OLD == 1 && n == 1) { mbar_wait(c.bar_full + 8, 1); SCHED_FIX3 }
#define SND(k) send_chunk<RANK, OLD, k>(c, r.X);
#define SCHED1 LV1k(0) LU1k(2) F G1 XW LP(0,1) LP(1,2) LP(2,3) W(1) PK(0,1) LP(3,4) LP(4,5) PK(1,2) LP(5,6) AS(0,1) PK(2,3) AS(1,2) AS(2,3) PK(3,4) F G2 LV1k(1) PK(4,5) LV1k(2) AS(3,4) PK(5,6) AS(4,5) W(1) TRS AS(5,6) F G4 LEk(0) F G5 W(1) TRF SIG F G3 LEk(1) F G6 LEk(2)
#define SCHED1_FIRST SIG LEk(0) LEk(1) LEk(2)
#define SCHED_FIX3 LU1k(0) LU1k(1) LU1k(2) LV1k(0)
#define SCHED2 F G7 EMP F G8 W(1) TRC F G9 FW W(0) SND(0) F G10 SND(1) F G11 SND(2) SND(3) FEN LU2k(0) DONE SND(4) W(1) TRD LU2k(1) SND(5) F G12

template <int RANK, int OLD, bool FIRST>
__device__ __forceinline__ void phase1(const Ctx& c, int n, Regs& r) {
  constexpr int MID = 1 - OLD;
  const uint64_t bd = get_bd(n);
  if (FIRST) {
    mbar_wait(c.bar_full + 8 * OLD, 0);
    LU1 LV1 W(1) TRS F G3 W(1) TRF F G6
    SCHED1_FIRST
  } else {
    SCHED1
  }
}

template <int RANK, int OLD>
__device__ __forceinline__ void phase2(const Ctx& c, int n, Regs& r) {
  constexpr int MID = 1 - OLD;
  const uint64_t bd = get_bd(n);
  wg_wait<0>();
  butterfly<RANK, 0, 48>(r.X, r.Y);
  const bool skip = (unsigned)(c.h0 + n * c.hstep) >= (unsigned)IMG_H;
  SCHED2
}

template <int RANK>
__device__ __forceinline__ void finish_strip(const Ctx& c, Regs& r, int buf) {
  warp_arrive_if(c.sig + 64 * (buf ^ c.wg), 1);
  wg_wait<0>();
  pack_acc<0, 6>(r.Z, r.Y);
  const int lane = threadIdx.x & 31, g = lane >> 2;
  const int px = 8 * (c.u0 + 4 * c.warp + (g >> 1)) + (g & 1) + 2 * RANK;
  char* o = c.out + ((size_t)(c.h0 + c.nrows * c.hstep) * IMG_W + px) * (CH * 2) + (lane & 3) * 16;
  mbar_wait(c.xfull + buf * 64, ((c.nrows - 1) >> 1) & 1);
#pragma unroll
  for (int ch = 0; ch < 6; ch++) lds4(r.P[ch], c.xaddr + buf * XBUF_BYTES + (ch & 1) * 6144 + (ch >> 1) * 64);
#pragma unroll
  for (int ch = 0; ch < 6; ch++)
    asm volatile("st.global.v4.b32 [%0], {%1,%2,%3,%4};" ::"l"(o + (ch & 1) * (4 * CH * 2) + (ch >> 1) * 64), "r"(badd(r.Z[ch][0], r.P[ch][0])),
                 "r"(badd(r.Z[ch][1], r.P[ch][1])), "r"(badd(r.Z[ch][2], r.P[ch][2])), "r"(badd(r.Z[ch][3], r.P[ch][3])) : "memory");
}

__device__ __forceinline__ void transform_weights(uint32_t sbase, int rank, uint32_t items, int lane) {
  const uint32_t bar_w = sbase + OFF_BAR + 8 * BAR_W;
  const uint32_t o_w0 = (rank ? 2 : 3) * 9 * BT_BYTES, o_w2 = (rank ? 3 : 2) * 9 * BT_BYTES;
#pragma unroll 1
  for (; items; items >>= 8) {
    const int item = (items & 255) - 1;
    if (item >= 18) break;
    const uint32_t base = sbase + OFF_W + item * 1536;
    mbar_wait(bar_w + 8 * (item / 6), 0);
    uint32_t wa[3][4], wb[3][4], wd[3][4];
    const uint32_t src = base + (lane >> 2) * 192 + (lane & 3) * 16;
#pragma unroll
    for (int m = 0; m < 3; m++) lds4(wa[m], src + o_w0 + m * 64);
#pragma unroll
    for (int m = 0; m < 3; m++) lds4(wd[m], src + o_w2 + m * 64);
#pragma unroll
    for (int m = 0; m < 3; m++) lds4(wb[m], src + m * 64);
    __syncwarp();
    const uint32_t dst = base + lane * 16;
#pragma unroll
    for (int m = 0; m < 3; m++) stsm4(dst + m * 512 + o_w0, wa[m][0], wa[m][1], wa[m][2], wa[m][3]);
#pragma unroll
    for (int m = 0; m < 3; m++) stsm4(dst + m * 512 + o_w2, wd[m][0], wd[m][1], wd[m][2], wd[m][3]);
#pragma unroll
    for (int m = 0; m < 3; m++) {
      uint32_t g1[4], g2[4];
#pragma unroll
      for (int ss = 0; ss < 4; ss++) {
        const uint32_t a = wa[m][ss], b = wb[m][ss], d = wd[m][ss];
        const float slo = 0.5f * (bf_lo(a) + bf_lo(d)), shi = 0.5f * (bf_hi(a) + bf_hi(d));
        const float blo = bf_lo(b), bhi = bf_hi(b);
        g1[ss] = pack2(fmaf(blo, 0.5f, slo), fmaf(bhi, 0.5f, shi));
        g2[ss] = pack2(fmaf(blo, -0.5f, slo), fmaf(bhi, -0.5f, shi));
      }
      stsm4(dst + m * 512, g1[0], g1[1], g1[2], g1[3]);
      stsm4(dst + m * 512 + 9 * BT_BYTES, g2[0], g2[1], g2[2], g2[3]);
    }
  }
  asm volatile("fence.proxy.async.shared::cta;" ::: "memory");
  __syncwarp();
  if (elect_one()) mbar_arrive(bar_w + 24);
  __syncwarp();
}

template <int RANK>
__device__ __forceinline__ void run_strip(const Ctx& c, uint32_t row0_off, uint32_t bar_row0) {
  Regs r;
#pragma unroll
  for (int i = 0; i < 48; i++) { r.X[i] = 0.f; r.Y[i] = 0.f; r.Z[i % 6][i / 12] = 0; r.P[i % 6][i / 12] = 0; }
#pragma unroll
  for (int m = 1; m >= 0; m--) {
    const uint32_t off = m ? STAGE_BYTES : row0_off;
    mbar_wait(m ? c.bar_full + 8 : bar_row0, 0);
    if (m == 0 && (unsigned)c.h0 >= (unsigned)IMG_H) {
#pragma unroll
      for (int i = 0; i < 48; i++) asm volatile("" : "=r"(r.T[i / 12][0][(i / 4) % 3][i % 4]));
      continue;
    }
    ld3(r.U, c.aU, off);
    ld3(r.V, c.aU, off + OFF_V);
    ld3(r.E, c.aE, off);
    tr_sum(r.T[0][m], r.U, r.V);
    tr_dif(r.T[1][m], r.U, r.V);
    if (m) mbar_wait(SMEM_BASE + (RANK << 24) + OFF_BAR + 8 * BAR_W + 24, 0);
    wg_fence();
    if (m) { batch_<0, 1, 1>(r.X, r.T[0][1], BDESC); batch_<1, 1, 1>(r.Y, r.T[1][1], BDESC); }
    else   { batch_<0, 0, 0>(r.X, r.T[0][0], BDESC); batch_<1, 0, 0>(r.Y, r.T[1][0], BDESC); }
    tr_t3(r.T[RANK == 0 ? 2 : 3][m], r.U, r.E);
    tr_t0(r.T[RANK == 0 ? 3 : 2][m], r.V, r.E);
  }
  warp_done(c.bar_full + 8 * (BAR_EMPTY - BAR_FULL + 1));
  phase1<RANK, 0, true>(c, 0, r);
#pragma unroll 1
  for (int n = 0;; n += 2) {
    phase2<RANK, 0>(c, n, r);
    if (n + 1 == c.nrows) break;
    phase1<RANK, 1, false>(c, n + 1, r);
    phase2<RANK, 1>(c, n + 1, r);
    if (n + 2 == c.nrows) break;
    phase1<RANK, 0, false>(c, n + 2, r);
  }
  finish_strip<RANK>(c, r, (c.nrows - 1) & 1);
}

constexpr int NCL = 66;
struct Strip { int seg, h0, nrows; };
__device__ __forceinline__ bool is_down(int cl) { return cl < 2 || !((cl - 2) & 4); }
__device__ __forceinline__ Strip get_strip(int cl, int wg) {
  const int k = cl - 2, i = k >> 2;
  const int q = (i & 1) ? (wg ? 16 + 15 * i : 16 * i + 16) : (wg ? 30 + 15 * i : 16 * i - 1);
  return cl < 2 ? Strip{2 * cl + wg, -1, 16} : Strip{k & 3, 2 * q + wg, 16 - wg};
}

__device__ __forceinline__ void load_rows(const CUtensorMap* xmap, const char* x, uint32_t sbase, int rank, int wg, Strip sp, int hstep) {
  const uint32_t full = sbase + OFF_BAR + 8 * (BAR_FULL + 2 * wg), empty = full + 8 * (BAR_EMPTY - BAR_FULL);
  const uint32_t in_base = sbase + OFF_IN + wg * WG_IN_BYTES;
  const int halo = sp.seg != 3 * rank ? 6 : 0;
  const char* xseg = x + (sp.seg * 128 + (rank ? 64 : -halo)) * (CH * 2);
  const int pf_bytes = (64 + halo) * CH * 2;
#pragma unroll 1
  for (int m = 3; m <= sp.nrows + 2; m++) {
    const int s = m & 1, h = sp.h0 + m * hstep;
    mbar_wait(empty + 8 * s, ((m - 3) >> 1) & 1);
    if (m == 3) {
      asm volatile("mbarrier.arrive.shared::cluster.b64 _, [%0];" ::"r"((sbase + OFF_BAR + 8 * (BAR_READY + wg)) ^ 0x01000000u) : "memory");
    }
    if (m <= 4) mbar_arrive(full + 8 * s);
    if (m < sp.nrows + 2) {
      const int hp = h + hstep;
      const bool pf = m >= 4 + PF_START && m + 1 < sp.nrows + 2 && (unsigned)hp < (unsigned)IMG_H;
      mbar_expect_tx(full + 8 * s, 2 * BOX_BYTES);
      tma_load5(in_base + s * STAGE_BYTES, xmap, full + 8 * s, rank * 48, 0, sp.seg * 16, 0, h);
      tma_load5(in_base + s * STAGE_BYTES + OFF_BOXB, xmap, full + 8 * s, rank * 48, 2, sp.seg * 16 - 1, 0, h);
      if (pf) asm volatile("cp.async.bulk.prefetch.L2.global [%0], %1;" ::"l"(xseg + (size_t)hp * (IMG_W * CH * 2)), "r"(pf_bytes) : "memory");
    } else {
      mbar_arrive(full + 8 * s);
    }
  }
}
__device__ __forceinline__ void store_rows(const CUtensorMap* omap, uint32_t sbase, int rank, int wg, Strip sp, int hstep) {
  const uint32_t full = sbase + OFF_BAR + 8 * (BAR_FULL + 2 * wg), staged = full + 8 * (BAR_STAGED - BAR_FULL);
  const uint32_t xfull = sbase + OFF_BAR + 8 * (BAR_XFULL + 4 * wg);
#pragma unroll 1
  for (int n = 0; n < sp.nrows - 1; n++) {
    const int b = n & 1;
    mbar_wait(staged + 8 * b, ((n + 1) >> 1) & 1);
    tma_store5(omap, sbase + OFF_X + (2 * wg + b) * XBUF_BYTES, 0, sp.seg * 16, 0, rank, sp.h0 + (n + 1) * hstep);
#pragma unroll
    for (int q = 0; q < 4; q++) mbar_expect_tx(xfull + 64 * b + 8 * q, X_BYTES);
    asm volatile("cp.async.bulk.wait_group.read 0;" ::: "memory");
    if (n == 0) mbar_wait(xfull + 64, 0);
    if (n + 2 < sp.nrows) asm volatile("mbarrier.arrive.shared::cluster.b64 _, [%0];" ::"r"((full + 8 * (b ^ 1)) ^ 0x01000000u) : "memory");
  }
}

__global__ void __cluster_dims__(2, 1, 1) __launch_bounds__(384, 1)
dilated_conv_wino_kernel(const __grid_constant__ CUtensorMap xmap, const __grid_constant__ CUtensorMap omap,
                         const __nv_bfloat16* __restrict__ x, const __nv_bfloat16* __restrict__ w, __nv_bfloat16* __restrict__ out,
                         uint32_t zero) {
  extern __shared__ uint8_t smem_raw[];
  const int tid = threadIdx.x;
  const int w12 = __shfl_sync(0xffffffff, tid >> 5, 0);
  const int wg = w12 >> 2, warp = w12 & 3;
  const int lane = tid & 31;
  const int rank = blockIdx.x & 1;
  const int cl = blockIdx.x >> 1;
  const bool down = is_down(cl);
  const uint32_t sbase = SMEM_BASE + (rank << 24);
  const uint32_t b0 = sbase + OFF_BAR;
  const uint32_t bar_w = b0 + 8 * BAR_W;

  if (w12 >= 9) {
    if (elect_one()) {
      const int a = w12 - 9, i = down ? a : 2 - a;
      const char* src = reinterpret_cast<const char*>(w) + (uint32_t)((i * 6 + rank) * (3 * BT_BYTES));
      const uint32_t dst = sbase + OFF_W + a * 3 * BT_BYTES;
      mbar_init(bar_w + 8 * a, 1);
      mbar_expect_tx(bar_w + 8 * a, 9 * BT_BYTES);
      bulk_load(dst + (rank ? 2 : 3) * 9 * BT_BYTES, src, 3 * BT_BYTES, bar_w + 8 * a);
      bulk_load(dst, src + 6 * BT_BYTES, 3 * BT_BYTES, bar_w + 8 * a);
      bulk_load(dst + (rank ? 3 : 2) * 9 * BT_BYTES, src + 12 * BT_BYTES, 3 * BT_BYTES, bar_w + 8 * a);
    }
  } else if (elect_one()) {
    if (w12 < 8) {
      const uint32_t xf = b0 + 8 * (BAR_XFULL + w12);
      mbar_init(xf, 2);
      mbar_init(xf + 64, 2);
      if (w12 < 4) {
        mbar_init(b0 + 8 * (BAR_FULL + w12), 2);
        mbar_expect_tx(b0 + 8 * (BAR_FULL + w12), 2 * BOX_BYTES);
        mbar_arrive(b0 + 8 * (BAR_FULL + w12));
      } else {
        mbar_init(b0 + 8 * (BAR_EMPTY + warp), 4);
        mbar_init(b0 + 8 * (BAR_STAGED + warp), 4);
      }
      mbar_expect_tx(xf, X_BYTES);
      mbar_expect_tx(xf + 64, X_BYTES);
    } else {
      asm volatile("prefetch.tensormap [%0];" ::"l"(&xmap) : "memory");
#pragma unroll
      for (int q = 0; q < 2; q++) {
        mbar_init(b0 + 8 * (BAR_ROW0 + q), 1);
        mbar_init(b0 + 8 * (BAR_READY + q), 1);
      }
      mbar_init(bar_w + 24, 12);
#pragma unroll
      for (int q = 0; q < 2; q++) mbar_expect_tx(b0 + 8 * (BAR_ROW0 + q), 2 * BOX_BYTES);
    }
    asm volatile("fence.mbarrier_init.release.cluster;" ::: "memory");
  }
  __syncthreads();
  asm volatile("barrier.cluster.arrive.relaxed.aligned;" ::: "memory");
  const Strip s0 = get_strip(cl, 0), s1 = get_strip(cl, 1);
  const int hstep = down ? 2 : -2;
  if (w12 == 8 || w12 == 9) {
    if (elect_one()) {
#pragma unroll 1
      for (uint32_t order = cl < 2 ? FIRST_ROWS_BORDER : FIRST_ROWS; order; order >>= 4) {
        const int g = (order >> 2) & 1, m = order & 3;
        const uint32_t dst = m == 0 ? sbase + (g ? OFF_ROW0_1 : OFF_ROW0_0) : sbase + OFF_IN + g * WG_IN_BYTES + (m & 1) * STAGE_BYTES;
        const uint32_t bar = b0 + 8 * (m == 0 ? BAR_ROW0 + g : BAR_FULL + 2 * g + (m & 1));
        tma_load5(dst + warp * OFF_BOXB, &xmap, bar, rank * 48, 2 * warp, (g ? s1.seg : s0.seg) * 16 - warp, 0, (g ? s1.h0 : s0.h0) + m * hstep);
      }
      asm volatile("prefetch.tensormap [%0];" ::"l"(&omap) : "memory");
    }
    __syncwarp();
  }
  if ((uint32_t)__cvta_generic_to_shared(smem_raw) != sbase || mapa(sbase, rank ^ 1) != (sbase ^ 0x01000000u)) __trap();
  asm volatile("barrier.cluster.wait.aligned;" ::: "memory");
  transform_weights(sbase, rank, (wg == 0 ? WITEMS0 : wg == 1 ? WITEMS1 : WITEMS2) + warp * 0x010101u, lane);

  if (wg == 2) {
    asm volatile("setmaxnreg.dec.sync.aligned.u32 24;");
    if (elect_one()) {
      if (warp < 2) load_rows(&xmap, reinterpret_cast<const char*>(x), sbase, rank, warp, warp ? s1 : s0, hstep);
      else store_rows(&omap, sbase, rank, warp - 2, warp == 3 ? s1 : s0, hstep);
    }
  } else {
    asm volatile("setmaxnreg.inc.sync.aligned.u32 240;");
    Ctx c;
    c.out = reinterpret_cast<char*>(out);
    c.zero = zero;
    c.wg = wg;
    c.warp = warp;
    c.sig = b0 + 8 * (BAR_XFULL + (w12 ^ 4));
    c.bar_full = b0 + 8 * (BAR_FULL + wg * NSTAGE);
    c.bar_ready = b0 + 8 * (BAR_READY + wg);
    c.u0 = (wg ? s1.seg : s0.seg) * 16;
    c.h0 = wg ? s1.h0 : s0.h0;
    c.hstep = hstep;
    c.nrows = wg ? s1.nrows : s0.nrows;
    c.xfull = b0 + 8 * (BAR_XFULL + w12);
    const uint32_t in_base = sbase + OFF_IN + wg * WG_IN_BYTES;
    {
      const int g = lane & 7, mi = lane >> 3;
      const int rU = 8 * warp + g + ((mi & 1) ? 34 : 0);
      const int rE = 8 * warp + g + ((mi & 1) ? 2 : 70 + 34);
      const uint32_t pU = in_base + rU * 128, pE = in_base + rE * 128;
      c.aU = pU + (((mi >> 1) ^ ((pU >> 7) & 7)) << 4);
      c.aE = pE + (((mi >> 1) ^ ((pE >> 7) & 7)) << 4);
    }
    c.xaddr = sbase + OFF_X + wg * 2 * XBUF_BYTES + (warp * 8 + (lane >> 2)) * 192 + (lane & 3) * 16;
    const uint32_t row0_off = sbase + (wg ? OFF_ROW0_1 : OFF_ROW0_0) - in_base;
    const uint32_t bar_row0 = cl < 2 ? bar_w : b0 + 8 * (BAR_ROW0 + wg);
    if (rank == 0) run_strip<0>(c, row0_off, bar_row0); else run_strip<1>(c, row0_off, bar_row0);
  }
}

typedef CUresult (*EncodeTiledFn)(CUtensorMap*, CUtensorMapDataType, cuuint32_t, void*, const cuuint64_t*, const cuuint64_t*,
                                  const cuuint32_t*, const cuuint32_t*, CUtensorMapInterleave, CUtensorMapSwizzle,
                                  CUtensorMapL2promotion, CUtensorMapFloatOOBfill);

}

extern "C" void kernel_launch(void* const* d_in, const int* in_sizes, int n_in, void* d_out, int out_size) {
  (void)in_sizes; (void)n_in; (void)out_size;
  static EncodeTiledFn encode = nullptr;
  if (!encode) {
    void* fn = nullptr;
    cudaDriverEntryPointQueryResult qr;
    cudaGetDriverEntryPoint("cuTensorMapEncodeTiled", &fn, cudaEnableDefault, &qr);
    encode = (EncodeTiledFn)fn;
    cudaFuncSetAttribute(dilated_conv_wino_kernel, cudaFuncAttributeMaxDynamicSharedMemorySize, SMEM_BYTES);
  }
  CUtensorMap xmap;
  const cuuint64_t dims[5] = {CH, 4, IMG_W / 8, 2, IMG_H};
  const cuuint64_t strides[4] = {CH * 2, 8 * CH * 2, 4 * CH * 2, IMG_W * CH * 2};
  const cuuint32_t box[5] = {48, 2, 17, 2, 1};
  const cuuint32_t estr[5] = {1, 1, 1, 1, 1};
  encode(&xmap, CU_TENSOR_MAP_DATA_TYPE_BFLOAT16, 5, d_in[0], dims, strides, box, estr, CU_TENSOR_MAP_INTERLEAVE_NONE,
         CU_TENSOR_MAP_SWIZZLE_128B, CU_TENSOR_MAP_L2_PROMOTION_L2_128B, CU_TENSOR_MAP_FLOAT_OOB_FILL_NONE);
  CUtensorMap omap;
  const cuuint64_t odims[5] = {2 * CH, IMG_W / 8, 2, 2, IMG_H};
  const cuuint64_t ostrides[4] = {8 * CH * 2, 4 * CH * 2, 2 * CH * 2, IMG_W * CH * 2};
  const cuuint32_t obox[5] = {2 * CH, 16, 2, 1, 1};
  encode(&omap, CU_TENSOR_MAP_DATA_TYPE_BFLOAT16, 5, d_out, odims, ostrides, obox, estr, CU_TENSOR_MAP_INTERLEAVE_NONE,
         CU_TENSOR_MAP_SWIZZLE_NONE, CU_TENSOR_MAP_L2_PROMOTION_NONE, CU_TENSOR_MAP_FLOAT_OOB_FILL_NONE);
  dilated_conv_wino_kernel<<<2 * NCL, 384, SMEM_BYTES>>>(xmap, omap, (const __nv_bfloat16*)d_in[0], (const __nv_bfloat16*)d_in[1], (__nv_bfloat16*)d_out, 0u);
}
```

```cpp
#include <cuda_runtime.h>
#include <cuda_bf16.h>
#include <cuda.h>
#include <stdint.h>

namespace {

constexpr int IMG_H = 512, IMG_W = 512, CH = 96;
constexpr int NSTAGE = 2;

constexpr int BT_BYTES   = 3072;
constexpr int W_BYTES    = 36 * BT_BYTES;
constexpr int BOX_BYTES  = 68 * 96;
constexpr int OFF_BOXB   = 70 * 128;
constexpr int STAGE_BYTES = 144 * 128;
constexpr int OFF_V      = 72 * 128;
constexpr int WG_IN_BYTES = STAGE_BYTES + 138 * 128;
constexpr int OFF_W      = 0;
constexpr int OFF_IN     = OFF_W + W_BYTES;
constexpr int OFF_X      = OFF_IN + 2 * WG_IN_BYTES;
constexpr int X_BYTES    = 3072;
constexpr int XBUF_BYTES = 4 * X_BYTES;
constexpr int SMEM_BYTES = OFF_X + 4 * XBUF_BYTES;
constexpr int OFF_ROW0_0 = OFF_X + ((OFF_IN - OFF_X) & 1023);
constexpr int OFF_ROW0_1 = OFF_X + 2 * XBUF_BYTES + ((OFF_IN + WG_IN_BYTES - OFF_X) & 1023);
constexpr int OFF_BAR    = OFF_IN + 138 * 128;
constexpr int BAR_FULL = 0, BAR_EMPTY = 4, BAR_STAGED = 8, BAR_XFULL = 12, BAR_W = 28, BAR_ROW0 = 32, BAR_READY = 34;
static_assert(SMEM_BYTES <= 232448, "shared memory");
constexpr uint32_t SMEM_BASE = 1024;
constexpr uint64_t BDESC = (uint64_t)((SMEM_BASE + OFF_W) >> 4) | ((uint64_t)(1536 >> 4) << 16) | ((uint64_t)(128 >> 4) << 32);

__device__ __forceinline__ void wg_fence()  { asm volatile("wgmma.fence.sync.aligned;" ::: "memory"); }
__device__ __forceinline__ void wg_commit() { asm volatile("wgmma.commit_group.sync.aligned;" ::: "memory"); }
template <int N> __device__ __forceinline__ void wg_wait() { asm volatile("wgmma.wait_group.sync.aligned %0;" ::"n"(N) : "memory"); }

template <int SCALE_D>
__device__ __forceinline__ void wgmma96(float (&d)[48], const uint32_t (&a)[4], uint64_t DESC) {
  asm volatile(
      "{\n.reg .pred p;\nsetp.ne.b32 p, %53, 0;\n"
      "wgmma.mma_async.sync.aligned.m64n96k16.f32.bf16.bf16 "
      "{%0,%1,%2,%3,%4,%5,%6,%7,%8,%9,%10,%11,%12,%13,%14,%15,%16,%17,%18,%19,%20,%21,%22,%23,"
      "%24,%25,%26,%27,%28,%29,%30,%31,%32,%33,%34,%35,%36,%37,%38,%39,%40,%41,%42,%43,%44,%45,%46,%47}, "
      "{%48,%49,%50,%51}, %52, p, 1, 1, 1;\n}\n"
      : "+f"(d[0]), "+f"(d[1]), "+f"(d[2]), "+f"(d[3]), "+f"(d[4]), "+f"(d[5]), "+f"(d[6]), "+f"(d[7]),
        "+f"(d[8]), "+f"(d[9]), "+f"(d[10]), "+f"(d[11]), "+f"(d[12]), "+f"(d[13]), "+f"(d[14]), "+f"(d[15]),
        "+f"(d[16]), "+f"(d[17]), "+f"(d[18]), "+f"(d[19]), "+f"(d[20]), "+f"(d[21]), "+f"(d[22]), "+f"(d[23]),
        "+f"(d[24]), "+f"(d[25]), "+f"(d[26]), "+f"(d[27]), "+f"(d[28]), "+f"(d[29]), "+f"(d[30]), "+f"(d[31]),
        "+f"(d[32]), "+f"(d[33]), "+f"(d[34]), "+f"(d[35]), "+f"(d[36]), "+f"(d[37]), "+f"(d[38]), "+f"(d[39]),
        "+f"(d[40]), "+f"(d[41]), "+f"(d[42]), "+f"(d[43]), "+f"(d[44]), "+f"(d[45]), "+f"(d[46]), "+f"(d[47])
      : "r"(a[0]), "r"(a[1]), "r"(a[2]), "r"(a[3]), "l"(DESC), "n"(SCALE_D));
}

__device__ __forceinline__ void ldsm4(uint32_t (&r)[4], uint32_t addr) {
  asm volatile("ldmatrix.sync.aligned.m8n8.x4.shared.b16 {%0,%1,%2,%3}, [%4];"
               : "=r"(r[0]), "=r"(r[1]), "=r"(r[2]), "=r"(r[3]) : "r"(addr) : "memory");
}
__device__ __forceinline__ uint32_t badd(uint32_t a, uint32_t b) {
  uint32_t d; asm volatile("add.rn.bf16x2 %0, %1, %2;" : "=r"(d) : "r"(a), "r"(b)); return d;
}
__device__ __forceinline__ uint32_t bsub(uint32_t a, uint32_t b) {
  uint32_t d; asm volatile("sub.rn.bf16x2 %0, %1, %2;" : "=r"(d) : "r"(a), "r"(b)); return d;
}
__device__ __forceinline__ float bf_lo(uint32_t v) {
  return __uint_as_float(v << 16);
}
__device__ __forceinline__ float bf_hi(uint32_t v) { return __uint_as_float(v & 0xffff0000u); }
__device__ __forceinline__ uint32_t pack2(float lo, float hi) {
  uint32_t d; asm volatile("cvt.rn.bf16x2.f32 %0, %1, %2;" : "=r"(d) : "f"(hi), "f"(lo)); return d;
}

__device__ __forceinline__ void mbar_wait(uint32_t bar, uint32_t parity) {
  asm volatile(
      "{\n.reg .pred p;\n.reg .u32 it;\n"
      "mbarrier.try_wait.parity.shared::cta.b64 p, [%0], %1;\n"
      "@p bra WAIT_DONE;\n"
      "mov.u32 it, 0;\n"
      "WAIT_LOOP:\n"
      ".pragma \"nounroll\";\n"
      "mbarrier.try_wait.parity.shared::cta.b64 p, [%0], %1;\n"
      "@p bra WAIT_DONE;\n"
      "add.u32 it, it, 1;\n"
      "setp.lt.u32 p, it, 4194304;\n"
      "@p bra WAIT_LOOP;\n"
      "trap;\n"
      "WAIT_DONE:\n}\n" ::"r"(bar), "r"(parity) : "memory");
}
__device__ __forceinline__ void mbar_init(uint32_t bar, uint32_t count) {
  asm volatile("mbarrier.init.shared::cta.b64 [%0], %1;" ::"r"(bar), "r"(count) : "memory");
}
__device__ __forceinline__ void mbar_arrive(uint32_t bar) {
  asm volatile("mbarrier.arrive.shared::cta.b64 _, [%0];" ::"r"(bar) : "memory");
}
__device__ __forceinline__ void mbar_expect_tx(uint32_t bar, uint32_t bytes) {
  asm volatile("mbarrier.arrive.expect_tx.shared::cta.b64 _, [%0], %1;" ::"r"(bar), "r"(bytes) : "memory");
}
__device__ __forceinline__ void tma_load5(uint32_t dst, const CUtensorMap* map, uint32_t bar, int c0, int c1, int c2, int c3, int c4) {
  asm volatile("cp.async.bulk.tensor.5d.shared::cluster.global.mbarrier::complete_tx::bytes [%0], [%1, {%3,%4,%5,%6,%7}], [%2];"
               ::"r"(dst), "l"(map), "r"(bar), "r"(c0), "r"(c1), "r"(c2), "r"(c3), "r"(c4) : "memory");
}
__device__ __forceinline__ void bulk_load(uint32_t dst, const void* src, uint32_t bytes, uint32_t bar) {
  asm volatile("cp.async.bulk.shared::cluster.global.mbarrier::complete_tx::bytes [%0], [%1], %2, [%3];"
               ::"r"(dst), "l"(src), "r"(bytes), "r"(bar) : "memory");
}
template <int OFF>
__device__ __forceinline__ void st_async4(uint32_t cluster_addr, uint32_t cluster_bar, uint32_t a, uint32_t b, uint32_t c, uint32_t d) {
  asm volatile("st.async.shared::cluster.mbarrier::complete_tx::bytes.v4.b32 [%0+%6], {%2,%3,%4,%5}, [%1];"
               ::"r"(cluster_addr), "r"(cluster_bar), "r"(a), "r"(b), "r"(c), "r"(d), "n"(OFF) : "memory");
}
__device__ __forceinline__ void stsm4(uint32_t addr, uint32_t a, uint32_t b, uint32_t c, uint32_t d) {
  asm volatile("stmatrix.sync.aligned.m8n8.x4.shared.b16 [%0], {%1,%2,%3,%4};" ::"r"(addr), "r"(a), "r"(b), "r"(c), "r"(d) : "memory");
}
__device__ __forceinline__ void lds4(uint32_t (&r)[4], uint32_t addr) {
  asm volatile("ld.shared.v4.b32 {%0,%1,%2,%3}, [%4];" : "=r"(r[0]), "=r"(r[1]), "=r"(r[2]), "=r"(r[3]) : "r"(addr) : "memory");
}
__device__ __forceinline__ void sts4(uint32_t addr, const uint32_t (&r)[4]) {
  asm volatile("st.shared.v4.b32 [%0], {%1,%2,%3,%4};" ::"r"(addr), "r"(r[0]), "r"(r[1]), "r"(r[2]), "r"(r[3]) : "memory");
}
__device__ __forceinline__ void tma_store5(const CUtensorMap* map, uint32_t src, int c0, int c1, int c2, int c3, int c4) {
  asm volatile("cp.async.bulk.tensor.5d.global.shared::cta.bulk_group [%0, {%2,%3,%4,%5,%6}], [%1];"
               ::"l"(map), "r"(src), "r"(c0), "r"(c1), "r"(c2), "r"(c3), "r"(c4) : "memory");
  asm volatile("cp.async.bulk.commit_group;" ::: "memory");
}
__device__ __forceinline__ bool elect_one() {
  uint32_t p;
  asm volatile("{\n.reg .pred P;\nelect.sync _|P, 0xffffffff;\nselp.u32 %0, 1, 0, P;\n}\n" : "=r"(p));
  return p;
}
__device__ __forceinline__ uint32_t mapa(uint32_t addr, uint32_t rank) {
  uint32_t r; asm("mapa.shared::cluster.u32 %0, %1, %2;" : "=r"(r) : "r"(addr), "r"(rank)); return r;
}

__device__ __forceinline__ void tr_sum(uint32_t (&t)[3][4], const uint32_t (&U)[3][4], const uint32_t (&V)[3][4]) {
#pragma unroll
  for (int k = 0; k < 3; k++)
#pragma unroll
    for (int i = 0; i < 4; i++) t[k][i] = badd(U[k][i], V[k][i]);
}
__device__ __forceinline__ void tr_dif(uint32_t (&t)[3][4], const uint32_t (&U)[3][4], const uint32_t (&V)[3][4]) {
#pragma unroll
  for (int k = 0; k < 3; k++)
#pragma unroll
    for (int i = 0; i < 4; i++) t[k][i] = bsub(V[k][i], U[k][i]);
}
__device__ __forceinline__ void tr_t0(uint32_t (&t)[3][4], const uint32_t (&V)[3][4], const uint32_t (&E)[3][4]) {
#pragma unroll
  for (int k = 0; k < 3; k++) {
    t[k][0] = bsub(E[k][0], V[k][0]); t[k][1] = bsub(V[k][0], V[k][1]);
    t[k][2] = bsub(E[k][2], V[k][2]); t[k][3] = bsub(V[k][2], V[k][3]);
  }
}
__device__ __forceinline__ void tr_t3(uint32_t (&t)[3][4], const uint32_t (&U)[3][4], const uint32_t (&E)[3][4]) {
#pragma unroll
  for (int k = 0; k < 3; k++) {
    t[k][0] = bsub(U[k][1], U[k][0]); t[k][1] = bsub(E[k][1], U[k][1]);
    t[k][2] = bsub(U[k][3], U[k][2]); t[k][3] = bsub(E[k][3], U[k][3]);
  }
}
__device__ __forceinline__ void ld3(uint32_t (&R)[3][4], uint32_t aU, int off) {
#pragma unroll
  for (int k = 0; k < 3; k++) ldsm4(R[k], (aU ^ (32 * k)) + off);
}
template <int COMP, int AGE, int FIRST>
__device__ __forceinline__ void batch_(float (&acc)[48], const uint32_t (&t)[3][4], uint64_t bd) {
  constexpr int base = ((COMP * 3 + AGE) * 3) * BT_BYTES;
  wgmma96<FIRST ? 0 : 1>(acc, t[0], bd + ((base) >> 4));
  wgmma96<1>(acc, t[1], bd + ((base + BT_BYTES) >> 4));
  wgmma96<1>(acc, t[2], bd + ((base + 2 * BT_BYTES) >> 4));
  wg_commit();
}

template <int RANK, int I0, int I1>
__device__ __forceinline__ void butterfly(float (&X)[48], float (&Y)[48]) {
#pragma unroll
  for (int i = I0; i < I1; i++) {
    if (RANK == 0) asm volatile("sub.rn.f32 %0, %0, %1;\nfma.rn.f32 %1, %1, 0f40000000, %0;" : "+f"(X[i]), "+f"(Y[i]));
    else           asm volatile("add.rn.f32 %0, %0, %1;\nfma.rn.f32 %1, %1, 0fC0000000, %0;" : "+f"(X[i]), "+f"(Y[i]));
  }
}

struct Ctx {
  uint32_t aU, aE;
  uint32_t bar_full;
  uint32_t bar_ready;
  uint32_t xaddr, xfull;
  char* out;
  int wg, warp;
  uint32_t sig;
  int u0, h0, hstep;
  int nrows;
  uint32_t zero;
};

template <int BUF, int C0, int C1>
__device__ __forceinline__ void load_partner(const Ctx& c, uint32_t (&P)[6][4]) {
#pragma unroll
  for (int ch = C0; ch < C1; ch++) lds4(P[ch], c.xaddr + BUF * XBUF_BYTES + (ch & 1) * 6144 + (ch >> 1) * 64);
}
template <int RANK, int BUF, int CH0>
__device__ __forceinline__ void send_chunk(const Ctx& c, const float (&X)[48]) {
  constexpr uint32_t RDELTA = RANK ? 0xFF000000u : 0x01000000u;
  constexpr int m = CH0 >> 1, s = CH0 & 1;
  uint32_t o[4];
#pragma unroll
  for (int ss = 0; ss < 4; ss++) o[ss] = pack2(X[16 * m + 4 * ss + 2 * s], X[16 * m + 4 * ss + 2 * s + 1]);
  st_async4<BUF * XBUF_BYTES + s * 6144 + m * 64>(c.xaddr + RDELTA, c.xfull + BUF * 64 + RDELTA, o[0], o[1], o[2], o[3]);
}

constexpr int PF_START = 1;
constexpr uint32_t WITEMS0 = 0x404001u, WITEMS1 = 0x110d05u, WITEMS2 = 0x404009u;
constexpr uint32_t FIRST_ROWS = 0x642501u, FIRST_ROWS_BORDER = 0x6521u;

struct Regs {
  float X[48], Y[48];
  uint32_t T[4][2][3][4];
  uint32_t U[3][4], V[3][4], E[3][4];
  uint32_t Z[6][4], P[6][4];
};

__device__ __forceinline__ void warp_done(uint32_t bar) {
  asm volatile("fence.proxy.async.shared::cta;" ::: "memory");
  __syncwarp();
  asm volatile("{\n.reg .pred q;\nelect.sync _|q, 0xffffffff;\n@q mbarrier.arrive.shared::cta.b64 _, [%0];\n}\n" ::"r"(bar) : "memory");
}
__device__ __forceinline__ void warp_release(uint32_t bar, uint32_t a, uint32_t b, uint32_t c, uint32_t d, uint32_t zero) {
  asm volatile("{\n.reg .pred q;\n.reg .b32 t;\nlop3.b32 t, %1, %4, %5, 0x80;\nlop3.b32 t, t, %2, %3, 0x80;\nor.b32 t, t, 1;\n"
               "elect.sync _|q, 0xffffffff;\n@q mbarrier.arrive.shared::cta.b64 _, [%0], t;\n}\n"
               ::"r"(bar), "r"(a), "r"(b), "r"(c), "r"(d), "r"(zero) : "memory");
}
__device__ __forceinline__ void warp_arrive_if(uint32_t bar, int on) {
  asm volatile("{\n.reg .pred p, q;\nelect.sync _|q, 0xffffffff;\nsetp.ne.and.s32 p, %1, 0, q;\n@p mbarrier.arrive.shared::cta.b64 _, [%0];\n}\n"
               ::"r"(bar), "r"(on) : "memory");
}
template <int C0, int C1>
__device__ __forceinline__ void pack_acc(uint32_t (&Z)[6][4], const float (&Y)[48]) {
#pragma unroll
  for (int ch = C0; ch < C1; ch++)
#pragma unroll
    for (int ss = 0; ss < 4; ss++) {
      const int i = 16 * (ch >> 1) + 4 * ss + 2 * (ch & 1);
      Z[ch][ss] = pack2(Y[i], Y[i + 1]);
    }
}
template <int BUF, int C0, int C1>
__device__ __forceinline__ void add_stage(const Ctx& c, uint32_t (&Z)[6][4], const uint32_t (&P)[6][4]) {
#pragma unroll
  for (int ch = C0; ch < C1; ch++)
#pragma unroll
    for (int ss = 0; ss < 4; ss++) Z[ch][ss] = badd(Z[ch][ss], P[ch][ss]);
#pragma unroll
  for (int ch = C0; ch < C1; ch++) sts4(c.xaddr + BUF * XBUF_BYTES + (ch & 1) * 6144 + (ch >> 1) * 64, Z[ch]);
}

__device__ __forceinline__ uint64_t get_bd(int n) { return BDESC + (uint64_t)(uint32_t)(n >> 8); }

#define G1  batch_<0, 0, 1>(r.X, r.T[0][OLD], bd);
#define G2  batch_<0, 1, 0>(r.X, r.T[0][MID], bd);
#define G3  batch_<0, 2, 0>(r.X, r.T[0][OLD], bd);
#define G4  batch_<1, 0, 1>(r.Y, r.T[1][OLD], bd);
#define G5  batch_<1, 1, 0>(r.Y, r.T[1][MID], bd);
#define G6  batch_<1, 2, 0>(r.Y, r.T[1][OLD], bd);
#define G7  if (OLD == 1) batch_<2, 0, 0>(r.X, r.T[2][OLD], bd); else { if (!skip) { F batch_<2, 0, 0>(r.X, r.T[2][OLD], bd); } else { F wg_commit(); } F }
#define G8  batch_<2, 1, 0>(r.X, r.T[2][MID], bd);
#define G9  batch_<2, 2, 0>(r.X, r.T[2][OLD], bd);
#define G10 if (OLD == 1) batch_<3, 0, 0>(r.Y, r.T[3][OLD], bd); else { if (!skip) { F batch_<3, 0, 0>(r.Y, r.T[3][OLD], bd); } else { F wg_commit(); } F }
#define G11 batch_<3, 1, 0>(r.Y, r.T[3][MID], bd);
#define G12 batch_<3, 2, 0>(r.Y, r.T[3][OLD], bd);
#define F   wg_fence();
#define W(k) wg_wait<k>();
#define PK(a, b) pack_acc<a, b>(r.Z, r.Y);
#define XW  mbar_wait(c.xfull + MID * 64, ((n - 1) >> 1) & 1); FIX3
#define LP(a, b) load_partner<MID, a, b>(c, r.P);
#define AS(a, b) add_stage<MID, a, b>(c, r.Z, r.P);
#define LV1 if (RANK == 0) ld3(r.V, c.aU, OLD * STAGE_BYTES + OFF_V); else ld3(r.U, c.aU, OLD * STAGE_BYTES);
#define LU1 if (RANK == 0) ld3(r.U, c.aU, OLD * STAGE_BYTES); else ld3(r.V, c.aU, OLD * STAGE_BYTES + OFF_V);
#define LEk(k)  ldsm4(r.E[k], (c.aE ^ (32 * k)) + OLD * STAGE_BYTES);
#define LV1k(k) if (RANK == 0) ldsm4(r.V[k], (c.aU ^ (32 * k)) + OLD * STAGE_BYTES + OFF_V); else ldsm4(r.U[k], (c.aU ^ (32 * k)) + OLD * STAGE_BYTES);
#define LV2k(k) if (RANK == 0) ldsm4(r.V[k], (c.aU ^ (32 * k)) + MID * STAGE_BYTES + OFF_V); else ldsm4(r.U[k], (c.aU ^ (32 * k)) + MID * STAGE_BYTES);
#define LU1k(k) if (RANK == 0) ldsm4(r.U[k], (c.aU ^ (32 * k)) + OLD * STAGE_BYTES); else ldsm4(r.V[k], (c.aU ^ (32 * k)) + OLD * STAGE_BYTES + OFF_V);
#define LU2k(k) if (RANK == 0) ldsm4(r.U[k], (c.aU ^ (32 * k)) + MID * STAGE_BYTES); else ldsm4(r.V[k], (c.aU ^ (32 * k)) + MID * STAGE_BYTES + OFF_V);
#define TRS tr_sum(r.T[0][OLD], r.U, r.V);
#define TRF tr_dif(r.T[1][OLD], r.U, r.V);
#define TRC if (RANK == 0) tr_t3(r.T[2][OLD], r.U, r.E); else tr_t0(r.T[2][OLD], r.V, r.E);
#define TRD if (RANK == 0) tr_t0(r.T[3][OLD], r.V, r.E); else tr_t3(r.T[3][OLD], r.U, r.E);
#define SIG warp_arrive_if(c.sig + 64 * (OLD ? c.wg : 1 - c.wg), OLD ? 1 : n | c.wg);
#define FEN asm volatile("fence.proxy.async.shared::cta;" ::: "memory");
#define DONE __syncwarp(); warp_arrive_if(c.bar_full + 8 * (BAR_STAGED - BAR_FULL + MID), 1);
#define EMP warp_release(c.bar_full + 8 * (BAR_EMPTY - BAR_FULL + OLD), r.E[0][RANK], r.E[1][RANK], r.E[2][RANK], __float_as_uint(r.Y[47]), c.zero);
#define FW  if (OLD == 1) mbar_wait(c.bar_full, ((n + 2) >> 1) & 1); \
            else mbar_wait(n ? c.bar_full + 8 : c.bar_ready, n ? ((n + 3) >> 1) & 1 : 0);
#define FIX3 if (OLD == 1 && n == 1) { mbar_wait(c.bar_full + 8, 1); SCHED_FIX3 }
#define SND(k) send_chunk<RANK, OLD, k>(c, r.X);
#define SCHED1 F G1 G2 W(2) PK(0,1) PK(1,2) XW PK(2,3) LP(0,1) AS(0,1) PK(3,4) PK(4,5) PK(5,6) LP(1,2) AS(1,2) LP(2,3) LP(3,4) LP(4,5) AS(2,3) AS(3,4) LU1k(0) F G4 LP(5,6) LV1k(0) LV1k(1) F G5 LV1k(2) LU1k(1) LU1k(2) AS(4,5) AS(5,6) W(3) TRS F G3 W(2) TRF LEk(0) LEk(1) LEk(2) F G6
#define SCHED1_FIRST LEk(0) LEk(1) LEk(2)
#define SCHED_FIX3
#define SCHED2 SIG F G7 G8 EMP W(1) TRC F G9 G10 FW W(1) SND(0) FEN SND(1) SND(2) F G11 SND(3) W(1) TRD SND(4) SND(5) F G12 DONE

template <int RANK, int OLD, bool FIRST>
__device__ __forceinline__ void phase1(const Ctx& c, int n, Regs& r) {
  constexpr int MID = 1 - OLD;
  const uint64_t bd = get_bd(n);
  if (FIRST) {
    mbar_wait(c.bar_full + 8 * OLD, 0);
    LU1 LV1 W(1) TRS F G3 W(1) TRF F G6
    SCHED1_FIRST
  } else {
    SCHED1
  }
}

template <int RANK, int OLD>
__device__ __forceinline__ void phase2(const Ctx& c, int n, Regs& r) {
  constexpr int MID = 1 - OLD;
  const uint64_t bd = get_bd(n);
  wg_wait<0>();
  butterfly<RANK, 0, 48>(r.X, r.Y);
  const bool skip = (unsigned)(c.h0 + n * c.hstep) >= (unsigned)IMG_H;
  SCHED2
}

template <int RANK>
__device__ __forceinline__ void finish_strip(const Ctx& c, Regs& r, int buf) {
  warp_arrive_if(c.sig + 64 * (buf ^ c.wg), 1);
  wg_wait<0>();
  pack_acc<0, 6>(r.Z, r.Y);
  const int lane = threadIdx.x & 31, g = lane >> 2;
  const int px = 8 * (c.u0 + 4 * c.warp + (g >> 1)) + (g & 1) + 2 * RANK;
  char* o = c.out + ((size_t)(c.h0 + c.nrows * c.hstep) * IMG_W + px) * (CH * 2) + (lane & 3) * 16;
  mbar_wait(c.xfull + buf * 64, ((c.nrows - 1) >> 1) & 1);
#pragma unroll
  for (int ch = 0; ch < 6; ch++) lds4(r.P[ch], c.xaddr + buf * XBUF_BYTES + (ch & 1) * 6144 + (ch >> 1) * 64);
#pragma unroll
  for (int ch = 0; ch < 6; ch++)
    asm volatile("st.global.v4.b32 [%0], {%1,%2,%3,%4};" ::"l"(o + (ch & 1) * (4 * CH * 2) + (ch >> 1) * 64), "r"(badd(r.Z[ch][0], r.P[ch][0])),
                 "r"(badd(r.Z[ch][1], r.P[ch][1])), "r"(badd(r.Z[ch][2], r.P[ch][2])), "r"(badd(r.Z[ch][3], r.P[ch][3])) : "memory");
}

__device__ __forceinline__ void transform_weights(uint32_t sbase, int rank, uint32_t items, int lane) {
  const uint32_t bar_w = sbase + OFF_BAR + 8 * BAR_W;
  const uint32_t o_w0 = (rank ? 2 : 3) * 9 * BT_BYTES, o_w2 = (rank ? 3 : 2) * 9 * BT_BYTES;
#pragma unroll 1
  for (; items; items >>= 8) {
    const int item = (items & 255) - 1;
    if (item >= 18) break;
    const uint32_t base = sbase + OFF_W + item * 1536;
    mbar_wait(bar_w + 8 * (item / 6), 0);
    uint32_t wa[3][4], wb[3][4], wd[3][4];
    const uint32_t src = base + (lane >> 2) * 192 + (lane & 3) * 16;
#pragma unroll
    for (int m = 0; m < 3; m++) lds4(wa[m], src + o_w0 + m * 64);
#pragma unroll
    for (int m = 0; m < 3; m++) lds4(wd[m], src + o_w2 + m * 64);
#pragma unroll
    for (int m = 0; m < 3; m++) lds4(wb[m], src + m * 64);
    __syncwarp();
    const uint32_t dst = base + lane * 16;
#pragma unroll
    for (int m = 0; m < 3; m++) stsm4(dst + m * 512 + o_w0, wa[m][0], wa[m][1], wa[m][2], wa[m][3]);
#pragma unroll
    for (int m = 0; m < 3; m++) stsm4(dst + m * 512 + o_w2, wd[m][0], wd[m][1], wd[m][2], wd[m][3]);
#pragma unroll
    for (int m = 0; m < 3; m++) {
      uint32_t g1[4], g2[4];
#pragma unroll
      for (int ss = 0; ss < 4; ss++) {
        const uint32_t a = wa[m][ss], b = wb[m][ss], d = wd[m][ss];
        const float slo = 0.5f * (bf_lo(a) + bf_lo(d)), shi = 0.5f * (bf_hi(a) + bf_hi(d));
        const float blo = bf_lo(b), bhi = bf_hi(b);
        g1[ss] = pack2(fmaf(blo, 0.5f, slo), fmaf(bhi, 0.5f, shi));
        g2[ss] = pack2(fmaf(blo, -0.5f, slo), fmaf(bhi, -0.5f, shi));
      }
      stsm4(dst + m * 512, g1[0], g1[1], g1[2], g1[3]);
      stsm4(dst + m * 512 + 9 * BT_BYTES, g2[0], g2[1], g2[2], g2[3]);
    }
  }
  asm volatile("fence.proxy.async.shared::cta;" ::: "memory");
  __syncwarp();
  if (elect_one()) mbar_arrive(bar_w + 24);
  __syncwarp();
}

template <int RANK>
__device__ __forceinline__ void run_strip(const Ctx& c, uint32_t row0_off, uint32_t bar_row0) {
  Regs r;
#pragma unroll
  for (int i = 0; i < 48; i++) { r.X[i] = 0.f; r.Y[i] = 0.f; r.Z[i % 6][i / 12] = 0; r.P[i % 6][i / 12] = 0; }
#pragma unroll
  for (int m = 1; m >= 0; m--) {
    const uint32_t off = m ? STAGE_BYTES : row0_off;
    mbar_wait(m ? c.bar_full + 8 : bar_row0, 0);
    if (m == 0 && (unsigned)c.h0 >= (unsigned)IMG_H) {
#pragma unroll
      for (int i = 0; i < 48; i++) asm volatile("" : "=r"(r.T[i / 12][0][(i / 4) % 3][i % 4]));
      continue;
    }
    ld3(r.U, c.aU, off);
    ld3(r.V, c.aU, off + OFF_V);
    ld3(r.E, c.aE, off);
    tr_sum(r.T[0][m], r.U, r.V);
    tr_dif(r.T[1][m], r.U, r.V);
    if (m) mbar_wait(SMEM_BASE + (RANK << 24) + OFF_BAR + 8 * BAR_W + 24, 0);
    wg_fence();
    if (m) { batch_<0, 1, 1>(r.X, r.T[0][1], BDESC); batch_<1, 1, 1>(r.Y, r.T[1][1], BDESC); }
    else   { batch_<0, 0, 0>(r.X, r.T[0][0], BDESC); batch_<1, 0, 0>(r.Y, r.T[1][0], BDESC); }
    tr_t3(r.T[RANK == 0 ? 2 : 3][m], r.U, r.E);
    tr_t0(r.T[RANK == 0 ? 3 : 2][m], r.V, r.E);
  }
  warp_done(c.bar_full + 8 * (BAR_EMPTY - BAR_FULL + 1));
  phase1<RANK, 0, true>(c, 0, r);
#pragma unroll 1
  for (int n = 0;; n += 2) {
    phase2<RANK, 0>(c, n, r);
    if (n + 1 == c.nrows) break;
    phase1<RANK, 1, false>(c, n + 1, r);
    phase2<RANK, 1>(c, n + 1, r);
    if (n + 2 == c.nrows) break;
    phase1<RANK, 0, false>(c, n + 2, r);
  }
  finish_strip<RANK>(c, r, (c.nrows - 1) & 1);
}

constexpr int NCL = 66;
struct Strip { int seg, h0, nrows; };
__device__ __forceinline__ bool is_down(int cl) { return cl < 2 || !((cl - 2) & 4); }
__device__ __forceinline__ Strip get_strip(int cl, int wg) {
  const int k = cl - 2, i = k >> 2;
  const int q = (i & 1) ? (wg ? 16 + 15 * i : 16 * i + 16) : (wg ? 30 + 15 * i : 16 * i - 1);
  return cl < 2 ? Strip{2 * cl + wg, -1, 16} : Strip{k & 3, 2 * q + wg, 16 - wg};
}

__device__ __forceinline__ void load_rows(const CUtensorMap* xmap, const char* x, uint32_t sbase, int rank, int wg, Strip sp, int hstep) {
  const uint32_t full = sbase + OFF_BAR + 8 * (BAR_FULL + 2 * wg), empty = full + 8 * (BAR_EMPTY - BAR_FULL);
  const uint32_t in_base = sbase + OFF_IN + wg * WG_IN_BYTES;
  const int halo = sp.seg != 3 * rank ? 6 : 0;
  const char* xseg = x + (sp.seg * 128 + (rank ? 64 : -halo)) * (CH * 2);
  const int pf_bytes = (64 + halo) * CH * 2;
#pragma unroll 1
  for (int m = 3; m <= sp.nrows + 2; m++) {
    const int s = m & 1, h = sp.h0 + m * hstep;
    mbar_wait(empty + 8 * s, ((m - 3) >> 1) & 1);
    if (m == 3) {
      asm volatile("mbarrier.arrive.shared::cluster.b64 _, [%0];" ::"r"((sbase + OFF_BAR + 8 * (BAR_READY + wg)) ^ 0x01000000u) : "memory");
    }
    if (m <= 4) mbar_arrive(full + 8 * s);
    if (m < sp.nrows + 2) {
      const int hp = h + hstep;
      const bool pf = m >= 4 + PF_START && m + 1 < sp.nrows + 2 && (unsigned)hp < (unsigned)IMG_H;
      mbar_expect_tx(full + 8 * s, 2 * BOX_BYTES);
      tma_load5(in_base + s * STAGE_BYTES, xmap, full + 8 * s, rank * 48, 0, sp.seg * 16, 0, h);
      tma_load5(in_base + s * STAGE_BYTES + OFF_BOXB, xmap, full + 8 * s, rank * 48, 2, sp.seg * 16 - 1, 0, h);
      if (pf) asm volatile("cp.async.bulk.prefetch.L2.global [%0], %1;" ::"l"(xseg + (size_t)hp * (IMG_W * CH * 2)), "r"(pf_bytes) : "memory");
    } else {
      mbar_arrive(full + 8 * s);
    }
  }
}
__device__ __forceinline__ void store_rows(const CUtensorMap* omap, uint32_t sbase, int rank, int wg, Strip sp, int hstep) {
  const uint32_t full = sbase + OFF_BAR + 8 * (BAR_FULL + 2 * wg), staged = full + 8 * (BAR_STAGED - BAR_FULL);
  const uint32_t xfull = sbase + OFF_BAR + 8 * (BAR_XFULL + 4 * wg);
#pragma unroll 1
  for (int n = 0; n < sp.nrows - 1; n++) {
    const int b = n & 1;
    mbar_wait(staged + 8 * b, ((n + 1) >> 1) & 1);
    tma_store5(omap, sbase + OFF_X + (2 * wg + b) * XBUF_BYTES, 0, sp.seg * 16, 0, rank, sp.h0 + (n + 1) * hstep);
#pragma unroll
    for (int q = 0; q < 4; q++) mbar_expect_tx(xfull + 64 * b + 8 * q, X_BYTES);
    asm volatile("cp.async.bulk.wait_group.read 0;" ::: "memory");
    if (n == 0) mbar_wait(xfull + 64, 0);
    if (n + 2 < sp.nrows) asm volatile("mbarrier.arrive.shared::cluster.b64 _, [%0];" ::"r"((full + 8 * (b ^ 1)) ^ 0x01000000u) : "memory");
  }
}

__global__ void __cluster_dims__(2, 1, 1) __launch_bounds__(384, 1)
dilated_conv_wino_kernel(const __grid_constant__ CUtensorMap xmap, const __grid_constant__ CUtensorMap omap,
                         const __nv_bfloat16* __restrict__ x, const __nv_bfloat16* __restrict__ w, __nv_bfloat16* __restrict__ out,
                         uint32_t zero) {
  extern __shared__ uint8_t smem_raw[];
  const int tid = threadIdx.x;
  const int w12 = __shfl_sync(0xffffffff, tid >> 5, 0);
  const int wg = w12 >> 2, warp = w12 & 3;
  const int lane = tid & 31;
  const int rank = blockIdx.x & 1;
  const int cl = blockIdx.x >> 1;
  const bool down = is_down(cl);
  const uint32_t sbase = SMEM_BASE + (rank << 24);
  const uint32_t b0 = sbase + OFF_BAR;
  const uint32_t bar_w = b0 + 8 * BAR_W;

  if (w12 >= 9) {
    if (elect_one()) {
      const int a = w12 - 9, i = down ? a : 2 - a;
      const char* src = reinterpret_cast<const char*>(w) + (uint32_t)((i * 6 + rank) * (3 * BT_BYTES));
      const uint32_t dst = sbase + OFF_W + a * 3 * BT_BYTES;
      mbar_init(bar_w + 8 * a, 1);
      mbar_expect_tx(bar_w + 8 * a, 9 * BT_BYTES);
      bulk_load(dst + (rank ? 2 : 3) * 9 * BT_BYTES, src, 3 * BT_BYTES, bar_w + 8 * a);
      bulk_load(dst, src + 6 * BT_BYTES, 3 * BT_BYTES, bar_w + 8 * a);
      bulk_load(dst + (rank ? 3 : 2) * 9 * BT_BYTES, src + 12 * BT_BYTES, 3 * BT_BYTES, bar_w + 8 * a);
    }
  } else if (elect_one()) {
    if (w12 < 8) {
      const uint32_t xf = b0 + 8 * (BAR_XFULL + w12);
      mbar_init(xf, 2);
      mbar_init(xf + 64, 2);
      if (w12 < 4) {
        mbar_init(b0 + 8 * (BAR_FULL + w12), 2);
        mbar_expect_tx(b0 + 8 * (BAR_FULL + w12), 2 * BOX_BYTES);
        mbar_arrive(b0 + 8 * (BAR_FULL + w12));
      } else {
        mbar_init(b0 + 8 * (BAR_EMPTY + warp), 4);
        mbar_init(b0 + 8 * (BAR_STAGED + warp), 4);
      }
      mbar_expect_tx(xf, X_BYTES);
      mbar_expect_tx(xf + 64, X_BYTES);
    } else {
      asm volatile("prefetch.tensormap [%0];" ::"l"(&xmap) : "memory");
#pragma unroll
      for (int q = 0; q < 2; q++) {
        mbar_init(b0 + 8 * (BAR_ROW0 + q), 1);
        mbar_init(b0 + 8 * (BAR_READY + q), 1);
      }
      mbar_init(bar_w + 24, 12);
#pragma unroll
      for (int q = 0; q < 2; q++) mbar_expect_tx(b0 + 8 * (BAR_ROW0 + q), 2 * BOX_BYTES);
    }
    asm volatile("fence.mbarrier_init.release.cluster;" ::: "memory");
  }
  __syncthreads();
  asm volatile("barrier.cluster.arrive.relaxed.aligned;" ::: "memory");
  const Strip s0 = get_strip(cl, 0), s1 = get_strip(cl, 1);
  const int hstep = down ? 2 : -2;
  if (w12 == 8 || w12 == 9) {
    if (elect_one()) {
#pragma unroll 1
      for (uint32_t order = cl < 2 ? FIRST_ROWS_BORDER : FIRST_ROWS; order; order >>= 4) {
        const int g = (order >> 2) & 1, m = order & 3;
        const uint32_t dst = m == 0 ? sbase + (g ? OFF_ROW0_1 : OFF_ROW0_0) : sbase + OFF_IN + g * WG_IN_BYTES + (m & 1) * STAGE_BYTES;
        const uint32_t bar = b0 + 8 * (m == 0 ? BAR_ROW0 + g : BAR_FULL + 2 * g + (m & 1));
        tma_load5(dst + warp * OFF_BOXB, &xmap, bar, rank * 48, 2 * warp, (g ? s1.seg : s0.seg) * 16 - warp, 0, (g ? s1.h0 : s0.h0) + m * hstep);
      }
      asm volatile("prefetch.tensormap [%0];" ::"l"(&omap) : "memory");
    }
    __syncwarp();
  }
  if ((uint32_t)__cvta_generic_to_shared(smem_raw) != sbase || mapa(sbase, rank ^ 1) != (sbase ^ 0x01000000u)) __trap();
  asm volatile("barrier.cluster.wait.aligned;" ::: "memory");
  transform_weights(sbase, rank, (wg == 0 ? WITEMS0 : wg == 1 ? WITEMS1 : WITEMS2) + warp * 0x010101u, lane);

  if (wg == 2) {
    asm volatile("setmaxnreg.dec.sync.aligned.u32 24;");
    if (elect_one()) {
      if (warp < 2) load_rows(&xmap, reinterpret_cast<const char*>(x), sbase, rank, warp, warp ? s1 : s0, hstep);
      else store_rows(&omap, sbase, rank, warp - 2, warp == 3 ? s1 : s0, hstep);
    }
  } else {
    asm volatile("setmaxnreg.inc.sync.aligned.u32 240;");
    Ctx c;
    c.out = reinterpret_cast<char*>(out);
    c.zero = zero;
    c.wg = wg;
    c.warp = warp;
    c.sig = b0 + 8 * (BAR_XFULL + (w12 ^ 4));
    c.bar_full = b0 + 8 * (BAR_FULL + wg * NSTAGE);
    c.bar_ready = b0 + 8 * (BAR_READY + wg);
    c.u0 = (wg ? s1.seg : s0.seg) * 16;
    c.h0 = wg ? s1.h0 : s0.h0;
    c.hstep = hstep;
    c.nrows = wg ? s1.nrows : s0.nrows;
    c.xfull = b0 + 8 * (BAR_XFULL + w12);
    const uint32_t in_base = sbase + OFF_IN + wg * WG_IN_BYTES;
    {
      const int g = lane & 7, mi = lane >> 3;
      const int rU = 8 * warp + g + ((mi & 1) ? 34 : 0);
      const int rE = 8 * warp + g + ((mi & 1) ? 2 : 70 + 34);
      const uint32_t pU = in_base + rU * 128, pE = in_base + rE * 128;
      c.aU = pU + (((mi >> 1) ^ ((pU >> 7) & 7)) << 4);
      c.aE = pE + (((mi >> 1) ^ ((pE >> 7) & 7)) << 4);
    }
    c.xaddr = sbase + OFF_X + wg * 2 * XBUF_BYTES + (warp * 8 + (lane >> 2)) * 192 + (lane & 3) * 16;
    const uint32_t row0_off = sbase + (wg ? OFF_ROW0_1 : OFF_ROW0_0) - in_base;
    const uint32_t bar_row0 = cl < 2 ? bar_w : b0 + 8 * (BAR_ROW0 + wg);
    if (rank == 0) run_strip<0>(c, row0_off, bar_row0); else run_strip<1>(c, row0_off, bar_row0);
  }
}

typedef CUresult (*EncodeTiledFn)(CUtensorMap*, CUtensorMapDataType, cuuint32_t, void*, const cuuint64_t*, const cuuint64_t*,
                                  const cuuint32_t*, const cuuint32_t*, CUtensorMapInterleave, CUtensorMapSwizzle,
                                  CUtensorMapL2promotion, CUtensorMapFloatOOBfill);

}

extern "C" void kernel_launch(void* const* d_in, const int* in_sizes, int n_in, void* d_out, int out_size) {
  (void)in_sizes; (void)n_in; (void)out_size;
  static EncodeTiledFn encode = nullptr;
  if (!encode) {
    void* fn = nullptr;
    cudaDriverEntryPointQueryResult qr;
    cudaGetDriverEntryPoint("cuTensorMapEncodeTiled", &fn, cudaEnableDefault, &qr);
    encode = (EncodeTiledFn)fn;
    cudaFuncSetAttribute(dilated_conv_wino_kernel, cudaFuncAttributeMaxDynamicSharedMemorySize, SMEM_BYTES);
  }
  CUtensorMap xmap;
  const cuuint64_t dims[5] = {CH, 4, IMG_W / 8, 2, IMG_H};
  const cuuint64_t strides[4] = {CH * 2, 8 * CH * 2, 4 * CH * 2, IMG_W * CH * 2};
  const cuuint32_t box[5] = {48, 2, 17, 2, 1};
  const cuuint32_t estr[5] = {1, 1, 1, 1, 1};
  encode(&xmap, CU_TENSOR_MAP_DATA_TYPE_BFLOAT16, 5, d_in[0], dims, strides, box, estr, CU_TENSOR_MAP_INTERLEAVE_NONE,
         CU_TENSOR_MAP_SWIZZLE_128B, CU_TENSOR_MAP_L2_PROMOTION_L2_128B, CU_TENSOR_MAP_FLOAT_OOB_FILL_NONE);
  CUtensorMap omap;
  const cuuint64_t odims[5] = {2 * CH, IMG_W / 8, 2, 2, IMG_H};
  const cuuint64_t ostrides[4] = {8 * CH * 2, 4 * CH * 2, 2 * CH * 2, IMG_W * CH * 2};
  const cuuint32_t obox[5] = {2 * CH, 16, 2, 1, 1};
  encode(&omap, CU_TENSOR_MAP_DATA_TYPE_BFLOAT16, 5, d_out, odims, ostrides, obox, estr, CU_TENSOR_MAP_INTERLEAVE_NONE,
         CU_TENSOR_MAP_SWIZZLE_NONE, CU_TENSOR_MAP_L2_PROMOTION_NONE, CU_TENSOR_MAP_FLOAT_OOB_FILL_NONE);
  dilated_conv_wino_kernel<<<2 * NCL, 384, SMEM_BYTES>>>(xmap, omap, (const __nv_bfloat16*)d_in[0], (const __nv_bfloat16*)d_in[1], (__nv_bfloat16*)d_out, 0u);
}
```

```cpp
#include <cuda_runtime.h>
#include <cuda_bf16.h>
#include <cuda.h>
#include <stdint.h>

namespace {

constexpr int IMG_H = 512, IMG_W = 512, CH = 96;
constexpr int NSTAGE = 2;

constexpr int BT_BYTES   = 3072;
constexpr int W_BYTES    = 36 * BT_BYTES;
constexpr int BOX_BYTES  = 68 * 96;
constexpr int OFF_BOXB   = 70 * 128;
constexpr int STAGE_BYTES = 144 * 128;
constexpr int OFF_V      = 72 * 128;
constexpr int WG_IN_BYTES = STAGE_BYTES + 138 * 128;
constexpr int OFF_W      = 0;
constexpr int OFF_IN     = OFF_W + W_BYTES;
constexpr int OFF_X      = OFF_IN + 2 * WG_IN_BYTES;
constexpr int XBUF_BYTES = 64 * CH * 2;
constexpr int SMEM_BYTES = OFF_X + 4 * XBUF_BYTES;
constexpr int OFF_ROW0_0 = OFF_X + ((OFF_IN - OFF_X) & 1023);
constexpr int OFF_ROW0_1 = OFF_X + 2 * XBUF_BYTES + ((OFF_IN + WG_IN_BYTES - OFF_X) & 1023);
constexpr int OFF_BAR    = OFF_IN + 138 * 128;
constexpr int BAR_FULL = 0, BAR_EMPTY = 4, BAR_STAGED = 8, BAR_XFREE = 12, BAR_W = 16, BAR_ROW0 = 20;
static_assert(SMEM_BYTES <= 232448, "shared memory");
constexpr uint32_t SMEM_BASE = 1024;
constexpr uint64_t BDESC = (uint64_t)((SMEM_BASE + OFF_W) >> 4) | ((uint64_t)(1536 >> 4) << 16) | ((uint64_t)(128 >> 4) << 32);

__device__ __forceinline__ void wg_fence()  { asm volatile("wgmma.fence.sync.aligned;" ::: "memory"); }
__device__ __forceinline__ void wg_commit() { asm volatile("wgmma.commit_group.sync.aligned;" ::: "memory"); }
template <int N> __device__ __forceinline__ void wg_wait() { asm volatile("wgmma.wait_group.sync.aligned %0;" ::"n"(N) : "memory"); }

template <int SCALE_D>
__device__ __forceinline__ void wgmma96(float (&d)[48], const uint32_t (&a)[4], uint64_t DESC) {
  asm volatile(
      "{\n.reg .pred p;\nsetp.ne.b32 p, %53, 0;\n"
      "wgmma.mma_async.sync.aligned.m64n96k16.f32.bf16.bf16 "
      "{%0,%1,%2,%3,%4,%5,%6,%7,%8,%9,%10,%11,%12,%13,%14,%15,%16,%17,%18,%19,%20,%21,%22,%23,"
      "%24,%25,%26,%27,%28,%29,%30,%31,%32,%33,%34,%35,%36,%37,%38,%39,%40,%41,%42,%43,%44,%45,%46,%47}, "
      "{%48,%49,%50,%51}, %52, p, 1, 1, 1;\n}\n"
      : "+f"(d[0]), "+f"(d[1]), "+f"(d[2]), "+f"(d[3]), "+f"(d[4]), "+f"(d[5]), "+f"(d[6]), "+f"(d[7]),
        "+f"(d[8]), "+f"(d[9]), "+f"(d[10]), "+f"(d[11]), "+f"(d[12]), "+f"(d[13]), "+f"(d[14]), "+f"(d[15]),
        "+f"(d[16]), "+f"(d[17]), "+f"(d[18]), "+f"(d[19]), "+f"(d[20]), "+f"(d[21]), "+f"(d[22]), "+f"(d[23]),
        "+f"(d[24]), "+f"(d[25]), "+f"(d[26]), "+f"(d[27]), "+f"(d[28]), "+f"(d[29]), "+f"(d[30]), "+f"(d[31]),
        "+f"(d[32]), "+f"(d[33]), "+f"(d[34]), "+f"(d[35]), "+f"(d[36]), "+f"(d[37]), "+f"(d[38]), "+f"(d[39]),
        "+f"(d[40]), "+f"(d[41]), "+f"(d[42]), "+f"(d[43]), "+f"(d[44]), "+f"(d[45]), "+f"(d[46]), "+f"(d[47])
      : "r"(a[0]), "r"(a[1]), "r"(a[2]), "r"(a[3]), "l"(DESC), "n"(SCALE_D));
}

__device__ __forceinline__ void ldsm4(uint32_t (&r)[4], uint32_t addr) {
  asm volatile("ldmatrix.sync.aligned.m8n8.x4.shared.b16 {%0,%1,%2,%3}, [%4];"
               : "=r"(r[0]), "=r"(r[1]), "=r"(r[2]), "=r"(r[3]) : "r"(addr) : "memory");
}
__device__ __forceinline__ uint32_t badd(uint32_t a, uint32_t b) {
  uint32_t d; asm volatile("add.rn.bf16x2 %0, %1, %2;" : "=r"(d) : "r"(a), "r"(b)); return d;
}
__device__ __forceinline__ uint32_t bsub(uint32_t a, uint32_t b) {
  uint32_t d; asm volatile("sub.rn.bf16x2 %0, %1, %2;" : "=r"(d) : "r"(a), "r"(b)); return d;
}
__device__ __forceinline__ float bf_lo(uint32_t v) {
  return __uint_as_float(v << 16);
}
__device__ __forceinline__ float bf_hi(uint32_t v) { return __uint_as_float(v & 0xffff0000u); }
__device__ __forceinline__ uint32_t pack2(float lo, float hi) {
  uint32_t d; asm volatile("cvt.rn.bf16x2.f32 %0, %1, %2;" : "=r"(d) : "f"(hi), "f"(lo)); return d;
}

__device__ __forceinline__ void mbar_wait(uint32_t bar, uint32_t parity) {
  asm volatile(
      "{\n.reg .pred p;\n.reg .u32 it;\n"
      "mbarrier.try_wait.parity.shared::cta.b64 p, [%0], %1;\n"
      "@p bra WAIT_DONE;\n"
      "mov.u32 it, 0;\n"
      "WAIT_LOOP:\n"
      ".pragma \"nounroll\";\n"
      "mbarrier.try_wait.parity.shared::cta.b64 p, [%0], %1;\n"
      "@p bra WAIT_DONE;\n"
      "add.u32 it, it, 1;\n"
      "setp.lt.u32 p, it, 4194304;\n"
      "@p bra WAIT_LOOP;\n"
      "trap;\n"
      "WAIT_DONE:\n}\n" ::"r"(bar), "r"(parity) : "memory");
}
__device__ __forceinline__ void mbar_init(uint32_t bar, uint32_t count) {
  asm volatile("mbarrier.init.shared::cta.b64 [%0], %1;" ::"r"(bar), "r"(count) : "memory");
}
__device__ __forceinline__ void mbar_arrive(uint32_t bar) {
  asm volatile("mbarrier.arrive.shared::cta.b64 _, [%0];" ::"r"(bar) : "memory");
}
__device__ __forceinline__ void mbar_expect_tx(uint32_t bar, uint32_t bytes) {
  asm volatile("mbarrier.arrive.expect_tx.shared::cta.b64 _, [%0], %1;" ::"r"(bar), "r"(bytes) : "memory");
}
__device__ __forceinline__ void tma_load5(uint32_t dst, const CUtensorMap* map, uint32_t bar, int c0, int c1, int c2, int c3, int c4) {
  asm volatile("cp.async.bulk.tensor.5d.shared::cluster.global.mbarrier::complete_tx::bytes [%0], [%1, {%3,%4,%5,%6,%7}], [%2];"
               ::"r"(dst), "l"(map), "r"(bar), "r"(c0), "r"(c1), "r"(c2), "r"(c3), "r"(c4) : "memory");
}
__device__ __forceinline__ void bulk_load(uint32_t dst, const void* src, uint32_t bytes, uint32_t bar) {
  asm volatile("cp.async.bulk.shared::cluster.global.mbarrier::complete_tx::bytes [%0], [%1], %2, [%3];"
               ::"r"(dst), "l"(src), "r"(bytes), "r"(bar) : "memory");
}
template <int OFF>
__device__ __forceinline__ void st_async4(uint32_t cluster_addr, uint32_t cluster_bar, uint32_t a, uint32_t b, uint32_t c, uint32_t d) {
  asm volatile("st.async.shared::cluster.mbarrier::complete_tx::bytes.v4.b32 [%0+%6], {%2,%3,%4,%5}, [%1];"
               ::"r"(cluster_addr), "r"(cluster_bar), "r"(a), "r"(b), "r"(c), "r"(d), "n"(OFF) : "memory");
}
__device__ __forceinline__ void stsm4(uint32_t addr, uint32_t a, uint32_t b, uint32_t c, uint32_t d) {
  asm volatile("stmatrix.sync.aligned.m8n8.x4.shared.b16 [%0], {%1,%2,%3,%4};" ::"r"(addr), "r"(a), "r"(b), "r"(c), "r"(d) : "memory");
}
__device__ __forceinline__ void lds4(uint32_t (&r)[4], uint32_t addr) {
  asm volatile("ld.shared.v4.b32 {%0,%1,%2,%3}, [%4];" : "=r"(r[0]), "=r"(r[1]), "=r"(r[2]), "=r"(r[3]) : "r"(addr) : "memory");
}
__device__ __forceinline__ void sts4(uint32_t addr, const uint32_t (&r)[4]) {
  asm volatile("st.shared.v4.b32 [%0], {%1,%2,%3,%4};" ::"r"(addr), "r"(r[0]), "r"(r[1]), "r"(r[2]), "r"(r[3]) : "memory");
}
__device__ __forceinline__ void tma_store5(const CUtensorMap* map, uint32_t src, int c0, int c1, int c2, int c3, int c4) {
  asm volatile("cp.async.bulk.tensor.5d.global.shared::cta.bulk_group [%0, {%2,%3,%4,%5,%6}], [%1];"
               ::"l"(map), "r"(src), "r"(c0), "r"(c1), "r"(c2), "r"(c3), "r"(c4) : "memory");
  asm volatile("cp.async.bulk.commit_group;" ::: "memory");
}
__device__ __forceinline__ bool elect_one() {
  uint32_t p;
  asm volatile("{\n.reg .pred P;\nelect.sync _|P, 0xffffffff;\nselp.u32 %0, 1, 0, P;\n}\n" : "=r"(p));
  return p;
}
__device__ __forceinline__ uint32_t mapa(uint32_t addr, uint32_t rank) {
  uint32_t r; asm("mapa.shared::cluster.u32 %0, %1, %2;" : "=r"(r) : "r"(addr), "r"(rank)); return r;
}

__device__ __forceinline__ void tr_sum(uint32_t (&t)[3][4], const uint32_t (&U)[3][4], const uint32_t (&V)[3][4]) {
#pragma unroll
  for (int k = 0; k < 3; k++)
#pragma unroll
    for (int i = 0; i < 4; i++) t[k][i] = badd(U[k][i], V[k][i]);
}
__device__ __forceinline__ void tr_dif(uint32_t (&t)[3][4], const uint32_t (&U)[3][4], const uint32_t (&V)[3][4]) {
#pragma unroll
  for (int k = 0; k < 3; k++)
#pragma unroll
    for (int i = 0; i < 4; i++) t[k][i] = bsub(V[k][i], U[k][i]);
}
__device__ __forceinline__ void tr_t0(uint32_t (&t)[3][4], const uint32_t (&V)[3][4], const uint32_t (&E)[3][4]) {
#pragma unroll
  for (int k = 0; k < 3; k++) {
    t[k][0] = bsub(E[k][0], V[k][0]); t[k][1] = bsub(V[k][0], V[k][1]);
    t[k][2] = bsub(E[k][2], V[k][2]); t[k][3] = bsub(V[k][2], V[k][3]);
  }
}
__device__ __forceinline__ void tr_t3(uint32_t (&t)[3][4], const uint32_t (&U)[3][4], const uint32_t (&E)[3][4]) {
#pragma unroll
  for (int k = 0; k < 3; k++) {
    t[k][0] = bsub(U[k][1], U[k][0]); t[k][1] = bsub(E[k][1], U[k][1]);
    t[k][2] = bsub(U[k][3], U[k][2]); t[k][3] = bsub(E[k][3], U[k][3]);
  }
}
__device__ __forceinline__ void ld3(uint32_t (&R)[3][4], uint32_t aU, int off) {
#pragma unroll
  for (int k = 0; k < 3; k++) ldsm4(R[k], (aU ^ (32 * k)) + off);
}
template <int COMP, int AGE, int FIRST>
__device__ __forceinline__ void batch_(float (&acc)[48], const uint32_t (&t)[3][4], uint64_t bd) {
  constexpr int base = ((COMP * 3 + AGE) * 3) * BT_BYTES;
  wgmma96<FIRST ? 0 : 1>(acc, t[0], bd + ((base) >> 4));
  wgmma96<1>(acc, t[1], bd + ((base + BT_BYTES) >> 4));
  wgmma96<1>(acc, t[2], bd + ((base + 2 * BT_BYTES) >> 4));
  wg_commit();
}

template <int RANK, int I0, int I1>
__device__ __forceinline__ void butterfly(float (&X)[48], float (&Y)[48]) {
#pragma unroll
  for (int i = I0; i < I1; i++) {
    if (RANK == 0) asm volatile("sub.rn.f32 %0, %0, %1;\nfma.rn.f32 %1, %1, 0f40000000, %0;" : "+f"(X[i]), "+f"(Y[i]));
    else           asm volatile("add.rn.f32 %0, %0, %1;\nfma.rn.f32 %1, %1, 0fC0000000, %0;" : "+f"(X[i]), "+f"(Y[i]));
  }
}

struct Ctx {
  uint32_t aU, aE;
  uint32_t bar_full;
  uint32_t xaddr;
  char* out;
  int wg, warp;
  int u0, h0, hstep;
  int nrows;
  uint32_t zero;
};

template <int BUF, int C0, int C1>
__device__ __forceinline__ void load_partner(const Ctx& c, uint32_t (&P)[6][4]) {
#pragma unroll
  for (int ch = C0; ch < C1; ch++) lds4(P[ch], c.xaddr + BUF * XBUF_BYTES + (ch & 1) * 6144 + (ch >> 1) * 64);
}
template <int RANK, int BUF, int CH0>
__device__ __forceinline__ void send_chunk(const Ctx& c, const float (&X)[48]) {
  constexpr uint32_t RDELTA = RANK ? 0xFF000000u : 0x01000000u;
  constexpr int m = CH0 >> 1, s = CH0 & 1;
  uint32_t o[4];
#pragma unroll
  for (int ss = 0; ss < 4; ss++) o[ss] = pack2(X[16 * m + 4 * ss + 2 * s], X[16 * m + 4 * ss + 2 * s + 1]);
  st_async4<BUF * XBUF_BYTES + s * 6144 + m * 64>(c.xaddr + RDELTA, c.bar_full + 8 * (1 - BUF) + RDELTA, o[0], o[1], o[2], o[3]);
}

constexpr int PF_START = 1;
constexpr uint32_t WITEMS0 = 0x404009u, WITEMS1 = 0x110d01u, WITEMS2 = 0x404005u;
constexpr uint32_t FIRST_ROWS = 0x645201u, FIRST_ROWS_BORDER = 0x6521u;

struct Regs {
  float X[48], Y[48];
  uint32_t T[4][2][3][4];
  uint32_t U[3][4], V[3][4], E[3][4];
  uint32_t Z[6][4], P[6][4];
};

__device__ __forceinline__ void warp_done(uint32_t bar) {
  asm volatile("fence.proxy.async.shared::cta;" ::: "memory");
  __syncwarp();
  asm volatile("{\n.reg .pred q;\nelect.sync _|q, 0xffffffff;\n@q mbarrier.arrive.shared::cta.b64 _, [%0];\n}\n" ::"r"(bar) : "memory");
}
__device__ __forceinline__ void warp_release(uint32_t bar, uint32_t a, uint32_t b, uint32_t c, uint32_t d, uint32_t zero) {
  asm volatile("{\n.reg .pred q;\n.reg .b32 t;\nlop3.b32 t, %1, %4, %5, 0x80;\nlop3.b32 t, t, %2, %3, 0x80;\nor.b32 t, t, 1;\n"
               "elect.sync _|q, 0xffffffff;\n@q mbarrier.arrive.shared::cta.b64 _, [%0], t;\n}\n"
               ::"r"(bar), "r"(a), "r"(b), "r"(c), "r"(d), "r"(zero) : "memory");
}
__device__ __forceinline__ void warp_arrive_if(uint32_t bar, int on) {
  asm volatile("{\n.reg .pred p, q;\nelect.sync _|q, 0xffffffff;\nsetp.ne.and.s32 p, %1, 0, q;\n@p mbarrier.arrive.shared::cta.b64 _, [%0];\n}\n"
               ::"r"(bar), "r"(on) : "memory");
}
template <int C0, int C1>
__device__ __forceinline__ void pack_acc(uint32_t (&Z)[6][4], const float (&Y)[48]) {
#pragma unroll
  for (int ch = C0; ch < C1; ch++)
#pragma unroll
    for (int ss = 0; ss < 4; ss++) {
      const int i = 16 * (ch >> 1) + 4 * ss + 2 * (ch & 1);
      Z[ch][ss] = pack2(Y[i], Y[i + 1]);
    }
}
template <int BUF, int C0, int C1>
__device__ __forceinline__ void add_stage(const Ctx& c, uint32_t (&Z)[6][4], const uint32_t (&P)[6][4]) {
#pragma unroll
  for (int ch = C0; ch < C1; ch++)
#pragma unroll
    for (int ss = 0; ss < 4; ss++) Z[ch][ss] = badd(Z[ch][ss], P[ch][ss]);
#pragma unroll
  for (int ch = C0; ch < C1; ch++) sts4(c.xaddr + BUF * XBUF_BYTES + (ch & 1) * 6144 + (ch >> 1) * 64, Z[ch]);
}

__device__ __forceinline__ uint64_t get_bd(int n) { return BDESC + (uint64_t)(uint32_t)(n >> 8); }

#define G1  batch_<0, 0, 1>(r.X, r.T[0][OLD], bd);
#define G2  batch_<0, 1, 0>(r.X, r.T[0][MID], bd);
#define G3  batch_<0, 2, 0>(r.X, r.T[0][OLD], bd);
#define G4  batch_<1, 0, 1>(r.Y, r.T[1][OLD], bd);
#define G5  batch_<1, 1, 0>(r.Y, r.T[1][MID], bd);
#define G6  batch_<1, 2, 0>(r.Y, r.T[1][OLD], bd);
#define G7  if (OLD == 1) batch_<2, 0, 0>(r.X, r.T[2][OLD], bd); else { if (!skip) { F batch_<2, 0, 0>(r.X, r.T[2][OLD], bd); } else { F wg_commit(); } F }
#define G8  batch_<2, 1, 0>(r.X, r.T[2][MID], bd);
#define G9  batch_<2, 2, 0>(r.X, r.T[2][OLD], bd);
#define G10 if (OLD == 1) batch_<3, 0, 0>(r.Y, r.T[3][OLD], bd); else { if (!skip) { F batch_<3, 0, 0>(r.Y, r.T[3][OLD], bd); } else { F wg_commit(); } F }
#define G11 batch_<3, 1, 0>(r.Y, r.T[3][MID], bd);
#define G12 batch_<3, 2, 0>(r.Y, r.T[3][OLD], bd);
#define F   wg_fence();
#define W(k) wg_wait<k>();
#define PK(a, b) pack_acc<a, b>(r.Z, r.Y);
#define XW  mbar_wait(c.bar_full + 8 * OLD, ((n + 1) >> 1) & 1);
#define LP(a, b) load_partner<MID, a, b>(c, r.P);
#define AS(a, b) add_stage<MID, a, b>(c, r.Z, r.P);
#define LV1 if (RANK == 0) ld3(r.V, c.aU, OLD * STAGE_BYTES + OFF_V); else ld3(r.U, c.aU, OLD * STAGE_BYTES);
#define LU1 if (RANK == 0) ld3(r.U, c.aU, OLD * STAGE_BYTES); else ld3(r.V, c.aU, OLD * STAGE_BYTES + OFF_V);
#define LEk(k)  ldsm4(r.E[k], (c.aE ^ (32 * k)) + OLD * STAGE_BYTES);
#define LV1k(k) if (RANK == 0) ldsm4(r.V[k], (c.aU ^ (32 * k)) + OLD * STAGE_BYTES + OFF_V); else ldsm4(r.U[k], (c.aU ^ (32 * k)) + OLD * STAGE_BYTES);
#define LU1k(k) if (RANK == 0) ldsm4(r.U[k], (c.aU ^ (32 * k)) + OLD * STAGE_BYTES); else ldsm4(r.V[k], (c.aU ^ (32 * k)) + OLD * STAGE_BYTES + OFF_V);
#define TRS tr_sum(r.T[0][OLD], r.U, r.V);
#define TRF tr_dif(r.T[1][OLD], r.U, r.V);
#define TRC if (RANK == 0) tr_t3(r.T[2][OLD], r.U, r.E); else tr_t0(r.T[2][OLD], r.V, r.E);
#define TRD if (RANK == 0) tr_t0(r.T[3][OLD], r.V, r.E); else tr_t3(r.T[3][OLD], r.U, r.E);
#define SIG warp_arrive_if((c.bar_full ^ 16) + 8 * (OLD ^ c.wg), OLD ? 1 : n | c.wg);
#define FEN asm volatile("fence.proxy.async.shared::cta;" ::: "memory");
#define DONE __syncwarp(); warp_arrive_if(c.bar_full + 8 * (BAR_STAGED - BAR_FULL + MID), 1);
#define EMP warp_release(c.bar_full + 8 * (BAR_EMPTY - BAR_FULL + OLD), r.E[0][RANK], r.E[1][RANK], r.E[2][RANK], __float_as_uint(r.Y[47]), c.zero);
#define FW  mbar_wait(c.bar_full + 8 * (BAR_XFREE - BAR_FULL + OLD), (n >> 1) & 1);
#define SND(k) send_chunk<RANK, OLD, k>(c, r.X);
#define SCHED1 F G1 G2 W(2) PK(0,1) XW PK(1,2) LP(0,1) PK(2,3) AS(0,1) LP(1,2) LP(2,3) AS(1,2) PK(3,4) LP(3,4) LP(4,5) AS(2,3) PK(4,5) LU1k(0) PK(5,6) AS(3,4) F G4 LV1k(0) LP(5,6) LV1k(1) F G5 LV1k(2) LU1k(1) LU1k(2) AS(4,5) W(1) TRF AS(5,6) TRS F G3 LEk(0) F G6 LEk(1) LEk(2)
#define SCHED1_FIRST LEk(0) LEk(1) LEk(2)
#define SCHED2 SIG F G7 G8 EMP W(1) TRC F G9 G10 FW W(1) SND(0) FEN SND(1) F G11 SND(2) SND(3) W(1) TRD SND(4) F G12 SND(5) DONE

template <int RANK, int OLD, bool FIRST>
__device__ __forceinline__ void phase1(const Ctx& c, int n, Regs& r) {
  constexpr int MID = 1 - OLD;
  const uint64_t bd = get_bd(n);
  if (FIRST) {
    mbar_wait(c.bar_full + 8 * OLD, 0);
    LU1 LV1 W(1) TRS F G3 W(1) TRF F G6
    SCHED1_FIRST
  } else {
    SCHED1
  }
}

template <int RANK, int OLD>
__device__ __forceinline__ void phase2(const Ctx& c, int n, Regs& r) {
  constexpr int MID = 1 - OLD;
  const uint64_t bd = get_bd(n);
  wg_wait<0>();
  butterfly<RANK, 0, 48>(r.X, r.Y);
  const bool skip = (unsigned)(c.h0 + n * c.hstep) >= (unsigned)IMG_H;
  SCHED2
}

template <int RANK>
__device__ __forceinline__ void finish_strip(const Ctx& c, Regs& r, int buf) {
  warp_arrive_if((c.bar_full ^ 16) + 8 * (buf ^ 1 ^ c.wg), 1);
  wg_wait<0>();
  pack_acc<0, 6>(r.Z, r.Y);
  const int lane = threadIdx.x & 31, g = lane >> 2;
  const int px = 8 * (c.u0 + 4 * c.warp + (g >> 1)) + (g & 1) + 2 * RANK;
  char* o = c.out + ((size_t)(c.h0 + c.nrows * c.hstep) * IMG_W + px) * (CH * 2) + (lane & 3) * 16;
  mbar_wait(c.bar_full + 8 * (buf ^ 1), ((c.nrows + 1) >> 1) & 1);
#pragma unroll
  for (int ch = 0; ch < 6; ch++) lds4(r.P[ch], c.xaddr + buf * XBUF_BYTES + (ch & 1) * 6144 + (ch >> 1) * 64);
#pragma unroll
  for (int ch = 0; ch < 6; ch++)
    asm volatile("st.global.v4.b32 [%0], {%1,%2,%3,%4};" ::"l"(o + (ch & 1) * (4 * CH * 2) + (ch >> 1) * 64), "r"(badd(r.Z[ch][0], r.P[ch][0])),
                 "r"(badd(r.Z[ch][1], r.P[ch][1])), "r"(badd(r.Z[ch][2], r.P[ch][2])), "r"(badd(r.Z[ch][3], r.P[ch][3])) : "memory");
}

__device__ __forceinline__ void transform_weights(uint32_t sbase, int rank, uint32_t items, int lane) {
  const uint32_t bar_w = sbase + OFF_BAR + 8 * BAR_W;
  const uint32_t o_w0 = (rank ? 2 : 3) * 9 * BT_BYTES, o_w2 = (rank ? 3 : 2) * 9 * BT_BYTES;
#pragma unroll 1
  for (; items; items >>= 8) {
    const int item = (items & 255) - 1;
    if (item >= 18) break;
    const uint32_t base = sbase + OFF_W + item * 1536;
    mbar_wait(bar_w + 8 * (item / 6), 0);
    uint32_t wa[3][4], wb[3][4], wd[3][4];
    const uint32_t src = base + (lane >> 2) * 192 + (lane & 3) * 16;
#pragma unroll
    for (int m = 0; m < 3; m++) lds4(wa[m], src + o_w0 + m * 64);
#pragma unroll
    for (int m = 0; m < 3; m++) lds4(wd[m], src + o_w2 + m * 64);
#pragma unroll
    for (int m = 0; m < 3; m++) lds4(wb[m], src + m * 64);
    __syncwarp();
    const uint32_t dst = base + lane * 16;
#pragma unroll
    for (int m = 0; m < 3; m++) stsm4(dst + m * 512 + o_w0, wa[m][0], wa[m][1], wa[m][2], wa[m][3]);
#pragma unroll
    for (int m = 0; m < 3; m++) stsm4(dst + m * 512 + o_w2, wd[m][0], wd[m][1], wd[m][2], wd[m][3]);
#pragma unroll
    for (int m = 0; m < 3; m++) {
      uint32_t g1[4], g2[4];
#pragma unroll
      for (int ss = 0; ss < 4; ss++) {
        const uint32_t a = wa[m][ss], b = wb[m][ss], d = wd[m][ss];
        const float slo = 0.5f * (bf_lo(a) + bf_lo(d)), shi = 0.5f * (bf_hi(a) + bf_hi(d));
        const float blo = bf_lo(b), bhi = bf_hi(b);
        g1[ss] = pack2(fmaf(blo, 0.5f, slo), fmaf(bhi, 0.5f, shi));
        g2[ss] = pack2(fmaf(blo, -0.5f, slo), fmaf(bhi, -0.5f, shi));
      }
      stsm4(dst + m * 512, g1[0], g1[1], g1[2], g1[3]);
      stsm4(dst + m * 512 + 9 * BT_BYTES, g2[0], g2[1], g2[2], g2[3]);
    }
  }
  asm volatile("fence.proxy.async.shared::cta;" ::: "memory");
  __syncwarp();
  if (elect_one()) mbar_arrive(bar_w + 24);
  __syncwarp();
}

template <int RANK>
__device__ __forceinline__ void run_strip(const Ctx& c, uint32_t row0_off, uint32_t bar_row0) {
  Regs r;
  mbar_wait(SMEM_BASE + (RANK << 24) + OFF_BAR + 8 * (BAR_FULL + 1), 0);
#pragma unroll
  for (int i = 0; i < 48; i++) { r.X[i] = 0.f; r.Y[i] = 0.f; r.Z[i % 6][i / 12] = 0; r.P[i % 6][i / 12] = 0; }
#pragma unroll
  for (int m = 1; m >= 0; m--) {
    const uint32_t off = m ? STAGE_BYTES : row0_off;
    mbar_wait(m ? c.bar_full + 8 : bar_row0, 0);
    if (m == 0 && (unsigned)c.h0 >= (unsigned)IMG_H) {
#pragma unroll
      for (int i = 0; i < 48; i++) asm volatile("" : "=r"(r.T[i / 12][0][(i / 4) % 3][i % 4]));
      continue;
    }
    ld3(r.U, c.aU, off);
    ld3(r.V, c.aU, off + OFF_V);
    tr_sum(r.T[0][m], r.U, r.V);
    tr_dif(r.T[1][m], r.U, r.V);
    if (m) mbar_wait(SMEM_BASE + (RANK << 24) + OFF_BAR + 8 * BAR_W + 24, 0);
    ld3(r.E, c.aE, off);
    wg_fence();
    if (m) { batch_<0, 1, 1>(r.X, r.T[0][1], BDESC); batch_<1, 1, 1>(r.Y, r.T[1][1], BDESC); }
    else   { batch_<0, 0, 0>(r.X, r.T[0][0], BDESC); batch_<1, 0, 0>(r.Y, r.T[1][0], BDESC); }
    tr_t3(r.T[RANK == 0 ? 2 : 3][m], r.U, r.E);
    tr_t0(r.T[RANK == 0 ? 3 : 2][m], r.V, r.E);
  }
  warp_done(c.bar_full + 8 * (BAR_EMPTY - BAR_FULL + 1));
  phase1<RANK, 0, true>(c, 0, r);
#pragma unroll 1
  for (int n = 0;; n += 2) {
    phase2<RANK, 0>(c, n, r);
    if (n + 1 == c.nrows) break;
    phase1<RANK, 1, false>(c, n + 1, r);
    phase2<RANK, 1>(c, n + 1, r);
    if (n + 2 == c.nrows) break;
    phase1<RANK, 0, false>(c, n + 2, r);
  }
  finish_strip<RANK>(c, r, (c.nrows - 1) & 1);
}

constexpr int NCL = 66;
struct Strip { int seg, h0, nrows; };
__device__ __forceinline__ bool is_down(int cl) { return cl < 2 || !((cl - 2) & 4); }
__device__ __forceinline__ Strip get_strip(int cl, int wg) {
  const int k = cl - 2, i = k >> 2;
  const int q = (i & 1) ? (wg ? 16 + 15 * i : 16 * i + 16) : (wg ? 30 + 15 * i : 16 * i - 1);
  return cl < 2 ? Strip{2 * cl + wg, -1, 16} : Strip{k & 3, 2 * q + wg, 16 - wg};
}

__device__ __forceinline__ void load_rows(const CUtensorMap* xmap, const char* x, uint32_t sbase, int rank, int wg, Strip sp, int hstep) {
  const uint32_t full = sbase + OFF_BAR + 8 * (BAR_FULL + 2 * wg), empty = full + 8 * (BAR_EMPTY - BAR_FULL);
  const uint32_t in_base = sbase + OFF_IN + wg * WG_IN_BYTES;
  const int halo = sp.seg != 3 * rank ? 6 : 0;
  const char* xseg = x + (sp.seg * 128 + (rank ? 64 : -halo)) * (CH * 2);
  const int pf_bytes = (64 + halo) * CH * 2;
#pragma unroll 1
  for (int m = 3; m <= sp.nrows + 2; m++) {
    const int s = m & 1, h = sp.h0 + m * hstep;
    mbar_wait(empty + 8 * s, ((m - 3) >> 1) & 1);
    if (m == 3) {
      asm volatile("mbarrier.arrive.shared::cluster.b64 _, [%0];" ::"r"((full + 8 * (BAR_XFREE - BAR_FULL)) ^ 0x01000000u) : "memory");
      asm volatile("mbarrier.arrive.shared::cluster.b64 _, [%0];" ::"r"((full + 8 * (BAR_XFREE - BAR_FULL + 1)) ^ 0x01000000u) : "memory");
    }
    if (m < sp.nrows + 2) {
      const int hp = h + hstep;
      const bool pf = m >= 4 + PF_START && m + 1 < sp.nrows + 2 && (unsigned)hp < (unsigned)IMG_H;
      mbar_expect_tx(full + 8 * s, 2 * BOX_BYTES + XBUF_BYTES);
      tma_load5(in_base + s * STAGE_BYTES, xmap, full + 8 * s, rank * 48, 0, sp.seg * 16, 0, h);
      tma_load5(in_base + s * STAGE_BYTES + OFF_BOXB, xmap, full + 8 * s, rank * 48, 2, sp.seg * 16 - 1, 0, h);
      if (pf) asm volatile("cp.async.bulk.prefetch.L2.global [%0], %1;" ::"l"(xseg + (size_t)hp * (IMG_W * CH * 2)), "r"(pf_bytes) : "memory");
    } else {
      mbar_expect_tx(full + 8 * s, XBUF_BYTES);
    }
  }
}
__device__ __forceinline__ void store_rows(const CUtensorMap* omap, uint32_t sbase, int rank, int wg, Strip sp, int hstep) {
  const uint32_t full = sbase + OFF_BAR + 8 * (BAR_FULL + 2 * wg), staged = full + 8 * (BAR_STAGED - BAR_FULL);
#pragma unroll 1
  for (int n = 0; n < sp.nrows - 1; n++) {
    const int b = n & 1;
    mbar_wait(staged + 8 * b, ((n + 1) >> 1) & 1);
    tma_store5(omap, sbase + OFF_X + (2 * wg + b) * XBUF_BYTES, 0, sp.seg * 16, 0, rank, sp.h0 + (n + 1) * hstep);
    asm volatile("cp.async.bulk.wait_group.read 0;" ::: "memory");
    if (n + 2 < sp.nrows) asm volatile("mbarrier.arrive.shared::cluster.b64 _, [%0];" ::"r"((full + 8 * (BAR_XFREE - BAR_FULL + b)) ^ 0x01000000u) : "memory");
  }
}

__global__ void __cluster_dims__(2, 1, 1) __launch_bounds__(384, 1)
dilated_conv_wino_kernel(const __grid_constant__ CUtensorMap xmap, const __grid_constant__ CUtensorMap omap,
                         const __nv_bfloat16* __restrict__ x, const __nv_bfloat16* __restrict__ w, __nv_bfloat16* __restrict__ out,
                         uint32_t zero) {
  extern __shared__ uint8_t smem_raw[];
  const int tid = threadIdx.x;
  const int w12 = __shfl_sync(0xffffffff, tid >> 5, 0);
  const int wg = w12 >> 2, warp = w12 & 3;
  const int lane = tid & 31;
  const int rank = blockIdx.x & 1;
  const int cl = blockIdx.x >> 1;
  const bool down = is_down(cl);
  const uint32_t sbase = SMEM_BASE + (rank << 24);
  const uint32_t b0 = sbase + OFF_BAR;
  const uint32_t bar_w = b0 + 8 * BAR_W;

  if (w12 >= 9) {
    if (elect_one()) {
      const int a = w12 - 9, i = down ? a : 2 - a;
      const char* src = reinterpret_cast<const char*>(w) + (uint32_t)((i * 6 + rank) * (3 * BT_BYTES));
      const uint32_t dst = sbase + OFF_W + a * 3 * BT_BYTES;
      mbar_init(bar_w + 8 * a, 1);
      mbar_expect_tx(bar_w + 8 * a, 9 * BT_BYTES);
      bulk_load(dst + (rank ? 2 : 3) * 9 * BT_BYTES, src, 3 * BT_BYTES, bar_w + 8 * a);
      bulk_load(dst, src + 6 * BT_BYTES, 3 * BT_BYTES, bar_w + 8 * a);
      bulk_load(dst + (rank ? 3 : 2) * 9 * BT_BYTES, src + 12 * BT_BYTES, 3 * BT_BYTES, bar_w + 8 * a);
    }
  } else if (elect_one()) {
    if (w12 < 4) {
      mbar_init(b0 + 8 * (BAR_FULL + w12), 5);
      mbar_expect_tx(b0 + 8 * (BAR_FULL + w12), 2 * BOX_BYTES);
      asm volatile("mbarrier.arrive.shared::cta.b64 _, [%0], 4;" ::"r"(b0 + 8 * (BAR_FULL + w12)) : "memory");
    } else if (w12 < 8) {
      mbar_init(b0 + 8 * (BAR_EMPTY + warp), 4);
      mbar_init(b0 + 8 * (BAR_STAGED + warp), 4);
      mbar_init(b0 + 8 * (BAR_XFREE + warp), 1);
    } else {
#pragma unroll
      for (int q = 0; q < 2; q++) mbar_init(b0 + 8 * (BAR_ROW0 + q), 1);
      mbar_init(bar_w + 24, 12);
#pragma unroll
      for (int q = 0; q < 2; q++) mbar_expect_tx(b0 + 8 * (BAR_ROW0 + q), 2 * BOX_BYTES);
    }
    asm volatile("fence.mbarrier_init.release.cluster;" ::: "memory");
  }
  __syncthreads();
  asm volatile("barrier.cluster.arrive.relaxed.aligned;" ::: "memory");
  const Strip s0 = get_strip(cl, 0), s1 = get_strip(cl, 1);
  const int hstep = down ? 2 : -2;
  if (w12 == 8 || w12 == 9) {
    if (elect_one()) {
#pragma unroll 1
      for (uint32_t order = cl < 2 ? FIRST_ROWS_BORDER : FIRST_ROWS; order; order >>= 4) {
        const int g = (order >> 2) & 1, m = order & 3;
        const uint32_t dst = m == 0 ? sbase + (g ? OFF_ROW0_1 : OFF_ROW0_0) : sbase + OFF_IN + g * WG_IN_BYTES + (m & 1) * STAGE_BYTES;
        const uint32_t bar = b0 + 8 * (m == 0 ? BAR_ROW0 + g : BAR_FULL + 2 * g + (m & 1));
        tma_load5(dst + warp * OFF_BOXB, &xmap, bar, rank * 48, 2 * warp, (g ? s1.seg : s0.seg) * 16 - warp, 0, (g ? s1.h0 : s0.h0) + m * hstep);
      }
    }
    __syncwarp();
  }
  if ((uint32_t)__cvta_generic_to_shared(smem_raw) != sbase || mapa(sbase, rank ^ 1) != (sbase ^ 0x01000000u)) __trap();
  asm volatile("barrier.cluster.wait.aligned;" ::: "memory");
  transform_weights(sbase, rank, (wg == 0 ? WITEMS0 : wg == 1 ? WITEMS1 : WITEMS2) + warp * 0x010101u, lane);

  if (wg == 2) {
    asm volatile("setmaxnreg.dec.sync.aligned.u32 24;");
    if (elect_one()) {
      if (warp < 2) load_rows(&xmap, reinterpret_cast<const char*>(x), sbase, rank, warp, warp ? s1 : s0, hstep);
      else store_rows(&omap, sbase, rank, warp - 2, warp == 3 ? s1 : s0, hstep);
    }
  } else {
    asm volatile("setmaxnreg.inc.sync.aligned.u32 240;");
    Ctx c;
    c.out = reinterpret_cast<char*>(out);
    c.zero = zero;
    c.wg = wg;
    c.warp = warp;
    c.bar_full = b0 + 8 * (BAR_FULL + wg * NSTAGE);
    c.u0 = (wg ? s1.seg : s0.seg) * 16;
    c.h0 = wg ? s1.h0 : s0.h0;
    c.hstep = hstep;
    c.nrows = wg ? s1.nrows : s0.nrows;
    const uint32_t in_base = sbase + OFF_IN + wg * WG_IN_BYTES;
    {
      const int g = lane & 7, mi = lane >> 3;
      const int rU = 8 * warp + g + ((mi & 1) ? 34 : 0);
      const int rE = 8 * warp + g + ((mi & 1) ? 2 : 70 + 34);
      const uint32_t pU = in_base + rU * 128, pE = in_base + rE * 128;
      c.aU = pU + (((mi >> 1) ^ ((pU >> 7) & 7)) << 4);
      c.aE = pE + (((mi >> 1) ^ ((pE >> 7) & 7)) << 4);
    }
    c.xaddr = sbase + OFF_X + wg * 2 * XBUF_BYTES + (warp * 8 + (lane >> 2)) * 192 + (lane & 3) * 16;
    const uint32_t row0_off = sbase + (wg ? OFF_ROW0_1 : OFF_ROW0_0) - in_base;
    const uint32_t bar_row0 = cl < 2 ? bar_w : b0 + 8 * (BAR_ROW0 + wg);
    if (rank == 0) run_strip<0>(c, row0_off, bar_row0); else run_strip<1>(c, row0_off, bar_row0);
  }
}

typedef CUresult (*EncodeTiledFn)(CUtensorMap*, CUtensorMapDataType, cuuint32_t, void*, const cuuint64_t*, const cuuint64_t*,
                                  const cuuint32_t*, const cuuint32_t*, CUtensorMapInterleave, CUtensorMapSwizzle,
                                  CUtensorMapL2promotion, CUtensorMapFloatOOBfill);

}

extern "C" void kernel_launch(void* const* d_in, const int* in_sizes, int n_in, void* d_out, int out_size) {
  (void)in_sizes; (void)n_in; (void)out_size;
  static EncodeTiledFn encode = nullptr;
  if (!encode) {
    void* fn = nullptr;
    cudaDriverEntryPointQueryResult qr;
    cudaGetDriverEntryPoint("cuTensorMapEncodeTiled", &fn, cudaEnableDefault, &qr);
    encode = (EncodeTiledFn)fn;
    cudaFuncSetAttribute(dilated_conv_wino_kernel, cudaFuncAttributeMaxDynamicSharedMemorySize, SMEM_BYTES);
  }
  CUtensorMap xmap;
  const cuuint64_t dims[5] = {CH, 4, IMG_W / 8, 2, IMG_H};
  const cuuint64_t strides[4] = {CH * 2, 8 * CH * 2, 4 * CH * 2, IMG_W * CH * 2};
  const cuuint32_t box[5] = {48, 2, 17, 2, 1};
  const cuuint32_t estr[5] = {1, 1, 1, 1, 1};
  encode(&xmap, CU_TENSOR_MAP_DATA_TYPE_BFLOAT16, 5, d_in[0], dims, strides, box, estr, CU_TENSOR_MAP_INTERLEAVE_NONE,
         CU_TENSOR_MAP_SWIZZLE_128B, CU_TENSOR_MAP_L2_PROMOTION_L2_128B, CU_TENSOR_MAP_FLOAT_OOB_FILL_NONE);
  CUtensorMap omap;
  const cuuint64_t odims[5] = {2 * CH, IMG_W / 8, 2, 2, IMG_H};
  const cuuint64_t ostrides[4] = {8 * CH * 2, 4 * CH * 2, 2 * CH * 2, IMG_W * CH * 2};
  const cuuint32_t obox[5] = {2 * CH, 16, 2, 1, 1};
  encode(&omap, CU_TENSOR_MAP_DATA_TYPE_BFLOAT16, 5, d_out, odims, ostrides, obox, estr, CU_TENSOR_MAP_INTERLEAVE_NONE,
         CU_TENSOR_MAP_SWIZZLE_NONE, CU_TENSOR_MAP_L2_PROMOTION_NONE, CU_TENSOR_MAP_FLOAT_OOB_FILL_NONE);
  dilated_conv_wino_kernel<<<2 * NCL, 384, SMEM_BYTES>>>(xmap, omap, (const __nv_bfloat16*)d_in[0], (const __nv_bfloat16*)d_in[1], (__nv_bfloat16*)d_out, 0u);
}
```
